```python
import torch

def _softmax(x, axis=-1):
    return torch.softmax(x, dim=axis)
def _gelu(x):
    return torch.nn.functional.gelu(x, approximate="tanh")
def _silu(x):
    return torch.nn.functional.silu(x)
def _sigmoid(x):
    return torch.sigmoid(x)
def _layernorm(x, axis=-1, eps=1e-5):
    m = x.mean(dim=axis, keepdim=True)
    v = x.var(dim=axis, keepdim=True, unbiased=False)
    return (x - m) / torch.sqrt(v + eps)
def _scatter_add(tgt, idx, src, axis=0):
    return tgt.clone().index_add_(axis, idx, src)
def _segment_sum(src, seg, n):
    out = torch.zeros((n,) + src.shape[1:], dtype=src.dtype)
    return out.index_add_(0, seg, src)
def _pad(x, pw):
    flat = tuple(v for pair in reversed(pw) for v in pair)
    return torch.nn.functional.pad(x, flat)

kernel_name = 'standalone__gqa_softmax__near_ridge'

def setup_inputs():

    _w = (lambda a: (lambda t: t.to(torch.bfloat16) if t.is_floating_point() else t)(torch.as_tensor(a)))
    B, Hq, Hkv, Sq, Sk, D = 16, 32, 32, 848, 512, 192
    return {
        "q": _w((lambda *s: torch.randn(*s, dtype=torch.bfloat16) * 0.8)(B, Hq, Sq, D)),
        "k": _w((lambda *s: torch.randn(*s, dtype=torch.bfloat16) * 0.8)(B, Hkv, Sk, D)),
        "v": _w((lambda *s: torch.randn(*s, dtype=torch.bfloat16) * 0.05)(B, Hkv, Sk, D)),
    }

def reference(q, k, v):
    B, Hq, Sq, D = q.shape
    Hkv = k.shape[1]
    rep = Hq // Hkv
    k = (lambda x, n, axis: torch.repeat_interleave(x, n, dim=axis))(k, rep, axis=1)
    v = (lambda x, n, axis: torch.repeat_interleave(x, n, dim=axis))(v, rep, axis=1)
    scale = D ** -0.5
    scores = torch.einsum("bhqd,bhkd->bhqk", q, k) * scale
    p = _softmax(scores, axis=-1)
    return torch.einsum("bhqk,bhkd->bhqd", p, v)
```

```cpp
#include <cuda_runtime.h>
#include <cuda_bf16.h>
#include <cuda.h>
#include <stdint.h>

namespace {

constexpr int NHEADS = 512;
constexpr int SQ = 848;
constexpr int SK = 512;
constexpr int HD = 192;
constexpr int BN = 64;
constexpr int NBLK = SK / BN;
constexpr int SLOT = 64 * HD * 2;
constexpr int SLAB = 1024;
constexpr int RGRP = 3 * SLAB;
constexpr int NSLOT = 7;
constexpr int NROUNDS = (NHEADS / 2) * 7;
constexpr int NTHREADS = 384;
constexpr int OFF_QO = 0;
constexpr int OFF_KV = 2 * SLOT;
constexpr int OFF_QT = (2 + NSLOT) * SLOT;
constexpr int OFF_PT = OFF_QT + 3 * 2048;
constexpr int OFF_RED = OFF_PT + 2 * 2048;
constexpr int OFF_BAR = OFF_RED + 512;
constexpr int SMEM_BYTES = OFF_BAR + 256;

#define QDELAY 4
constexpr uint32_t WAIT_LIMIT = 1u << 18;
#define SUSPEND 20000
constexpr uint32_t SUSPEND_NS = SUSPEND;

constexpr float SCALE_LOG2 = 0.07216878364870322f * 1.4426950408889634f;
constexpr float SHIFT = 7.0f;
constexpr float TINY_SUM = 5.9604644775390625e-08f;

__device__ __forceinline__ uint32_t smem_u32(const void* p) { return (uint32_t)__cvta_generic_to_shared(p); }
__device__ __forceinline__ void wg_fence() { asm volatile("wgmma.fence.sync.aligned;" ::: "memory"); }
__device__ __forceinline__ void wg_commit() { asm volatile("wgmma.commit_group.sync.aligned;" ::: "memory"); }
template <int N> __device__ __forceinline__ void wg_wait() { asm volatile("wgmma.wait_group.sync.aligned %0;" ::"n"(N) : "memory"); }
template <int N> __device__ __forceinline__ void fence_regs(float (&r)[N]) {
#pragma unroll
  for (int i = 0; i < N; i++) asm volatile("" : "+f"(r[i])::"memory");
}
template <int N> __device__ __forceinline__ void fence_regs(uint32_t (&r)[N]) {
#pragma unroll
  for (int i = 0; i < N; i++) asm volatile("" : "+r"(r[i])::"memory");
}

__device__ __forceinline__ void mbar_init(uint32_t bar, uint32_t cnt) {
  asm volatile("mbarrier.init.shared::cta.b64 [%0], %1;" ::"r"(bar), "r"(cnt));
}
__device__ __forceinline__ void mbar_expect_tx(uint32_t bar, uint32_t bytes) {
  asm volatile("mbarrier.arrive.expect_tx.shared::cta.b64 _, [%0], %1;" ::"r"(bar), "r"(bytes) : "memory");
}
__device__ __forceinline__ void mbar_arrive(uint32_t bar) {
  asm volatile("mbarrier.arrive.shared::cta.b64 _, [%0];" ::"r"(bar) : "memory");
}
__device__ __forceinline__ bool mbar_try(uint32_t bar, uint32_t parity) {
  uint32_t ok;
  asm volatile(
      "{\n.reg .pred p;\nmbarrier.try_wait.parity.shared::cta.b64 p, [%1], %2;\nselp.b32 %0, 1, 0, p;\n}\n"
      : "=r"(ok)
      : "r"(bar), "r"(parity)
      : "memory");
  return ok;
}
__device__ __forceinline__ bool mbar_try_sleep(uint32_t bar, uint32_t parity) {
  uint32_t ok;
  asm volatile(
      "{\n.reg .pred p;\nmbarrier.try_wait.parity.shared::cta.b64 p, [%1], %2, %3;\nselp.b32 %0, 1, 0, p;\n}\n"
      : "=r"(ok)
      : "r"(bar), "r"(parity), "r"(SUSPEND_NS)
      : "memory");
  return ok;
}
__device__ __forceinline__ bool mbar_test(uint32_t bar, uint32_t parity) {
  uint32_t ok;
  asm volatile(
      "{\n.reg .pred p;\nmbarrier.test_wait.parity.shared::cta.b64 p, [%1], %2;\nselp.b32 %0, 1, 0, p;\n}\n"
      : "=r"(ok)
      : "r"(bar), "r"(parity)
      : "memory");
  return ok;
}
__device__ __forceinline__ void mbar_wait(uint32_t bar, uint32_t parity) {
  if (mbar_try(bar, parity)) return;
  for (uint32_t n = 0; n < WAIT_LIMIT; n++)
    if (mbar_try(bar, parity)) break;
}
__device__ __forceinline__ void mbar_wait_sleep(uint32_t bar, uint32_t parity) {
  for (uint32_t n = 0; n < WAIT_LIMIT; n++) {
    if (mbar_try_sleep(bar, parity)) break;
  }
}

__device__ __forceinline__ void tma_load(uint32_t dst, const CUtensorMap* tm, uint32_t bar, int row, int head, uint64_t pol) {
  asm volatile(
      "cp.async.bulk.tensor.5d.shared::cluster.global.mbarrier::complete_tx::bytes.L2::cache_hint"
      " [%0], [%1, {%3, %3, %3, %4, %5}], [%2], %6;" ::"r"(dst),
      "l"(tm), "r"(bar), "r"(0), "r"(row >> 3), "r"(head), "l"(pol)
      : "memory");
}
__device__ __forceinline__ void tma_load_mc(uint32_t dst, const CUtensorMap* tm, uint32_t bar, int row, int head, uint64_t pol) {
  asm volatile(
      "cp.async.bulk.tensor.5d.shared::cluster.global.mbarrier::complete_tx::bytes.multicast::cluster.L2::cache_hint"
      " [%0], [%1, {%3, %3, %3, %4, %5}], [%2], %7, %6;" ::"r"(dst),
      "l"(tm), "r"(bar), "r"(0), "r"(row >> 3), "r"(head), "l"(pol), "h"((uint16_t)3)
      : "memory");
}
__device__ __forceinline__ void tma_store(const CUtensorMap* tm, uint32_t src, int row, int head, uint64_t pol) {
  asm volatile(
      "cp.async.bulk.tensor.5d.global.shared::cta.bulk_group.L2::cache_hint"
      " [%0, {%2, %2, %2, %3, %4}], [%1], %5;" ::"l"(tm),
      "r"(src), "r"(0), "r"(row >> 3), "r"(head), "l"(pol)
      : "memory");
}
__device__ __forceinline__ void ldsm_x4(uint32_t addr, uint32_t& r0, uint32_t& r1, uint32_t& r2, uint32_t& r3) {
  asm volatile("ldmatrix.sync.aligned.m8n8.x4.shared.b16 {%0, %1, %2, %3}, [%4];"
               : "=r"(r0), "=r"(r1), "=r"(r2), "=r"(r3)
               : "r"(addr)
               : "memory");
}
__device__ __forceinline__ void stsm_x4(uint32_t addr, uint32_t r0, uint32_t r1, uint32_t r2, uint32_t r3) {
  asm volatile("stmatrix.sync.aligned.m8n8.x4.shared.b16 [%0], {%1, %2, %3, %4};" ::"r"(addr), "r"(r0), "r"(r1), "r"(r2), "r"(r3)
               : "memory");
}
__device__ __forceinline__ void stsm_x4_trans(uint32_t addr, uint32_t r0, uint32_t r1, uint32_t r2, uint32_t r3) {
  asm volatile("stmatrix.sync.aligned.m8n8.x4.trans.shared.b16 [%0], {%1, %2, %3, %4};" ::"r"(addr), "r"(r0), "r"(r1), "r"(r2), "r"(r3)
               : "memory");
}
__device__ __forceinline__ float ex2(float x) {
  float y;
  asm("ex2.approx.ftz.f32 %0, %1;" : "=f"(y) : "f"(x));
  return y;
}
__device__ __forceinline__ float rcp(float x) {
  float y;
  asm("rcp.approx.ftz.f32 %0, %1;" : "=f"(y) : "f"(x));
  return y;
}
__device__ __forceinline__ uint32_t pack_bf16(float lo, float hi) {
  uint32_t r;
  asm("cvt.rn.bf16x2.f32 %0, %1, %2;" : "=r"(r) : "f"(hi), "f"(lo));
  return r;
}
__device__ __forceinline__ void wgmma_qk(float (&d)[32], uint32_t a0, uint32_t a1, uint32_t a2, uint32_t a3, uint64_t db, int scale_d) {
  asm volatile("{\n.reg .pred p;\nsetp.ne.b32 p, %37, 0;\n"
    "wgmma.mma_async.sync.aligned.m64n64k16.f32.bf16.bf16 "
    "{%0, %1, %2, %3, %4, %5, %6, %7, %8, %9, %10, %11, %12, %13, %14, %15, %16, %17, %18, %19, %20, %21, %22, %23, %24, %25, %26, %27, %28, %29, %30, %31}, "
    "{%32, %33, %34, %35}, %36, p, 1, 1, 0;\n}\n"
    : "+f"(d[0]), "+f"(d[1]), "+f"(d[2]), "+f"(d[3]), "+f"(d[4]), "+f"(d[5]), "+f"(d[6]), "+f"(d[7]), "+f"(d[8]), "+f"(d[9]), "+f"(d[10]), "+f"(d[11]), "+f"(d[12]), "+f"(d[13]), "+f"(d[14]), "+f"(d[15]), "+f"(d[16]), "+f"(d[17]), "+f"(d[18]), "+f"(d[19]), "+f"(d[20]), "+f"(d[21]), "+f"(d[22]), "+f"(d[23]), "+f"(d[24]), "+f"(d[25]), "+f"(d[26]), "+f"(d[27]), "+f"(d[28]), "+f"(d[29]), "+f"(d[30]), "+f"(d[31])
    : "r"(a0), "r"(a1), "r"(a2), "r"(a3), "l"(db), "r"(scale_d));
}

__device__ __forceinline__ void wgmma_pv(float (&d)[96], uint32_t a0, uint32_t a1, uint32_t a2, uint32_t a3, uint64_t db, int scale_d) {
  asm volatile("{\n.reg .pred p;\nsetp.ne.b32 p, %101, 0;\n"
    "wgmma.mma_async.sync.aligned.m64n192k16.f32.bf16.bf16 "
    "{%0, %1, %2, %3, %4, %5, %6, %7, %8, %9, %10, %11, %12, %13, %14, %15, %16, %17, %18, %19, %20, %21, %22, %23, %24, %25, %26, %27, %28, %29, %30, %31, %32, %33, %34, %35, %36, %37, %38, %39, %40, %41, %42, %43, %44, %45, %46, %47, %48, %49, %50, %51, %52, %53, %54, %55, %56, %57, %58, %59, %60, %61, %62, %63, %64, %65, %66, %67, %68, %69, %70, %71, %72, %73, %74, %75, %76, %77, %78, %79, %80, %81, %82, %83, %84, %85, %86, %87, %88, %89, %90, %91, %92, %93, %94, %95}, "
    "{%96, %97, %98, %99}, %100, p, 1, 1, 1;\n}\n"
    : "+f"(d[0]), "+f"(d[1]), "+f"(d[2]), "+f"(d[3]), "+f"(d[4]), "+f"(d[5]), "+f"(d[6]), "+f"(d[7]), "+f"(d[8]), "+f"(d[9]), "+f"(d[10]), "+f"(d[11]), "+f"(d[12]), "+f"(d[13]), "+f"(d[14]), "+f"(d[15]), "+f"(d[16]), "+f"(d[17]), "+f"(d[18]), "+f"(d[19]), "+f"(d[20]), "+f"(d[21]), "+f"(d[22]), "+f"(d[23]), "+f"(d[24]), "+f"(d[25]), "+f"(d[26]), "+f"(d[27]), "+f"(d[28]), "+f"(d[29]), "+f"(d[30]), "+f"(d[31]), "+f"(d[32]), "+f"(d[33]), "+f"(d[34]), "+f"(d[35]), "+f"(d[36]), "+f"(d[37]), "+f"(d[38]), "+f"(d[39]), "+f"(d[40]), "+f"(d[41]), "+f"(d[42]), "+f"(d[43]), "+f"(d[44]), "+f"(d[45]), "+f"(d[46]), "+f"(d[47]), "+f"(d[48]), "+f"(d[49]), "+f"(d[50]), "+f"(d[51]), "+f"(d[52]), "+f"(d[53]), "+f"(d[54]), "+f"(d[55]), "+f"(d[56]), "+f"(d[57]), "+f"(d[58]), "+f"(d[59]), "+f"(d[60]), "+f"(d[61]), "+f"(d[62]), "+f"(d[63]), "+f"(d[64]), "+f"(d[65]), "+f"(d[66]), "+f"(d[67]), "+f"(d[68]), "+f"(d[69]), "+f"(d[70]), "+f"(d[71]), "+f"(d[72]), "+f"(d[73]), "+f"(d[74]), "+f"(d[75]), "+f"(d[76]), "+f"(d[77]), "+f"(d[78]), "+f"(d[79]), "+f"(d[80]), "+f"(d[81]), "+f"(d[82]), "+f"(d[83]), "+f"(d[84]), "+f"(d[85]), "+f"(d[86]), "+f"(d[87]), "+f"(d[88]), "+f"(d[89]), "+f"(d[90]), "+f"(d[91]), "+f"(d[92]), "+f"(d[93]), "+f"(d[94]), "+f"(d[95])
    : "r"(a0), "r"(a1), "r"(a2), "r"(a3), "l"(db), "r"(scale_d));
}

__device__ __forceinline__ void wgmma_qkT(float (&d)[8], uint64_t da, uint64_t db, int scale_d) {
  asm volatile("{\n.reg .pred p;\nsetp.ne.b32 p, %10, 0;\n"
    "wgmma.mma_async.sync.aligned.m64n16k16.f32.bf16.bf16 "
    "{%0, %1, %2, %3, %4, %5, %6, %7}, "
    "%8, %9, p, 1, 1, 0, 0;\n}\n"
    : "+f"(d[0]), "+f"(d[1]), "+f"(d[2]), "+f"(d[3]), "+f"(d[4]), "+f"(d[5]), "+f"(d[6]), "+f"(d[7])
    : "l"(da), "l"(db), "r"(scale_d));
}
__device__ __forceinline__ void wgmma_pvT(float (&d)[8], uint64_t da, uint64_t db, int scale_d) {
  asm volatile("{\n.reg .pred p;\nsetp.ne.b32 p, %10, 0;\n"
    "wgmma.mma_async.sync.aligned.m64n16k16.f32.bf16.bf16 "
    "{%0, %1, %2, %3, %4, %5, %6, %7}, "
    "%8, %9, p, 1, 1, 1, 0;\n}\n"
    : "+f"(d[0]), "+f"(d[1]), "+f"(d[2]), "+f"(d[3]), "+f"(d[4]), "+f"(d[5]), "+f"(d[6]), "+f"(d[7])
    : "l"(da), "l"(db), "r"(scale_d));
}

__device__ __forceinline__ void wgmma_qk0(float (&d)[32], uint32_t a0, uint32_t a1, uint32_t a2, uint32_t a3, uint64_t db) {
  asm volatile("{\n.reg .pred p;\nsetp.ne.b32 p, 0, 0;\n"
    "wgmma.mma_async.sync.aligned.m64n64k16.f32.bf16.bf16 "
    "{%0, %1, %2, %3, %4, %5, %6, %7, %8, %9, %10, %11, %12, %13, %14, %15, %16, %17, %18, %19, %20, %21, %22, %23, %24, %25, %26, %27, %28, %29, %30, %31}, "
    "{%32, %33, %34, %35}, %36, p, 1, 1, 0;\n}\n"
    : "=f"(d[0]), "=f"(d[1]), "=f"(d[2]), "=f"(d[3]), "=f"(d[4]), "=f"(d[5]), "=f"(d[6]), "=f"(d[7]), "=f"(d[8]), "=f"(d[9]), "=f"(d[10]), "=f"(d[11]), "=f"(d[12]), "=f"(d[13]), "=f"(d[14]), "=f"(d[15]), "=f"(d[16]), "=f"(d[17]), "=f"(d[18]), "=f"(d[19]), "=f"(d[20]), "=f"(d[21]), "=f"(d[22]), "=f"(d[23]), "=f"(d[24]), "=f"(d[25]), "=f"(d[26]), "=f"(d[27]), "=f"(d[28]), "=f"(d[29]), "=f"(d[30]), "=f"(d[31])
    : "r"(a0), "r"(a1), "r"(a2), "r"(a3), "l"(db));
}
__device__ __forceinline__ void wgmma_pv0(float (&d)[96], uint32_t a0, uint32_t a1, uint32_t a2, uint32_t a3, uint64_t db) {
  asm volatile("{\n.reg .pred p;\nsetp.ne.b32 p, 0, 0;\n"
    "wgmma.mma_async.sync.aligned.m64n192k16.f32.bf16.bf16 "
    "{%0, %1, %2, %3, %4, %5, %6, %7, %8, %9, %10, %11, %12, %13, %14, %15, %16, %17, %18, %19, %20, %21, %22, %23, %24, %25, %26, %27, %28, %29, %30, %31, %32, %33, %34, %35, %36, %37, %38, %39, %40, %41, %42, %43, %44, %45, %46, %47, %48, %49, %50, %51, %52, %53, %54, %55, %56, %57, %58, %59, %60, %61, %62, %63, %64, %65, %66, %67, %68, %69, %70, %71, %72, %73, %74, %75, %76, %77, %78, %79, %80, %81, %82, %83, %84, %85, %86, %87, %88, %89, %90, %91, %92, %93, %94, %95}, "
    "{%96, %97, %98, %99}, %100, p, 1, 1, 1;\n}\n"
    : "=f"(d[0]), "=f"(d[1]), "=f"(d[2]), "=f"(d[3]), "=f"(d[4]), "=f"(d[5]), "=f"(d[6]), "=f"(d[7]), "=f"(d[8]), "=f"(d[9]), "=f"(d[10]), "=f"(d[11]), "=f"(d[12]), "=f"(d[13]), "=f"(d[14]), "=f"(d[15]), "=f"(d[16]), "=f"(d[17]), "=f"(d[18]), "=f"(d[19]), "=f"(d[20]), "=f"(d[21]), "=f"(d[22]), "=f"(d[23]), "=f"(d[24]), "=f"(d[25]), "=f"(d[26]), "=f"(d[27]), "=f"(d[28]), "=f"(d[29]), "=f"(d[30]), "=f"(d[31]), "=f"(d[32]), "=f"(d[33]), "=f"(d[34]), "=f"(d[35]), "=f"(d[36]), "=f"(d[37]), "=f"(d[38]), "=f"(d[39]), "=f"(d[40]), "=f"(d[41]), "=f"(d[42]), "=f"(d[43]), "=f"(d[44]), "=f"(d[45]), "=f"(d[46]), "=f"(d[47]), "=f"(d[48]), "=f"(d[49]), "=f"(d[50]), "=f"(d[51]), "=f"(d[52]), "=f"(d[53]), "=f"(d[54]), "=f"(d[55]), "=f"(d[56]), "=f"(d[57]), "=f"(d[58]), "=f"(d[59]), "=f"(d[60]), "=f"(d[61]), "=f"(d[62]), "=f"(d[63]), "=f"(d[64]), "=f"(d[65]), "=f"(d[66]), "=f"(d[67]), "=f"(d[68]), "=f"(d[69]), "=f"(d[70]), "=f"(d[71]), "=f"(d[72]), "=f"(d[73]), "=f"(d[74]), "=f"(d[75]), "=f"(d[76]), "=f"(d[77]), "=f"(d[78]), "=f"(d[79]), "=f"(d[80]), "=f"(d[81]), "=f"(d[82]), "=f"(d[83]), "=f"(d[84]), "=f"(d[85]), "=f"(d[86]), "=f"(d[87]), "=f"(d[88]), "=f"(d[89]), "=f"(d[90]), "=f"(d[91]), "=f"(d[92]), "=f"(d[93]), "=f"(d[94]), "=f"(d[95])
    : "r"(a0), "r"(a1), "r"(a2), "r"(a3), "l"(db));
}
__device__ __forceinline__ void wgmma_qkT0(float (&d)[8], uint64_t da, uint64_t db) {
  asm volatile("{\n.reg .pred p;\nsetp.ne.b32 p, 0, 0;\n"
    "wgmma.mma_async.sync.aligned.m64n16k16.f32.bf16.bf16 "
    "{%0, %1, %2, %3, %4, %5, %6, %7}, "
    "%8, %9, p, 1, 1, 0, 0;\n}\n"
    : "=f"(d[0]), "=f"(d[1]), "=f"(d[2]), "=f"(d[3]), "=f"(d[4]), "=f"(d[5]), "=f"(d[6]), "=f"(d[7])
    : "l"(da), "l"(db));
}
__device__ __forceinline__ void wgmma_pvT0(float (&d)[8], uint64_t da, uint64_t db) {
  asm volatile("{\n.reg .pred p;\nsetp.ne.b32 p, 0, 0;\n"
    "wgmma.mma_async.sync.aligned.m64n16k16.f32.bf16.bf16 "
    "{%0, %1, %2, %3, %4, %5, %6, %7}, "
    "%8, %9, p, 1, 1, 1, 0;\n}\n"
    : "=f"(d[0]), "=f"(d[1]), "=f"(d[2]), "=f"(d[3]), "=f"(d[4]), "=f"(d[5]), "=f"(d[6]), "=f"(d[7])
    : "l"(da), "l"(db));
}

struct Round { int head, qrow, mc; };
__device__ __forceinline__ Round decode_round(int g, int rank) {
  int p = g / 7, r = g - p * 7;
  Round o;
  if (r < 3) { o.head = 2 * p; o.qrow = r * 256 + rank * 128; o.mc = 1; }
  else if (r == 3) { o.head = 2 * p + rank; o.qrow = 768; o.mc = 0; }
  else { o.head = 2 * p + 1; o.qrow = (r - 4) * 256 + rank * 128; o.mc = 1; }
  return o;
}

__device__ __forceinline__ uint32_t kdesc0(uint32_t s_kv) { return ((s_kv & 0x3FFFFu) >> 4) | (1u << 16); }
__device__ __forceinline__ uint32_t vdesc0(uint32_t s_kv) { return ((s_kv & 0x3FFFFu) >> 4) | ((uint32_t)(SLAB >> 4) << 16); }
constexpr uint64_t DESC_HI = ((uint64_t)(RGRP >> 4) << 32) | ((uint64_t)1 << 62);
constexpr uint64_t DESC_HI_PT = ((uint64_t)(1024 >> 4) << 32) | ((uint64_t)1 << 62);

__device__ __forceinline__ void issue_qk(float (&S)[32], const uint32_t (&Q)[48], uint32_t kdesc) {
  const uint64_t d = DESC_HI | kdesc;
  wgmma_qk0(S, Q[0], Q[1], Q[2], Q[3], d);
#pragma unroll
  for (int kk = 1; kk < 12; kk++)
    wgmma_qk(S, Q[kk * 4], Q[kk * 4 + 1], Q[kk * 4 + 2], Q[kk * 4 + 3], d + (uint64_t)((kk / 4) * (SLAB / 16) + (kk % 4) * 2), 1);
}
__device__ __forceinline__ void issue_qk3(float (&S)[32], const uint32_t (&Q)[48], uint32_t kdesc) {
  const uint64_t d = DESC_HI | kdesc;
  wgmma_qk0(S, Q[0], Q[1], Q[2], Q[3], d);
#pragma unroll
  for (int kk = 1; kk < 12; kk++) {
    if (kk % 4 == 0) wg_commit();
    wgmma_qk(S, Q[kk * 4], Q[kk * 4 + 1], Q[kk * 4 + 2], Q[kk * 4 + 3], d + (uint64_t)((kk / 4) * (SLAB / 16) + (kk % 4) * 2), 1);
  }
}
template <bool ACCUMULATE>
__device__ __forceinline__ void issue_pv(float (&O)[96], const uint32_t (&P)[16], uint32_t vdesc) {
  const uint64_t d = DESC_HI | vdesc;
  if (ACCUMULATE) wgmma_pv(O, P[0], P[1], P[2], P[3], d, 1);
  else wgmma_pv0(O, P[0], P[1], P[2], P[3], d);
#pragma unroll
  for (int kk = 1; kk < 4; kk++)
    wgmma_pv(O, P[kk * 4], P[kk * 4 + 1], P[kk * 4 + 2], P[kk * 4 + 3], d + (uint64_t)(kk * (2 * RGRP / 16)), 1);
}

template <int K0 = 0, int K1 = 12>
__device__ __forceinline__ void load_q(uint32_t (&Q)[48], uint32_t lane_addr) {
#pragma unroll
  for (int kk = K0; kk < K1; kk++)
    ldsm_x4((lane_addr ^ ((kk % 4) << 5)) + (kk / 4) * SLAB, Q[kk * 4], Q[kk * 4 + 1], Q[kk * 4 + 2], Q[kk * 4 + 3]);
}

__device__ __forceinline__ void exp_block(const float (&S)[32], uint32_t (&P)[16], float mc0, float mc1, float& s0, float& s1) {
  s0 = 0.f; s1 = 0.f;
#pragma unroll
  for (int i = 0; i < 8; i++) {
    float a = ex2(fmaf(S[4 * i + 0], SCALE_LOG2, -mc0));
    float b = ex2(fmaf(S[4 * i + 1], SCALE_LOG2, -mc0));
    float c = ex2(fmaf(S[4 * i + 2], SCALE_LOG2, -mc1));
    float d = ex2(fmaf(S[4 * i + 3], SCALE_LOG2, -mc1));
    s0 += a + b;
    s1 += c + d;
    P[2 * i] = pack_bf16(a, b);
    P[2 * i + 1] = pack_bf16(c, d);
  }
}

struct Softmax {
  float mc0, mc1;
  float l0, l1;
};

__device__ __forceinline__ void softmax_slow(const float (&S)[32], uint32_t (&P)[16], float (&O)[96], Softmax& st, bool first, float& s0, float& s1) {
  float m0 = fmaxf(S[0], S[1]), m1 = fmaxf(S[2], S[3]);
#pragma unroll
  for (int i = 1; i < 8; i++) {
    m0 = fmaxf(m0, fmaxf(S[4 * i], S[4 * i + 1]));
    m1 = fmaxf(m1, fmaxf(S[4 * i + 2], S[4 * i + 3]));
  }
  m0 = fmaxf(m0, __shfl_xor_sync(0xffffffffu, m0, 1));
  m1 = fmaxf(m1, __shfl_xor_sync(0xffffffffu, m1, 1));
  m0 = fmaxf(m0, __shfl_xor_sync(0xffffffffu, m0, 2));
  m1 = fmaxf(m1, __shfl_xor_sync(0xffffffffu, m1, 2));
  float n0 = fmaf(m0, SCALE_LOG2, SHIFT), n1 = fmaf(m1, SCALE_LOG2, SHIFT);
  if (!first) {
    n0 = fmaxf(n0, st.mc0); n1 = fmaxf(n1, st.mc1);
    const float f0 = ex2(st.mc0 - n0), f1 = ex2(st.mc1 - n1);
    st.l0 *= f0; st.l1 *= f1;
    wg_wait<0>();
    fence_regs(O);
#pragma unroll
    for (int i = 0; i < 24; i++) {
      O[4 * i] *= f0; O[4 * i + 1] *= f0; O[4 * i + 2] *= f1; O[4 * i + 3] *= f1;
    }
  }
  st.mc0 = n0; st.mc1 = n1;
  exp_block(S, P, n0, n1, s0, s1);
}

__device__ __forceinline__ void softmax_block(const float (&S)[32], uint32_t (&P)[16], float (&O)[96], Softmax& st, bool first,
                                              bool fetch_q, uint32_t (&Q)[48], uint32_t lane_addr) {
  float s0, s1;
  if (fetch_q) load_q<8, 12>(Q, lane_addr);
  exp_block(S, P, st.mc0, st.mc1, s0, s1);
  bool bad = !(s0 < 2.0f && s1 < 2.0f);
  if (first) {
    bad = bad || !(s0 >= TINY_SUM && s1 >= TINY_SUM);
    st.l0 = 0.f; st.l1 = 0.f;
  }
  if (__builtin_expect(__any_sync(0xffffffffu, bad), 0)) softmax_slow(S, P, O, st, first, s0, s1);
  st.l0 += s0; st.l1 += s1;
}

__device__ __forceinline__ void row_norm(float l0, float l1, float& i0, float& i1) {
  l0 += __shfl_xor_sync(0xffffffffu, l0, 1);
  l1 += __shfl_xor_sync(0xffffffffu, l1, 1);
  l0 += __shfl_xor_sync(0xffffffffu, l0, 2);
  l1 += __shfl_xor_sync(0xffffffffu, l1, 2);
  i0 = rcp(l0); i1 = rcp(l1);
  asm volatile("" : "+f"(i0), "+f"(i1)::"memory");
}
template <int K0, int K1>
__device__ __forceinline__ void epilogue_part(const float (&O)[96], float i0, float i1, uint32_t lane_addr) {
#pragma unroll
  for (int kk = K0; kk < K1; kk++) {
    const int b = kk * 8;
    stsm_x4((lane_addr ^ ((kk % 4) << 5)) + (kk / 4) * SLAB,
            pack_bf16(O[b] * i0, O[b + 1] * i0), pack_bf16(O[b + 2] * i1, O[b + 3] * i1),
            pack_bf16(O[b + 4] * i0, O[b + 5] * i0), pack_bf16(O[b + 6] * i1, O[b + 7] * i1));
  }
}
__device__ __forceinline__ void epilogue_done(uint32_t bar, int lane) {
  __syncwarp();
  if (lane == 0) mbar_arrive(bar);
}

struct TailState { float mc[4]; float l[4]; };

__device__ __forceinline__ uint32_t wg_barrier_or(bool pred) {
  uint32_t r;
  asm volatile("{\n.reg .pred p, q;\nsetp.ne.b32 q, %1, 0;\nbar.red.or.pred p, 3, 128, q;\nselp.b32 %0, 1, 0, p;\n}\n"
               : "=r"(r) : "r"((uint32_t)pred) : "memory");
  return r;
}
__device__ __forceinline__ void wg_barrier() { asm volatile("bar.sync 3, 128;" ::: "memory"); }

template <bool MAX>
__device__ __forceinline__ void tail_reduce(float (&v)[4], uint32_t red, int warp, int lane) {
#pragma unroll
  for (int o = 4; o < 32; o <<= 1)
#pragma unroll
    for (int i = 0; i < 4; i++) {
      const float x = __shfl_xor_sync(0xffffffffu, v[i], o);
      v[i] = MAX ? fmaxf(v[i], x) : v[i] + x;
    }
  if (lane < 4)
    asm volatile("st.shared.v4.f32 [%0], {%1, %2, %3, %4};" ::"r"(red + (warp * 4 + lane) * 16), "f"(v[0]), "f"(v[1]), "f"(v[2]), "f"(v[3]) : "memory");
  wg_barrier();
#pragma unroll
  for (int ww = 0; ww < 4; ww++) {
    float x0, x1, x2, x3;
    asm volatile("ld.shared.v4.f32 {%0, %1, %2, %3}, [%4];" : "=f"(x0), "=f"(x1), "=f"(x2), "=f"(x3) : "r"(red + (ww * 4 + (lane & 3)) * 16) : "memory");
    if (ww == 0) { v[0] = x0; v[1] = x1; v[2] = x2; v[3] = x3; }
    else if (MAX) { v[0] = fmaxf(v[0], x0); v[1] = fmaxf(v[1], x1); v[2] = fmaxf(v[2], x2); v[3] = fmaxf(v[3], x3); }
    else { v[0] += x0; v[1] += x1; v[2] += x2; v[3] += x3; }
  }
}

__device__ __forceinline__ void tail_exp(const float (&S)[8], const TailState& ts, float (&s)[4], uint32_t pt_addr) {
  float e[8];
#pragma unroll
  for (int i = 0; i < 8; i++) e[i] = ex2(fmaf(S[i], SCALE_LOG2, -ts.mc[(i & 1) + (i >> 2) * 2]));
  s[0] = e[0] + e[2]; s[1] = e[1] + e[3]; s[2] = e[4] + e[6]; s[3] = e[5] + e[7];
  stsm_x4_trans(pt_addr, pack_bf16(e[0], e[1]), pack_bf16(e[2], e[3]), pack_bf16(e[4], e[5]), pack_bf16(e[6], e[7]));
  asm volatile("fence.proxy.async.shared::cta;" ::: "memory");
}

__device__ __forceinline__ void tail_softmax(const float (&S)[8], float (&O)[3][8], TailState& ts, bool first, uint32_t pt_addr,
                                             uint32_t red, int warp, int lane) {
  float s[4];
  bool redo = first;
  if (!first) {
    tail_exp(S, ts, s, pt_addr);
    redo = wg_barrier_or(!(s[0] < 2.0f && s[1] < 2.0f && s[2] < 2.0f && s[3] < 2.0f));
  }
  if (redo) {
    float m[4] = {fmaxf(S[0], S[2]), fmaxf(S[1], S[3]), fmaxf(S[4], S[6]), fmaxf(S[5], S[7])};
    tail_reduce<true>(m, red, warp, lane);
    if (!first) {
      wg_wait<0>();
      fence_regs(O[0]); fence_regs(O[1]); fence_regs(O[2]);
    }
#pragma unroll
    for (int i = 0; i < 4; i++) {
      float nn = fmaf(m[i], SCALE_LOG2, SHIFT);
      if (!first) {
        nn = fmaxf(nn, ts.mc[i]);
        const float f = ex2(ts.mc[i] - nn);
        ts.l[i] *= f;
#pragma unroll
        for (int b = 0; b < 3; b++) { O[b][(i & 1) + (i >> 1) * 4] *= f; O[b][(i & 1) + (i >> 1) * 4 + 2] *= f; }
      } else {
        ts.l[i] = 0.f;
      }
      ts.mc[i] = nn;
    }
    tail_exp(S, ts, s, pt_addr);
    wg_barrier();
  }
#pragma unroll
  for (int i = 0; i < 4; i++) ts.l[i] += s[i];
}

__device__ __forceinline__ void issue_qkT(float (&S8)[8], uint32_t kdesc, uint32_t qt_addr) {
  const uint64_t da = DESC_HI | kdesc;
  const uint64_t db = DESC_HI | (uint64_t)(((qt_addr & 0x3FFFFu) >> 4) | (1u << 16));
  wgmma_qkT0(S8, da, db);
#pragma unroll
  for (int kk = 1; kk < 12; kk++)
    wgmma_qkT(S8, da + (uint64_t)((kk / 4) * (SLAB / 16) + (kk % 4) * 2), db + (uint64_t)((kk / 4) * (SLAB / 16) + (kk % 4) * 2), 1);
}
template <bool ACCUMULATE>
__device__ __forceinline__ void issue_pvT(float (&O)[3][8], uint32_t vdesc, uint32_t pt_base) {
  const uint64_t da = DESC_HI | vdesc;
  const uint64_t db = DESC_HI_PT | (uint64_t)(((pt_base & 0x3FFFFu) >> 4) | (1u << 16));
#pragma unroll
  for (int kk = 0; kk < 4; kk++)
#pragma unroll
    for (int b = 0; b < 3; b++) {
      if (kk == 0 && !ACCUMULATE) wgmma_pvT0(O[b], da + (uint64_t)(b * (SLAB / 16)), db);
      else wgmma_pvT(O[b], da + (uint64_t)(b * (SLAB / 16) + kk * (2 * RGRP / 16)), db + (uint64_t)(kk * 2), 1);
    }
}

template <bool B> struct Bool { static constexpr bool value = B; };

constexpr int MAX_CLUSTERS = 72;
constexpr int MAX_ROUNDS = 32;
struct Schedule {
  uint32_t tails[MAX_CLUSTERS];
  uint16_t start[MAX_CLUSTERS + 1];
  uint16_t list[NROUNDS];
};

#define EV(k)
#define EV_STEP(n)

__global__ void __cluster_dims__(2, 1, 1) __launch_bounds__(NTHREADS, 1)
attn_kernel(const __grid_constant__ CUtensorMap tmQ, const __grid_constant__ CUtensorMap tmQT, const __grid_constant__ CUtensorMap tmK,
            const __grid_constant__ CUtensorMap tmV, const __grid_constant__ CUtensorMap tmO, const __grid_constant__ Schedule sched) {
  extern __shared__ __align__(1024) uint8_t smem_raw[];
  const uint32_t sbase = smem_u32(smem_raw);
  const uint32_t s_qo = sbase + OFF_QO;
  const uint32_t s_kv = sbase + OFF_KV;
  const uint32_t s_bar = sbase + OFF_BAR;
  const uint32_t bar_full = s_bar;
  const uint32_t bar_empty = s_bar + 8 * NSLOT;
  const uint32_t bar_qfull = s_bar + 16 * NSLOT;
  const uint32_t bar_ostg = bar_qfull + 16;
  const uint32_t bar_qreq = bar_ostg + 16;

  uint32_t rank;
  asm("mov.u32 %0, %%cluster_ctarank;" : "=r"(rank));
  const int cluster = blockIdx.x >> 1;
  const int first_round = sched.start[cluster];
  const int nrounds = sched.start[cluster + 1] - first_round;
  const int nblocks = nrounds * NBLK;

  if (threadIdx.x == 32) {
    asm volatile("prefetch.tensormap [%0];" ::"l"(&tmQ) : "memory");
    asm volatile("prefetch.tensormap [%0];" ::"l"(&tmK) : "memory");
    asm volatile("prefetch.tensormap [%0];" ::"l"(&tmV) : "memory");
  }
  if (threadIdx.x == 0) {
    for (int i = 0; i < NSLOT; i++) {
      mbar_init(bar_full + 8 * i, 1);
      mbar_init(bar_empty + 8 * i, 4);
    }
    for (int i = 0; i < 2; i++) {
      mbar_init(bar_qfull + 8 * i, 1);
      mbar_init(bar_ostg + 8 * i, 4);
      mbar_init(bar_qreq + 8 * i, 2);
    }
    asm volatile("fence.mbarrier_init.release.cluster;" ::: "memory");
  }
  __syncthreads();
  if (threadIdx.x == 32 || threadIdx.x == 64) {
    const int w = (threadIdx.x >> 5) - 1;
    uint64_t pol;
    asm volatile("createpolicy.fractional.L2::evict_first.b64 %0, 1.0;" : "=l"(pol));
    const Round r = decode_round(sched.list[first_round] & 0x7ff, rank);
    mbar_expect_tx(bar_qfull + 8 * w, SLOT);
    tma_load(s_qo + w * SLOT, &tmQ, bar_qfull + 8 * w, r.qrow + w * 64, r.head, pol);
  }
  asm volatile("barrier.cluster.arrive.relaxed.aligned;\nbarrier.cluster.wait.aligned;" ::: "memory");

  const int wg = __shfl_sync(0xffffffffu, threadIdx.x >> 7, 0);
  const int warp = __shfl_sync(0xffffffffu, (threadIdx.x >> 5) & 3, 0);
  const int lane = threadIdx.x & 31;

  if (wg == 0) {
    asm volatile("setmaxnreg.dec.sync.aligned.u32 24;");
    if (warp == 0 && lane == 0) {
      uint64_t pol;
      asm volatile("createpolicy.fractional.L2::evict_unchanged.b64 %0, 1.0;" : "=l"(pol));
      uint32_t slot = 0, phase = 1;
      auto load = [&](const CUtensorMap* tm, int n, uint32_t owner) {
        const Round r = decode_round(sched.list[first_round + (n >> 3)] & 0x7ff, rank);
        mbar_wait_sleep(bar_empty + 8 * slot, phase);
        mbar_expect_tx(bar_full + 8 * slot, SLOT);
        if (!r.mc) tma_load(s_kv + slot * SLOT, tm, bar_full + 8 * slot, (n & 7) * BN, r.head, pol);
        else if (rank == owner) tma_load_mc(s_kv + slot * SLOT, tm, bar_full + 8 * slot, (n & 7) * BN, r.head, pol);
        if (++slot == NSLOT) { slot = 0; phase ^= 1; }
      };
      load(&tmK, 0, 0);
      for (int n = 0; n < nblocks; n++) {
        load(&tmK, n + 1 < nblocks ? n + 1 : n, 0);
        load(&tmV, n, 1);
      }
      for (int i = 0; i < NSLOT; i++) {
        mbar_wait_sleep(bar_empty + 8 * slot, phase);
        if (++slot == NSLOT) { slot = 0; phase ^= 1; }
      }
    } else if ((warp == 1 || warp == 2) && lane == 0) {
      const int w = warp - 1;
      uint64_t pol;
      asm volatile("createpolicy.fractional.L2::evict_first.b64 %0, 1.0;" : "=l"(pol));
      const uint32_t buf = s_qo + w * SLOT;
      Round r = decode_round(sched.list[first_round] & 0x7ff, rank);
      Round prev = r;
      for (int t = 0; t <= nrounds; t++) {
        mbar_wait_sleep(bar_ostg + 8 * w, t & 1);
        if (t > 0) {
          asm volatile("fence.proxy.async.shared::cta;" ::: "memory");
          tma_store(&tmO, buf, prev.qrow + w * 64, prev.head, pol);
          asm volatile("cp.async.bulk.commit_group;" ::: "memory");
          asm volatile("cp.async.bulk.wait_group.read 0;" ::: "memory");
          prev = r;
        }
        if (t + 1 < nrounds) {
          mbar_wait_sleep(bar_qreq + 8 * w, t & 1);
          const uint32_t e = sched.list[first_round + t + 1];
          r = decode_round(e & 0x7ff, rank);
          if (w == 1 && (e & 0x8000)) {
            mbar_expect_tx(bar_qfull + 8 * w, 3 * 2048);
            tma_load(sbase + OFF_QT, &tmQT, bar_qfull + 8 * w, r.qrow + 64, r.head, pol);
          } else {
            mbar_expect_tx(bar_qfull + 8 * w, SLOT);
            tma_load(buf, &tmQ, bar_qfull + 8 * w, r.qrow + w * 64, r.head, pol);
          }
        }
      }
      asm volatile("cp.async.bulk.wait_group 0;" ::: "memory");
    }
  } else {
    asm volatile("setmaxnreg.inc.sync.aligned.u32 240;");
    const int w = wg - 1;
    float O[96], S[32];
    uint32_t Q[48], P0[16], P1[16];
    Softmax st;
    st.mc0 = st.mc1 = SHIFT; st.l0 = st.l1 = 0.f;
    const uint32_t lane_addr = s_qo + w * SLOT + (warp * 2 + ((lane >> 3) & 1)) * RGRP + (lane & 7) * 128 + (((lane >> 4) ^ (lane & 7)) << 4);
    const uint32_t my_qfull = bar_qfull + 8 * w, my_ostg = bar_ostg + 8 * w;

    uint32_t slot = 0, phase = 0;
    uint32_t empty_remote;
    asm("mapa.shared::cluster.u32 %0, %1, %2;" : "=r"(empty_remote) : "r"(bar_empty), "r"(threadIdx.x & 1));
    const bool releaser = (threadIdx.x & 127) < 2;
    auto release = [&](uint32_t s) {
      if (releaser) asm volatile("mbarrier.arrive.shared::cluster.b64 _, [%0];" ::"r"(empty_remote + s) : "memory");
    };
    uint32_t knext, vnext, kph, vph, kdnext, vdnext;
    const uint32_t kd0 = kdesc0(s_kv), vd0 = vdesc0(s_kv);
    bool landed;
    auto probe = [&]() {
      knext = slot; kph = phase;
      slot += 8; if (slot == 8 * NSLOT) { slot = 0; phase ^= 1; }
      vnext = slot; vph = phase;
      slot += 8; if (slot == 8 * NSLOT) { slot = 0; phase ^= 1; }
      kdnext = kd0 + knext * (SLOT / 128); vdnext = vd0 + vnext * (SLOT / 128);
      asm volatile("" : "+r"(knext), "+r"(vnext), "+r"(kph), "+r"(vph), "+r"(kdnext), "+r"(vdnext), "+r"(slot), "+r"(phase));
      landed = mbar_test(bar_full + knext, kph) & mbar_test(bar_full + vnext, vph);
    };
    auto ensure = [&]() {
      if (!landed)
        for (uint32_t i = 0; i < WAIT_LIMIT; i++)
          if (mbar_try(bar_full + knext, kph) & mbar_try(bar_full + vnext, vph)) break;
    };

    uint32_t tails = w == 1 ? sched.tails[cluster] : 0u;
    auto turn_wait = [&]() { asm volatile("bar.sync %0, 256;" ::"r"(1 + w) : "memory"); };
    auto turn_pass = [&]() { asm volatile("bar.arrive %0, 256;" ::"r"(2 - w) : "memory"); };
    if (w == 1) turn_pass();

    uint32_t kslot, vslot = 0, vprev, kd, vd;

    mbar_wait(my_qfull, 0);
    load_q(Q, lane_addr);
    kslot = slot;
    mbar_wait(bar_full + kslot, 0);
    slot = 8;
    wg_fence();
    issue_qk(S, Q, kd0);
    wg_commit();
    probe();
    wg_wait<0>();
    fence_regs(S);
    release(kslot);
    __syncwarp();
    if (lane == 0) mbar_arrive(my_ostg);
    bool pending = false;

    int n = 0;
    int exit_n = -1;
#pragma unroll 1
    while (true) {
    bool to_tail;
#pragma unroll 1
    do {
      const int j = n & 7;
      const int t = n >> 3;
      EV_STEP(n);
      EV(0);
      const float lp0 = st.l0, lp1 = st.l1;
      softmax_block(S, P0, O, st, j == 0, false, Q, lane_addr);
      EV(1);
      ensure();
      kslot = knext; kd = kdnext;
      vprev = vslot;
      vslot = vnext; vd = vdnext;
      fence_regs(P0);
      if (j != 0) {
        wg_wait<0>();
        release(vprev);
        turn_wait();
        wg_fence();
        EV(2);
        issue_qk3(S, Q, kd);
        wg_commit();
        EV(3);
        issue_pv<true>(O, P0, vd);
        wg_commit();
        EV(4);
        turn_pass();
        probe();
        if (j == QDELAY && releaser) mbar_arrive(bar_qreq + 8 * w);
        if (j == 6) {
          if (n + 2 < nblocks) mbar_wait(my_qfull, (t + 1) & 1);
          wg_wait<3>();
          load_q<0, 4>(Q, lane_addr);
          wg_wait<2>();
          load_q<4, 8>(Q, lane_addr);
        }
        wg_wait<1>();
        EV(5);
        fence_regs(S);
        fence_regs(P1);
        release(kslot);
      } else {
        wg_wait<0>();
        fence_regs(O);
        fence_regs(P1);
        if (pending) {
          release(vprev);
          epilogue_part<0, 12>(O, lp0, lp1, lane_addr);
          epilogue_done(my_ostg, lane);
        }
        EV(6);
        turn_wait();
        wg_fence();
        EV(2);
        issue_qk(S, Q, kd);
        wg_commit();
        EV(3);
        issue_pv<false>(O, P0, vd);
        wg_commit();
        EV(4);
        turn_pass();
        probe();
        exit_n = (tails & 2) ? n + 6 : -1;
        tails >>= 1;
        asm volatile("" : "+r"(exit_n), "+r"(tails));
        wg_wait<1>();
        EV(5);
        fence_regs(S);
        release(kslot);
        pending = true;
      }
      const bool last = n + 2 == nblocks;
      to_tail = n == exit_n;
      EV_STEP(n + 1);
      EV(0);
      softmax_block(S, P1, O, st, false, j == 6, Q, lane_addr);
      EV(1);
      ensure();
      kslot = knext; kd = kdnext;
      vprev = vslot;
      vslot = vnext; vd = vdnext;
      fence_regs(P1);
      wg_wait<0>();
      release(vprev);
      turn_wait();
      if (to_tail) {
        wg_fence();
        issue_pv<true>(O, P1, vd);
        wg_commit();
        break;
      }
      wg_fence();
      EV(2);
      issue_qk(S, Q, kd);
      wg_commit();
      EV(3);
      issue_pv<true>(O, P1, vd);
      wg_commit();
      EV(4);
      if (w == 0 || !last) turn_pass();
      if (!last) probe();
      if (j == 6) row_norm(st.l0, st.l1, st.l0, st.l1);
      wg_wait<1>();
      EV(5);
      fence_regs(S);
      fence_regs(P0);
      release(kslot);
      n += 2;
    } while (n < nblocks);
      if (!to_tail) break;
      {
        n += 2;
        const int t = (n >> 3) - 1;
        const uint32_t qt = sbase + OFF_QT, pt = sbase + OFF_PT, red = sbase + OFF_RED;
        const uint32_t tl = ((lane & 7) + (lane >> 4) * 8) * 128 + (((warp * 2 + ((lane >> 3) & 1)) ^ (lane & 7)) << 4);
        const bool tlast = n + 8 == nblocks;
        TailState ts;
        float ST[8], OT[3][8];
        wg_fence();
        issue_qkT(ST, kd, qt);
        wg_commit();
        turn_pass();
        probe();
        wg_wait<0>();
        fence_regs(ST);
        fence_regs(O);
        release(kslot);
        release(vslot);
        {
          float i0, i1;
          row_norm(st.l0, st.l1, i0, i1);
          epilogue_part<0, 12>(O, i0, i1, lane_addr);
          epilogue_done(my_ostg, lane);
        }
        uint32_t vt_prev = 0;
        auto tail_step = [&](auto first_c, auto last_c, int jj) {
          constexpr bool FIRST = decltype(first_c)::value, LAST = decltype(last_c)::value;
          const uint32_t ptj = pt + (jj & 1) * 2048;
          EV_STEP(n + jj);
          EV(0);
          tail_softmax(ST, OT, ts, FIRST, ptj + tl, red, warp, lane);
          EV(1);
          ensure();
          kslot = knext; kd = kdnext;
          vt_prev = vslot;
          vslot = vnext; vd = vdnext;
          if (LAST) {
            if (!tlast) mbar_wait(my_qfull, t & 1);
            load_q(Q, lane_addr);
          }
          turn_wait();
          wg_fence();
          EV(2);
          if (!LAST) issue_qkT(ST, kd, qt);
          else issue_qk(S, Q, kd);
          wg_commit();
          EV(3);
          issue_pvT<!FIRST>(OT, vd, ptj);
          wg_commit();
          EV(4);
          if (!LAST || !tlast) turn_pass();
          if (!LAST || !tlast) probe();
          if (jj == QDELAY && releaser) mbar_arrive(bar_qreq + 8 * w);
          if (LAST) {
            wg_wait<0>();
            fence_regs(S);
            fence_regs(OT[0]); fence_regs(OT[1]); fence_regs(OT[2]);
            release(vslot);
          } else {
            wg_wait<1>();
            fence_regs(ST);
          }
          EV(5);
          release(kslot);
          if (!FIRST) release(vt_prev);
        };
        tail_step(Bool<true>(), Bool<false>(), 0);
#pragma unroll 1
        for (int jj = 1; jj < 7; jj++) tail_step(Bool<false>(), Bool<false>(), jj);
        tail_step(Bool<false>(), Bool<true>(), 7);
        tail_reduce<false>(ts.l, red + 256, warp, lane);
#pragma unroll
        for (int i = 0; i < 4; i++) ts.l[i] = rcp(ts.l[i]);
#pragma unroll
        for (int b = 0; b < 3; b++)
          stsm_x4_trans(s_qo + SLOT + b * SLAB + tl + (lane >> 4) * (RGRP - 1024),
                        pack_bf16(OT[b][0] * ts.l[0], OT[b][1] * ts.l[1]), pack_bf16(OT[b][2] * ts.l[0], OT[b][3] * ts.l[1]),
                        pack_bf16(OT[b][4] * ts.l[2], OT[b][5] * ts.l[3]), pack_bf16(OT[b][6] * ts.l[2], OT[b][7] * ts.l[3]));
        epilogue_done(my_ostg, lane);
#pragma unroll
        for (int i = 0; i < 96; i++) O[i] = 0.f;
        pending = false;
        n += 8;
        tails >>= 1;
        if (n >= nblocks) break;
      }
    }
    wg_wait<0>();
    fence_regs(O);
    if (pending) {
      release(vslot);
      epilogue_part<0, 12>(O, st.l0, st.l1, lane_addr);
      epilogue_done(my_ostg, lane);
    }
  }
}

typedef CUresult (*EncodeFn)(CUtensorMap*, CUtensorMapDataType, cuuint32_t, void*, const cuuint64_t*, const cuuint64_t*,
                             const cuuint32_t*, const cuuint32_t*, CUtensorMapInterleave, CUtensorMapSwizzle,
                             CUtensorMapL2promotion, CUtensorMapFloatOOBfill);

void make_map(EncodeFn fn, CUtensorMap* tm, const void* ptr, int rows, int box_rows) {
  cuuint64_t dims[5] = {64, 8, 3, (cuuint64_t)rows / 8, (cuuint64_t)NHEADS};
  cuuint64_t strides[4] = {HD * 2, 128, 8 * HD * 2, (cuuint64_t)rows * HD * 2};
  cuuint32_t box[5] = {64, 8, 3, (cuuint32_t)box_rows / 8, 1};
  cuuint32_t estr[5] = {1, 1, 1, 1, 1};
  fn(tm, CU_TENSOR_MAP_DATA_TYPE_BFLOAT16, 5, const_cast<void*>(ptr), dims, strides, box, estr,
     CU_TENSOR_MAP_INTERLEAVE_NONE, CU_TENSOR_MAP_SWIZZLE_128B, CU_TENSOR_MAP_L2_PROMOTION_L2_128B, CU_TENSOR_MAP_FLOAT_OOB_FILL_NONE);
}

#define COST_N 1308
#define COST_T 1203
#define COST_TN 1322
#define TAIL_LATE 36
void make_schedule(Schedule& s, int nclusters) {
  static uint16_t lists[MAX_CLUSTERS][NROUNDS];
  int cnt[MAX_CLUSTERS] = {0}, len[MAX_CLUSTERS], ntail[MAX_CLUSTERS] = {0}, first_t[MAX_CLUSTERS];
  long long busy[MAX_CLUSTERS] = {0};
  const int ntails = NROUNDS / 7, base = NROUNDS / nclusters, nheavy = NROUNDS % nclusters, nlight = nclusters - nheavy;
  int for_light = ntails, light_tails = 0;
  for (int c = 0; c < nclusters; c++) {
    const bool heavy = (c + 1) * nheavy / nclusters != c * nheavy / nclusters;
    len[c] = base + heavy;
    first_t[c] = heavy ? 1 + (c * nheavy / nclusters & 1) : 0;
    if (heavy) for_light -= (len[c] - first_t[c] + 1) / 2;
  }
  int gn = 0, gt = 3;
  for (int k = 0; k < NROUNDS; k++) {
    int c = -1;
    for (int i = 0; i < nclusters; i++)
      if (cnt[i] < len[i] && (c < 0 || busy[i] < busy[c])) c = i;
    const bool after_tail = cnt[c] > 0 && (lists[c][cnt[c] - 1] & 0x8000);
    const bool may_t = cnt[c] > 0 && !after_tail;
    bool tail;
    if (first_t[c]) tail = cnt[c] >= first_t[c] && (cnt[c] - first_t[c]) % 2 == 0;
    else tail = may_t && light_tails < for_light &&
                ((gn - gt >= TAIL_LATE && ntail[c] * nlight <= light_tails) || cnt[c] == len[c] - 1);
    if (gt >= NROUNDS) tail = false;
    if (gn >= NROUNDS) tail = true;
    const int g = tail ? gt : gn;
    if (tail) { gt += 7; ntail[c]++; if (!first_t[c]) light_tails++; }
    else { gn++; if (gn % 7 == 3) gn++; }
    const bool form_t = tail && may_t;
    lists[c][cnt[c]++] = (uint16_t)(g | (form_t ? 0x8000 : 0));
    busy[c] += form_t ? COST_T : after_tail ? COST_TN : COST_N;
  }
  bool use_tail = true;
  for (int c = 0; c < nclusters; c++) if (cnt[c] > MAX_ROUNDS) use_tail = false;
  if (!use_tail) for (int c = 0; c < nclusters; c++) for (int i = 0; i < cnt[c]; i++) lists[c][i] &= 0x7fff;
  int pos = 0;
  for (int c = 0; c < nclusters; c++) {
    s.start[c] = (uint16_t)pos;
    s.tails[c] = 0;
    for (int i = 0; i < cnt[c]; i++) {
      if (lists[c][i] & 0x8000) s.tails[c] |= 1u << i;
      s.list[pos++] = lists[c][i];
    }
  }
  for (int c = nclusters; c <= MAX_CLUSTERS; c++) s.start[c] = (uint16_t)pos;
}

}

extern "C" void kernel_launch(void* const* d_in, const int* in_sizes, int n_in, void* d_out, int out_size) {
  static EncodeFn encode = nullptr;
  static int nclusters = 0;
  static Schedule sched;
  if (!encode) {
    void* fn = nullptr;
    cudaDriverEntryPointQueryResult qr;
    cudaGetDriverEntryPoint("cuTensorMapEncodeTiled", &fn, cudaEnableDefault, &qr);
    encode = (EncodeFn)fn;
    int dev = 0, nsm = 0;
    cudaGetDevice(&dev);
    cudaDeviceGetAttribute(&nsm, cudaDevAttrMultiProcessorCount, dev);
    nclusters = nsm / 2 < MAX_CLUSTERS ? nsm / 2 : MAX_CLUSTERS;
    make_schedule(sched, nclusters);
    cudaFuncSetAttribute(attn_kernel, cudaFuncAttributeMaxDynamicSharedMemorySize, SMEM_BYTES);
  }
  CUtensorMap tmQ, tmQT, tmK, tmV, tmO;
  make_map(encode, &tmQ, d_in[0], SQ, 64);
  make_map(encode, &tmQT, d_in[0], SQ, 16);
  make_map(encode, &tmK, d_in[1], SK, 64);
  make_map(encode, &tmV, d_in[2], SK, 64);
  make_map(encode, &tmO, d_out, SQ, 64);
  attn_kernel<<<2 * nclusters, NTHREADS, SMEM_BYTES>>>(tmQ, tmQT, tmK, tmV, tmO, sched);
}
```

```cpp
#include <cuda_runtime.h>
#include <cuda_bf16.h>
#include <cuda.h>
#include <stdint.h>

namespace {

constexpr int NHEADS = 512;
constexpr int SQ = 848;
constexpr int SK = 512;
constexpr int HD = 192;
constexpr int BN = 64;
constexpr int NBLK = SK / BN;
constexpr int SLOT = 64 * HD * 2;
constexpr int SLAB = 1024;
constexpr int RGRP = 3 * SLAB;
constexpr int NSLOT = 7;
constexpr int NROUNDS = (NHEADS / 2) * 7;
constexpr int NTHREADS = 384;
constexpr int OFF_QO = 0;
constexpr int OFF_KV = 2 * SLOT;
constexpr int OFF_QT = (2 + NSLOT) * SLOT;
constexpr int OFF_PT = OFF_QT + 3 * 2048;
constexpr int OFF_RED = OFF_PT + 2 * 2048;
constexpr int OFF_BAR = OFF_RED + 256;
constexpr int SMEM_BYTES = OFF_BAR + 256;

#define ESPLIT 8
#define QDELAY 4
constexpr uint32_t WAIT_LIMIT = 1u << 18;
#define SUSPEND 20000
constexpr uint32_t SUSPEND_NS = SUSPEND;

constexpr float SCALE_LOG2 = 0.07216878364870322f * 1.4426950408889634f;
constexpr float SUM_MIN = 9.313225746154785e-10f;
constexpr float SUM_MAX = 1.152921504606847e+18f;
__device__ __forceinline__ bool sum_ok(float l) { return l >= SUM_MIN && l <= SUM_MAX; }

__device__ __forceinline__ uint32_t smem_u32(const void* p) { return (uint32_t)__cvta_generic_to_shared(p); }
__device__ __forceinline__ void wg_fence() { asm volatile("wgmma.fence.sync.aligned;" ::: "memory"); }
__device__ __forceinline__ void wg_commit() { asm volatile("wgmma.commit_group.sync.aligned;" ::: "memory"); }
template <int N> __device__ __forceinline__ void wg_wait() { asm volatile("wgmma.wait_group.sync.aligned %0;" ::"n"(N) : "memory"); }
template <int N> __device__ __forceinline__ void fence_regs(float (&r)[N]) {
#pragma unroll
  for (int i = 0; i < N; i++) asm volatile("" : "+f"(r[i])::"memory");
}
template <int N> __device__ __forceinline__ void fence_regs(uint32_t (&r)[N]) {
#pragma unroll
  for (int i = 0; i < N; i++) asm volatile("" : "+r"(r[i])::"memory");
}

__device__ __forceinline__ void mbar_init(uint32_t bar, uint32_t cnt) {
  asm volatile("mbarrier.init.shared::cta.b64 [%0], %1;" ::"r"(bar), "r"(cnt));
}
__device__ __forceinline__ void mbar_expect_tx(uint32_t bar, uint32_t bytes) {
  asm volatile("mbarrier.arrive.expect_tx.shared::cta.b64 _, [%0], %1;" ::"r"(bar), "r"(bytes) : "memory");
}
__device__ __forceinline__ void mbar_arrive(uint32_t bar) {
  asm volatile("mbarrier.arrive.shared::cta.b64 _, [%0];" ::"r"(bar) : "memory");
}
__device__ __forceinline__ bool mbar_try(uint32_t bar, uint32_t parity) {
  uint32_t ok;
  asm volatile(
      "{\n.reg .pred p;\nmbarrier.try_wait.parity.shared::cta.b64 p, [%1], %2;\nselp.b32 %0, 1, 0, p;\n}\n"
      : "=r"(ok)
      : "r"(bar), "r"(parity)
      : "memory");
  return ok;
}
__device__ __forceinline__ bool mbar_try_sleep(uint32_t bar, uint32_t parity) {
  uint32_t ok;
  asm volatile(
      "{\n.reg .pred p;\nmbarrier.try_wait.parity.shared::cta.b64 p, [%1], %2, %3;\nselp.b32 %0, 1, 0, p;\n}\n"
      : "=r"(ok)
      : "r"(bar), "r"(parity), "r"(SUSPEND_NS)
      : "memory");
  return ok;
}
__device__ __forceinline__ void mbar_wait(uint32_t bar, uint32_t parity) {
  if (mbar_try(bar, parity)) return;
  for (uint32_t n = 0; n < WAIT_LIMIT; n++)
    if (mbar_try(bar, parity)) break;
}
__device__ __forceinline__ void mbar_wait_sleep(uint32_t bar, uint32_t parity) {
  for (uint32_t n = 0; n < WAIT_LIMIT; n++) {
    if (mbar_try_sleep(bar, parity)) break;
  }
}

__device__ __forceinline__ void tma_load(uint32_t dst, const CUtensorMap* tm, uint32_t bar, int row, int head, uint64_t pol) {
  asm volatile(
      "cp.async.bulk.tensor.5d.shared::cluster.global.mbarrier::complete_tx::bytes.L2::cache_hint"
      " [%0], [%1, {%3, %3, %3, %4, %5}], [%2], %6;" ::"r"(dst),
      "l"(tm), "r"(bar), "r"(0), "r"(row >> 3), "r"(head), "l"(pol)
      : "memory");
}
__device__ __forceinline__ void tma_load_mc(uint32_t dst, const CUtensorMap* tm, uint32_t bar, int row, int head, uint64_t pol) {
  asm volatile(
      "cp.async.bulk.tensor.5d.shared::cluster.global.mbarrier::complete_tx::bytes.multicast::cluster.L2::cache_hint"
      " [%0], [%1, {%3, %3, %3, %4, %5}], [%2], %7, %6;" ::"r"(dst),
      "l"(tm), "r"(bar), "r"(0), "r"(row >> 3), "r"(head), "l"(pol), "h"((uint16_t)3)
      : "memory");
}
__device__ __forceinline__ void tma_store(const CUtensorMap* tm, uint32_t src, int row, int head, uint64_t pol) {
  asm volatile(
      "cp.async.bulk.tensor.5d.global.shared::cta.bulk_group.L2::cache_hint"
      " [%0, {%2, %2, %2, %3, %4}], [%1], %5;" ::"l"(tm),
      "r"(src), "r"(0), "r"(row >> 3), "r"(head), "l"(pol)
      : "memory");
}
__device__ __forceinline__ void ldsm_x4(uint32_t addr, uint32_t& r0, uint32_t& r1, uint32_t& r2, uint32_t& r3) {
  asm volatile("ldmatrix.sync.aligned.m8n8.x4.shared.b16 {%0, %1, %2, %3}, [%4];"
               : "=r"(r0), "=r"(r1), "=r"(r2), "=r"(r3)
               : "r"(addr)
               : "memory");
}
__device__ __forceinline__ void stsm_x4(uint32_t addr, uint32_t r0, uint32_t r1, uint32_t r2, uint32_t r3) {
  asm volatile("stmatrix.sync.aligned.m8n8.x4.shared.b16 [%0], {%1, %2, %3, %4};" ::"r"(addr), "r"(r0), "r"(r1), "r"(r2), "r"(r3)
               : "memory");
}
__device__ __forceinline__ void stsm_x4_trans(uint32_t addr, uint32_t r0, uint32_t r1, uint32_t r2, uint32_t r3) {
  asm volatile("stmatrix.sync.aligned.m8n8.x4.trans.shared.b16 [%0], {%1, %2, %3, %4};" ::"r"(addr), "r"(r0), "r"(r1), "r"(r2), "r"(r3)
               : "memory");
}
__device__ __forceinline__ float ex2(float x) {
  float y;
  asm("ex2.approx.ftz.f32 %0, %1;" : "=f"(y) : "f"(x));
  return y;
}
__device__ __forceinline__ float rcp(float x) {
  float y;
  asm("rcp.approx.ftz.f32 %0, %1;" : "=f"(y) : "f"(x));
  return y;
}
__device__ __forceinline__ uint32_t pack_bf16(float lo, float hi) {
  uint32_t r;
  asm("cvt.rn.bf16x2.f32 %0, %1, %2;" : "=r"(r) : "f"(hi), "f"(lo));
  return r;
}
__device__ __forceinline__ void wgmma_qk(float (&d)[32], uint32_t a0, uint32_t a1, uint32_t a2, uint32_t a3, uint64_t db, int scale_d) {
  asm volatile("{\n.reg .pred p;\nsetp.ne.b32 p, %37, 0;\n"
    "wgmma.mma_async.sync.aligned.m64n64k16.f32.bf16.bf16 "
    "{%0, %1, %2, %3, %4, %5, %6, %7, %8, %9, %10, %11, %12, %13, %14, %15, %16, %17, %18, %19, %20, %21, %22, %23, %24, %25, %26, %27, %28, %29, %30, %31}, "
    "{%32, %33, %34, %35}, %36, p, 1, 1, 0;\n}\n"
    : "+f"(d[0]), "+f"(d[1]), "+f"(d[2]), "+f"(d[3]), "+f"(d[4]), "+f"(d[5]), "+f"(d[6]), "+f"(d[7]), "+f"(d[8]), "+f"(d[9]), "+f"(d[10]), "+f"(d[11]), "+f"(d[12]), "+f"(d[13]), "+f"(d[14]), "+f"(d[15]), "+f"(d[16]), "+f"(d[17]), "+f"(d[18]), "+f"(d[19]), "+f"(d[20]), "+f"(d[21]), "+f"(d[22]), "+f"(d[23]), "+f"(d[24]), "+f"(d[25]), "+f"(d[26]), "+f"(d[27]), "+f"(d[28]), "+f"(d[29]), "+f"(d[30]), "+f"(d[31])
    : "r"(a0), "r"(a1), "r"(a2), "r"(a3), "l"(db), "r"(scale_d));
}

__device__ __forceinline__ void wgmma_pv(float (&d)[96], uint32_t a0, uint32_t a1, uint32_t a2, uint32_t a3, uint64_t db, int scale_d) {
  asm volatile("{\n.reg .pred p;\nsetp.ne.b32 p, %101, 0;\n"
    "wgmma.mma_async.sync.aligned.m64n192k16.f32.bf16.bf16 "
    "{%0, %1, %2, %3, %4, %5, %6, %7, %8, %9, %10, %11, %12, %13, %14, %15, %16, %17, %18, %19, %20, %21, %22, %23, %24, %25, %26, %27, %28, %29, %30, %31, %32, %33, %34, %35, %36, %37, %38, %39, %40, %41, %42, %43, %44, %45, %46, %47, %48, %49, %50, %51, %52, %53, %54, %55, %56, %57, %58, %59, %60, %61, %62, %63, %64, %65, %66, %67, %68, %69, %70, %71, %72, %73, %74, %75, %76, %77, %78, %79, %80, %81, %82, %83, %84, %85, %86, %87, %88, %89, %90, %91, %92, %93, %94, %95}, "
    "{%96, %97, %98, %99}, %100, p, 1, 1, 1;\n}\n"
    : "+f"(d[0]), "+f"(d[1]), "+f"(d[2]), "+f"(d[3]), "+f"(d[4]), "+f"(d[5]), "+f"(d[6]), "+f"(d[7]), "+f"(d[8]), "+f"(d[9]), "+f"(d[10]), "+f"(d[11]), "+f"(d[12]), "+f"(d[13]), "+f"(d[14]), "+f"(d[15]), "+f"(d[16]), "+f"(d[17]), "+f"(d[18]), "+f"(d[19]), "+f"(d[20]), "+f"(d[21]), "+f"(d[22]), "+f"(d[23]), "+f"(d[24]), "+f"(d[25]), "+f"(d[26]), "+f"(d[27]), "+f"(d[28]), "+f"(d[29]), "+f"(d[30]), "+f"(d[31]), "+f"(d[32]), "+f"(d[33]), "+f"(d[34]), "+f"(d[35]), "+f"(d[36]), "+f"(d[37]), "+f"(d[38]), "+f"(d[39]), "+f"(d[40]), "+f"(d[41]), "+f"(d[42]), "+f"(d[43]), "+f"(d[44]), "+f"(d[45]), "+f"(d[46]), "+f"(d[47]), "+f"(d[48]), "+f"(d[49]), "+f"(d[50]), "+f"(d[51]), "+f"(d[52]), "+f"(d[53]), "+f"(d[54]), "+f"(d[55]), "+f"(d[56]), "+f"(d[57]), "+f"(d[58]), "+f"(d[59]), "+f"(d[60]), "+f"(d[61]), "+f"(d[62]), "+f"(d[63]), "+f"(d[64]), "+f"(d[65]), "+f"(d[66]), "+f"(d[67]), "+f"(d[68]), "+f"(d[69]), "+f"(d[70]), "+f"(d[71]), "+f"(d[72]), "+f"(d[73]), "+f"(d[74]), "+f"(d[75]), "+f"(d[76]), "+f"(d[77]), "+f"(d[78]), "+f"(d[79]), "+f"(d[80]), "+f"(d[81]), "+f"(d[82]), "+f"(d[83]), "+f"(d[84]), "+f"(d[85]), "+f"(d[86]), "+f"(d[87]), "+f"(d[88]), "+f"(d[89]), "+f"(d[90]), "+f"(d[91]), "+f"(d[92]), "+f"(d[93]), "+f"(d[94]), "+f"(d[95])
    : "r"(a0), "r"(a1), "r"(a2), "r"(a3), "l"(db), "r"(scale_d));
}

__device__ __forceinline__ void wgmma_qkT(float (&d)[8], uint64_t da, uint64_t db, int scale_d) {
  asm volatile("{\n.reg .pred p;\nsetp.ne.b32 p, %10, 0;\n"
    "wgmma.mma_async.sync.aligned.m64n16k16.f32.bf16.bf16 "
    "{%0, %1, %2, %3, %4, %5, %6, %7}, "
    "%8, %9, p, 1, 1, 0, 0;\n}\n"
    : "+f"(d[0]), "+f"(d[1]), "+f"(d[2]), "+f"(d[3]), "+f"(d[4]), "+f"(d[5]), "+f"(d[6]), "+f"(d[7])
    : "l"(da), "l"(db), "r"(scale_d));
}
__device__ __forceinline__ void wgmma_pvT(float (&d)[8], uint64_t da, uint64_t db, int scale_d) {
  asm volatile("{\n.reg .pred p;\nsetp.ne.b32 p, %10, 0;\n"
    "wgmma.mma_async.sync.aligned.m64n16k16.f32.bf16.bf16 "
    "{%0, %1, %2, %3, %4, %5, %6, %7}, "
    "%8, %9, p, 1, 1, 1, 0;\n}\n"
    : "+f"(d[0]), "+f"(d[1]), "+f"(d[2]), "+f"(d[3]), "+f"(d[4]), "+f"(d[5]), "+f"(d[6]), "+f"(d[7])
    : "l"(da), "l"(db), "r"(scale_d));
}

__device__ __forceinline__ void wgmma_qk0(float (&d)[32], uint32_t a0, uint32_t a1, uint32_t a2, uint32_t a3, uint64_t db) {
  asm volatile("{\n.reg .pred p;\nsetp.ne.b32 p, 0, 0;\n"
    "wgmma.mma_async.sync.aligned.m64n64k16.f32.bf16.bf16 "
    "{%0, %1, %2, %3, %4, %5, %6, %7, %8, %9, %10, %11, %12, %13, %14, %15, %16, %17, %18, %19, %20, %21, %22, %23, %24, %25, %26, %27, %28, %29, %30, %31}, "
    "{%32, %33, %34, %35}, %36, p, 1, 1, 0;\n}\n"
    : "=f"(d[0]), "=f"(d[1]), "=f"(d[2]), "=f"(d[3]), "=f"(d[4]), "=f"(d[5]), "=f"(d[6]), "=f"(d[7]), "=f"(d[8]), "=f"(d[9]), "=f"(d[10]), "=f"(d[11]), "=f"(d[12]), "=f"(d[13]), "=f"(d[14]), "=f"(d[15]), "=f"(d[16]), "=f"(d[17]), "=f"(d[18]), "=f"(d[19]), "=f"(d[20]), "=f"(d[21]), "=f"(d[22]), "=f"(d[23]), "=f"(d[24]), "=f"(d[25]), "=f"(d[26]), "=f"(d[27]), "=f"(d[28]), "=f"(d[29]), "=f"(d[30]), "=f"(d[31])
    : "r"(a0), "r"(a1), "r"(a2), "r"(a3), "l"(db));
}
__device__ __forceinline__ void wgmma_pv0(float (&d)[96], uint32_t a0, uint32_t a1, uint32_t a2, uint32_t a3, uint64_t db) {
  asm volatile("{\n.reg .pred p;\nsetp.ne.b32 p, 0, 0;\n"
    "wgmma.mma_async.sync.aligned.m64n192k16.f32.bf16.bf16 "
    "{%0, %1, %2, %3, %4, %5, %6, %7, %8, %9, %10, %11, %12, %13, %14, %15, %16, %17, %18, %19, %20, %21, %22, %23, %24, %25, %26, %27, %28, %29, %30, %31, %32, %33, %34, %35, %36, %37, %38, %39, %40, %41, %42, %43, %44, %45, %46, %47, %48, %49, %50, %51, %52, %53, %54, %55, %56, %57, %58, %59, %60, %61, %62, %63, %64, %65, %66, %67, %68, %69, %70, %71, %72, %73, %74, %75, %76, %77, %78, %79, %80, %81, %82, %83, %84, %85, %86, %87, %88, %89, %90, %91, %92, %93, %94, %95}, "
    "{%96, %97, %98, %99}, %100, p, 1, 1, 1;\n}\n"
    : "=f"(d[0]), "=f"(d[1]), "=f"(d[2]), "=f"(d[3]), "=f"(d[4]), "=f"(d[5]), "=f"(d[6]), "=f"(d[7]), "=f"(d[8]), "=f"(d[9]), "=f"(d[10]), "=f"(d[11]), "=f"(d[12]), "=f"(d[13]), "=f"(d[14]), "=f"(d[15]), "=f"(d[16]), "=f"(d[17]), "=f"(d[18]), "=f"(d[19]), "=f"(d[20]), "=f"(d[21]), "=f"(d[22]), "=f"(d[23]), "=f"(d[24]), "=f"(d[25]), "=f"(d[26]), "=f"(d[27]), "=f"(d[28]), "=f"(d[29]), "=f"(d[30]), "=f"(d[31]), "=f"(d[32]), "=f"(d[33]), "=f"(d[34]), "=f"(d[35]), "=f"(d[36]), "=f"(d[37]), "=f"(d[38]), "=f"(d[39]), "=f"(d[40]), "=f"(d[41]), "=f"(d[42]), "=f"(d[43]), "=f"(d[44]), "=f"(d[45]), "=f"(d[46]), "=f"(d[47]), "=f"(d[48]), "=f"(d[49]), "=f"(d[50]), "=f"(d[51]), "=f"(d[52]), "=f"(d[53]), "=f"(d[54]), "=f"(d[55]), "=f"(d[56]), "=f"(d[57]), "=f"(d[58]), "=f"(d[59]), "=f"(d[60]), "=f"(d[61]), "=f"(d[62]), "=f"(d[63]), "=f"(d[64]), "=f"(d[65]), "=f"(d[66]), "=f"(d[67]), "=f"(d[68]), "=f"(d[69]), "=f"(d[70]), "=f"(d[71]), "=f"(d[72]), "=f"(d[73]), "=f"(d[74]), "=f"(d[75]), "=f"(d[76]), "=f"(d[77]), "=f"(d[78]), "=f"(d[79]), "=f"(d[80]), "=f"(d[81]), "=f"(d[82]), "=f"(d[83]), "=f"(d[84]), "=f"(d[85]), "=f"(d[86]), "=f"(d[87]), "=f"(d[88]), "=f"(d[89]), "=f"(d[90]), "=f"(d[91]), "=f"(d[92]), "=f"(d[93]), "=f"(d[94]), "=f"(d[95])
    : "r"(a0), "r"(a1), "r"(a2), "r"(a3), "l"(db));
}
__device__ __forceinline__ void wgmma_qkT0(float (&d)[8], uint64_t da, uint64_t db) {
  asm volatile("{\n.reg .pred p;\nsetp.ne.b32 p, 0, 0;\n"
    "wgmma.mma_async.sync.aligned.m64n16k16.f32.bf16.bf16 "
    "{%0, %1, %2, %3, %4, %5, %6, %7}, "
    "%8, %9, p, 1, 1, 0, 0;\n}\n"
    : "=f"(d[0]), "=f"(d[1]), "=f"(d[2]), "=f"(d[3]), "=f"(d[4]), "=f"(d[5]), "=f"(d[6]), "=f"(d[7])
    : "l"(da), "l"(db));
}
__device__ __forceinline__ void wgmma_pvT0(float (&d)[8], uint64_t da, uint64_t db) {
  asm volatile("{\n.reg .pred p;\nsetp.ne.b32 p, 0, 0;\n"
    "wgmma.mma_async.sync.aligned.m64n16k16.f32.bf16.bf16 "
    "{%0, %1, %2, %3, %4, %5, %6, %7}, "
    "%8, %9, p, 1, 1, 1, 0;\n}\n"
    : "=f"(d[0]), "=f"(d[1]), "=f"(d[2]), "=f"(d[3]), "=f"(d[4]), "=f"(d[5]), "=f"(d[6]), "=f"(d[7])
    : "l"(da), "l"(db));
}

struct Round { int head, qrow, mc; };
__device__ __forceinline__ Round decode_round(int g, int rank) {
  int p = g / 7, r = g - p * 7;
  Round o;
  if (r < 3) { o.head = 2 * p; o.qrow = r * 256 + rank * 128; o.mc = 1; }
  else if (r == 3) { o.head = 2 * p + rank; o.qrow = 768; o.mc = 0; }
  else { o.head = 2 * p + 1; o.qrow = (r - 4) * 256 + rank * 128; o.mc = 1; }
  return o;
}

__device__ __forceinline__ uint32_t kdesc0(uint32_t s_kv) { return ((s_kv & 0x3FFFFu) >> 4) | (1u << 16); }
__device__ __forceinline__ uint32_t vdesc0(uint32_t s_kv) { return ((s_kv & 0x3FFFFu) >> 4) | ((uint32_t)(SLAB >> 4) << 16); }
constexpr uint64_t DESC_HI = ((uint64_t)(RGRP >> 4) << 32) | ((uint64_t)1 << 62);
constexpr uint64_t DESC_HI_PT = ((uint64_t)(1024 >> 4) << 32) | ((uint64_t)1 << 62);

__device__ __forceinline__ void issue_qk(float (&S)[32], const uint32_t (&Q)[48], uint32_t kdesc) {
  const uint64_t d = DESC_HI | kdesc;
  wgmma_qk0(S, Q[0], Q[1], Q[2], Q[3], d);
#pragma unroll
  for (int kk = 1; kk < 12; kk++)
    wgmma_qk(S, Q[kk * 4], Q[kk * 4 + 1], Q[kk * 4 + 2], Q[kk * 4 + 3], d + (uint64_t)((kk / 4) * (SLAB / 16) + (kk % 4) * 2), 1);
}
__device__ __forceinline__ void issue_qk32(float (&S)[32], const uint32_t (&Q)[48], uint32_t kdesc) {
  uint32_t d[12];
#pragma unroll
  for (int kk = 0; kk < 12; kk++) {
    d[kk] = kdesc + ((kk / 4) * (SLAB / 16) + (kk % 4) * 2);
    asm volatile("" : "+r"(d[kk]));
  }
  wgmma_qk0(S, Q[0], Q[1], Q[2], Q[3], DESC_HI | d[0]);
#pragma unroll
  for (int kk = 1; kk < 12; kk++) wgmma_qk(S, Q[kk * 4], Q[kk * 4 + 1], Q[kk * 4 + 2], Q[kk * 4 + 3], DESC_HI | d[kk], 1);
}
__device__ __forceinline__ void issue_qk3(float (&S)[32], const uint32_t (&Q)[48], uint32_t kdesc) {
  const uint64_t d = DESC_HI | kdesc;
  wgmma_qk0(S, Q[0], Q[1], Q[2], Q[3], d);
#pragma unroll
  for (int kk = 1; kk < 12; kk++) {
    if (kk % 4 == 0) wg_commit();
    wgmma_qk(S, Q[kk * 4], Q[kk * 4 + 1], Q[kk * 4 + 2], Q[kk * 4 + 3], d + (uint64_t)((kk / 4) * (SLAB / 16) + (kk % 4) * 2), 1);
  }
}
template <bool ACCUMULATE>
__device__ __forceinline__ void issue_pv(float (&O)[96], const uint32_t (&P)[16], uint32_t vdesc) {
  const uint64_t d = DESC_HI | vdesc;
  if (ACCUMULATE) wgmma_pv(O, P[0], P[1], P[2], P[3], d, 1);
  else wgmma_pv0(O, P[0], P[1], P[2], P[3], d);
#pragma unroll
  for (int kk = 1; kk < 4; kk++)
    wgmma_pv(O, P[kk * 4], P[kk * 4 + 1], P[kk * 4 + 2], P[kk * 4 + 3], d + (uint64_t)(kk * (2 * RGRP / 16)), 1);
}

template <int K0 = 0, int K1 = 12>
__device__ __forceinline__ void load_q(uint32_t (&Q)[48], uint32_t lane_addr) {
#pragma unroll
  for (int kk = K0; kk < K1; kk++)
    ldsm_x4((lane_addr ^ ((kk % 4) << 5)) + (kk / 4) * SLAB, Q[kk * 4], Q[kk * 4 + 1], Q[kk * 4 + 2], Q[kk * 4 + 3]);
}

__device__ __forceinline__ void softmax_block(const float (&S)[32], uint32_t (&P)[16], float& l0, float& l1) {
#pragma unroll
  for (int i = 0; i < 8; i++) {
    const float a = ex2(S[4 * i + 0] * SCALE_LOG2);
    const float b = ex2(S[4 * i + 1] * SCALE_LOG2);
    const float c = ex2(S[4 * i + 2] * SCALE_LOG2);
    const float d = ex2(S[4 * i + 3] * SCALE_LOG2);
    l0 += a + b;
    l1 += c + d;
    P[2 * i] = pack_bf16(a, b);
    P[2 * i + 1] = pack_bf16(c, d);
  }
  fence_regs(P);
}

__device__ __forceinline__ void sums_put(uint32_t addr, float l0, float l1, uint32_t on) {
  asm volatile("{\n.reg .pred p;\nsetp.ne.u32 p, %3, 0;\n@p st.shared.v2.f32 [%0], {%1, %2};\n}\n" ::"r"(addr), "f"(l0), "f"(l1), "r"(on) : "memory");
}
__device__ __forceinline__ void sums_get(uint32_t addr, float& s0, float& s1) {
  float a, b, c, d, e, f, g, h;
  asm volatile("ld.shared.v4.f32 {%0, %1, %2, %3}, [%8];\nld.shared.v4.f32 {%4, %5, %6, %7}, [%8 + 16];\n"
               : "=f"(a), "=f"(b), "=f"(c), "=f"(d), "=f"(e), "=f"(f), "=f"(g), "=f"(h) : "r"(addr & ~31u) : "memory");
  s0 = (a + c) + (e + g);
  s1 = (b + d) + (f + h);
}

template <int K0, int K1>
__device__ __forceinline__ void epilogue_part(const float (&O)[96], float i0, float i1, uint32_t lane_addr) {
#pragma unroll
  for (int kk = K0; kk < K1; kk++) {
    const int b = kk * 8;
    stsm_x4((lane_addr ^ ((kk % 4) << 5)) + (kk / 4) * SLAB,
            pack_bf16(O[b] * i0, O[b + 1] * i0), pack_bf16(O[b + 2] * i1, O[b + 3] * i1),
            pack_bf16(O[b + 4] * i0, O[b + 5] * i0), pack_bf16(O[b + 6] * i1, O[b + 7] * i1));
  }
}
__device__ __forceinline__ void epilogue_done(uint32_t bar, int lane) {
  __syncwarp();
  if (lane == 0) mbar_arrive(bar);
}

__device__ __forceinline__ void redo_tile(const CUtensorMap* tmQ, const CUtensorMap* tmK, const CUtensorMap* tmV, const CUtensorMap* tmO,
                                          int head, int row, uint32_t qo, uint32_t kv, uint32_t lane_addr, uint32_t bar, uint32_t& phase,
                                          uint32_t wg_bar) {
  float O[96], S[32];
  uint32_t Q[48], P[16];
  uint64_t pol;
  asm volatile("createpolicy.fractional.L2::evict_normal.b64 %0, 1.0;" : "=l"(pol));
  const bool leader = (threadIdx.x & 127) == 0;
  if (leader) {
    mbar_expect_tx(bar, SLOT);
    tma_load(qo, tmQ, bar, row, head, pol);
  }
  mbar_wait(bar, phase);
  phase ^= 1;
  load_q(Q, lane_addr);
  float m0 = -INFINITY, m1 = -INFINITY, l0 = 0.f, l1 = 0.f;
#pragma unroll
  for (int i = 0; i < 96; i++) O[i] = 0.f;
#pragma unroll 1
  for (int j = 0; j < NBLK; j++) {
    asm volatile("bar.sync %0, 128;" ::"r"(wg_bar) : "memory");
    if (leader) {
      mbar_expect_tx(bar, 2 * SLOT);
      tma_load(kv, tmK, bar, j * BN, head, pol);
      tma_load(kv + SLOT, tmV, bar, j * BN, head, pol);
    }
    mbar_wait(bar, phase);
    phase ^= 1;
    wg_fence();
    issue_qk(S, Q, kdesc0(kv));
    wg_commit();
    wg_wait<0>();
    fence_regs(S);
    float n0 = m0, n1 = m1;
#pragma unroll
    for (int i = 0; i < 8; i++) {
      n0 = fmaxf(n0, fmaxf(S[4 * i], S[4 * i + 1]));
      n1 = fmaxf(n1, fmaxf(S[4 * i + 2], S[4 * i + 3]));
    }
#pragma unroll
    for (int o = 1; o < 4; o <<= 1) {
      n0 = fmaxf(n0, __shfl_xor_sync(0xffffffffu, n0, o));
      n1 = fmaxf(n1, __shfl_xor_sync(0xffffffffu, n1, o));
    }
    const float f0 = ex2((m0 - n0) * SCALE_LOG2), f1 = ex2((m1 - n1) * SCALE_LOG2);
    m0 = n0; m1 = n1;
    l0 *= f0; l1 *= f1;
#pragma unroll
    for (int i = 0; i < 24; i++) {
      O[4 * i] *= f0; O[4 * i + 1] *= f0; O[4 * i + 2] *= f1; O[4 * i + 3] *= f1;
    }
#pragma unroll
    for (int i = 0; i < 8; i++) {
      S[4 * i] -= m0; S[4 * i + 1] -= m0; S[4 * i + 2] -= m1; S[4 * i + 3] -= m1;
    }
    softmax_block(S, P, l0, l1);
    fence_regs(O);
    wg_fence();
    issue_pv<true>(O, P, vdesc0(kv + SLOT));
    wg_commit();
    wg_wait<0>();
    fence_regs(O);
  }
#pragma unroll
  for (int o = 1; o < 4; o <<= 1) {
    l0 += __shfl_xor_sync(0xffffffffu, l0, o);
    l1 += __shfl_xor_sync(0xffffffffu, l1, o);
  }
  epilogue_part<0, 12>(O, rcp(l0), rcp(l1), lane_addr);
  asm volatile("fence.proxy.async.shared::cta;" ::: "memory");
  asm volatile("bar.sync %0, 128;" ::"r"(wg_bar) : "memory");
  if (leader) {
    tma_store(tmO, qo, row, head, pol);
    asm volatile("cp.async.bulk.commit_group;" ::: "memory");
    asm volatile("cp.async.bulk.wait_group 0;" ::: "memory");
  }
}

__device__ __forceinline__ void wg_barrier() { asm volatile("bar.sync 3, 128;" ::: "memory"); }

__device__ __forceinline__ void tail_reduce(float (&v)[4], uint32_t red, int warp, int lane) {
#pragma unroll
  for (int o = 4; o < 32; o <<= 1)
#pragma unroll
    for (int i = 0; i < 4; i++) v[i] += __shfl_xor_sync(0xffffffffu, v[i], o);
  if (lane < 4)
    asm volatile("st.shared.v4.f32 [%0], {%1, %2, %3, %4};" ::"r"(red + (warp * 4 + lane) * 16), "f"(v[0]), "f"(v[1]), "f"(v[2]), "f"(v[3]) : "memory");
  wg_barrier();
#pragma unroll
  for (int ww = 0; ww < 4; ww++) {
    float x0, x1, x2, x3;
    asm volatile("ld.shared.v4.f32 {%0, %1, %2, %3}, [%4];" : "=f"(x0), "=f"(x1), "=f"(x2), "=f"(x3) : "r"(red + (ww * 4 + (lane & 3)) * 16) : "memory");
    if (ww == 0) { v[0] = x0; v[1] = x1; v[2] = x2; v[3] = x3; }
    else { v[0] += x0; v[1] += x1; v[2] += x2; v[3] += x3; }
  }
}

__device__ __forceinline__ void tail_softmax(const float (&S)[8], float (&l)[4], uint32_t pt_addr) {
  float e[8];
#pragma unroll
  for (int i = 0; i < 8; i++) e[i] = ex2(S[i] * SCALE_LOG2);
  stsm_x4_trans(pt_addr, pack_bf16(e[0], e[1]), pack_bf16(e[2], e[3]), pack_bf16(e[4], e[5]), pack_bf16(e[6], e[7]));
  asm volatile("fence.proxy.async.shared::cta;" ::: "memory");
  l[0] += e[0] + e[2]; l[1] += e[1] + e[3]; l[2] += e[4] + e[6]; l[3] += e[5] + e[7];
  wg_barrier();
}

__device__ __forceinline__ void issue_qkT(float (&S8)[8], uint32_t kdesc, uint32_t qt_addr) {
  const uint64_t da = DESC_HI | kdesc;
  const uint64_t db = DESC_HI | (uint64_t)(((qt_addr & 0x3FFFFu) >> 4) | (1u << 16));
  wgmma_qkT0(S8, da, db);
#pragma unroll
  for (int kk = 1; kk < 12; kk++)
    wgmma_qkT(S8, da + (uint64_t)((kk / 4) * (SLAB / 16) + (kk % 4) * 2), db + (uint64_t)((kk / 4) * (SLAB / 16) + (kk % 4) * 2), 1);
}
template <bool ACCUMULATE>
__device__ __forceinline__ void issue_pvT(float (&O)[3][8], uint32_t vdesc, uint32_t pt_base) {
  const uint64_t da = DESC_HI | vdesc;
  const uint64_t db = DESC_HI_PT | (uint64_t)(((pt_base & 0x3FFFFu) >> 4) | (1u << 16));
#pragma unroll
  for (int kk = 0; kk < 4; kk++)
#pragma unroll
    for (int b = 0; b < 3; b++) {
      if (kk == 0 && !ACCUMULATE) wgmma_pvT0(O[b], da + (uint64_t)(b * (SLAB / 16)), db);
      else wgmma_pvT(O[b], da + (uint64_t)(b * (SLAB / 16) + kk * (2 * RGRP / 16)), db + (uint64_t)(kk * 2), 1);
    }
}

template <bool B> struct Bool { static constexpr bool value = B; };

constexpr int MAX_CLUSTERS = 72;
constexpr int MAX_ROUNDS = 32;
struct Schedule {
  uint32_t tails[MAX_CLUSTERS];
  uint16_t start[MAX_CLUSTERS + 1];
  uint16_t list[NROUNDS];
};

#define TRACE_TILE()

__global__ void __cluster_dims__(2, 1, 1) __launch_bounds__(NTHREADS, 1)
attn_kernel(const __grid_constant__ CUtensorMap tmQ, const __grid_constant__ CUtensorMap tmQT, const __grid_constant__ CUtensorMap tmK,
            const __grid_constant__ CUtensorMap tmV, const __grid_constant__ CUtensorMap tmO, const __grid_constant__ Schedule sched) {
  extern __shared__ __align__(1024) uint8_t smem_raw[];
  const uint32_t sbase = smem_u32(smem_raw);
  const uint32_t s_qo = sbase + OFF_QO;
  const uint32_t s_kv = sbase + OFF_KV;
  const uint32_t s_bar = sbase + OFF_BAR;
  const uint32_t bar_full = s_bar;
  const uint32_t bar_empty = s_bar + 8 * NSLOT;
  const uint32_t bar_qfull = s_bar + 16 * NSLOT;
  const uint32_t bar_ostg = bar_qfull + 16;
  const uint32_t bar_qreq = bar_ostg + 16;
  const uint32_t bar_redo = bar_qreq + 16;
  const uint32_t s_redo = bar_redo + 16;

  uint32_t rank;
  asm("mov.u32 %0, %%cluster_ctarank;" : "=r"(rank));
  const int cluster = blockIdx.x >> 1;
  const int first_round = sched.start[cluster];
  const int nrounds = sched.start[cluster + 1] - first_round;
  const int nblocks = nrounds * NBLK;

  if (threadIdx.x == 32) {
    asm volatile("prefetch.tensormap [%0];" ::"l"(&tmQ) : "memory");
    asm volatile("prefetch.tensormap [%0];" ::"l"(&tmK) : "memory");
    asm volatile("prefetch.tensormap [%0];" ::"l"(&tmV) : "memory");
  }
  if (threadIdx.x == 0) {
    for (int i = 0; i < NSLOT; i++) {
      mbar_init(bar_full + 8 * i, 1);
      mbar_init(bar_empty + 8 * i, 4);
    }
    for (int i = 0; i < 2; i++) {
      mbar_init(bar_qfull + 8 * i, 1);
      mbar_init(bar_ostg + 8 * i, 4);
      mbar_init(bar_qreq + 8 * i, 2);
      mbar_init(bar_redo + 8 * i, 1);
      asm volatile("st.shared.u32 [%0], %1;" ::"r"(s_redo + 4 * i), "r"(0) : "memory");
    }
    asm volatile("fence.mbarrier_init.release.cluster;" ::: "memory");
  }
  __syncthreads();
  if (threadIdx.x == 32 || threadIdx.x == 64) {
    const int w = (threadIdx.x >> 5) - 1;
    uint64_t pol;
    asm volatile("createpolicy.fractional.L2::evict_first.b64 %0, 1.0;" : "=l"(pol));
    const Round r = decode_round(sched.list[first_round] & 0x7ff, rank);
    mbar_expect_tx(bar_qfull + 8 * w, SLOT);
    tma_load(s_qo + w * SLOT, &tmQ, bar_qfull + 8 * w, r.qrow + w * 64, r.head, pol);
  }
  asm volatile("barrier.cluster.arrive.relaxed.aligned;\nbarrier.cluster.wait.aligned;" ::: "memory");

  const int wg = __shfl_sync(0xffffffffu, threadIdx.x >> 7, 0);
  const int warp = __shfl_sync(0xffffffffu, (threadIdx.x >> 5) & 3, 0);
  const int lane = threadIdx.x & 31;

  if (wg == 0) {
    asm volatile("setmaxnreg.dec.sync.aligned.u32 24;");
    if (warp == 0 && lane == 0) {
      uint64_t pol;
      asm volatile("createpolicy.fractional.L2::evict_unchanged.b64 %0, 1.0;" : "=l"(pol));
      uint32_t slot = 0, phase = 1;
      auto load = [&](const CUtensorMap* tm, int n, uint32_t owner) {
        const Round r = decode_round(sched.list[first_round + (n >> 3)] & 0x7ff, rank);
        mbar_wait_sleep(bar_empty + 8 * slot, phase);
        mbar_expect_tx(bar_full + 8 * slot, SLOT);
        if (!r.mc) tma_load(s_kv + slot * SLOT, tm, bar_full + 8 * slot, (n & 7) * BN, r.head, pol);
        else if (rank == owner) tma_load_mc(s_kv + slot * SLOT, tm, bar_full + 8 * slot, (n & 7) * BN, r.head, pol);
        if (++slot == NSLOT) { slot = 0; phase ^= 1; }
      };
      load(&tmK, 0, 0);
      for (int n = 0; n < nblocks; n++) {
        load(&tmK, n + 1 < nblocks ? n + 1 : n, 0);
        load(&tmV, n, 1);
      }
      for (int i = 0; i < NSLOT; i++) {
        mbar_wait_sleep(bar_empty + 8 * slot, phase);
        if (++slot == NSLOT) { slot = 0; phase ^= 1; }
      }
    } else if ((warp == 1 || warp == 2) && lane == 0) {
      const int w = warp - 1;
      uint64_t pol;
      asm volatile("createpolicy.fractional.L2::evict_first.b64 %0, 1.0;" : "=l"(pol));
      const uint32_t buf = s_qo + w * SLOT;
      Round r = decode_round(sched.list[first_round] & 0x7ff, rank);
      Round prev = r;
      for (int t = 0; t <= nrounds; t++) {
        mbar_wait_sleep(bar_ostg + 8 * w, t & 1);
        if (t > 0) {
          asm volatile("fence.proxy.async.shared::cta;" ::: "memory");
          tma_store(&tmO, buf, prev.qrow + w * 64, prev.head, pol);
          asm volatile("cp.async.bulk.commit_group;" ::: "memory");
          asm volatile("cp.async.bulk.wait_group.read 0;" ::: "memory");
          prev = r;
        }
        if (t + 1 < nrounds) {
          mbar_wait_sleep(bar_qreq + 8 * w, t & 1);
          const uint32_t e = sched.list[first_round + t + 1];
          r = decode_round(e & 0x7ff, rank);
          if (w == 1 && (e & 0x8000)) {
            mbar_expect_tx(bar_qfull + 8 * w, 3 * 2048);
            tma_load(sbase + OFF_QT, &tmQT, bar_qfull + 8 * w, r.qrow + 64, r.head, pol);
          } else {
            mbar_expect_tx(bar_qfull + 8 * w, SLOT);
            tma_load(buf, &tmQ, bar_qfull + 8 * w, r.qrow + w * 64, r.head, pol);
          }
        } else if (t < nrounds) {
          mbar_arrive(bar_qfull + 8 * w);
        }
      }
      asm volatile("cp.async.bulk.wait_group 0;" ::: "memory");
      mbar_arrive(bar_redo + 8 * w);
    } else if (warp == 3) {
      uint32_t slot = 1, phase = 0;
      for (int n = 0; n < nblocks; n++) {
        mbar_wait(bar_full + 8 * slot, phase);
        if (++slot == NSLOT) { slot = 0; phase ^= 1; }
        mbar_wait(bar_full + 8 * slot, phase);
        if (++slot == NSLOT) { slot = 0; phase ^= 1; }
        asm volatile("bar.sync 1, 288;" ::: "memory");
        asm volatile("bar.arrive 2, 288;" ::: "memory");
        TRACE_TILE();
      }
    }
  } else {
    asm volatile("setmaxnreg.inc.sync.aligned.u32 240;");
    const int w = wg - 1;
    float O[96], S[32];
    uint32_t Q[48], P0[16], P1[16];
    float l0 = 0.f, l1 = 0.f, inv0 = 0.f, inv1 = 0.f;
    uint32_t redo = 0;
    const uint32_t lane_addr = s_qo + w * SLOT + (warp * 2 + ((lane >> 3) & 1)) * RGRP + (lane & 7) * 128 + (((lane >> 4) ^ (lane & 7)) << 4);
    const uint32_t sum_addr = s_qo + w * SLOT + warp * 2 * RGRP + lane * 8;
    const uint32_t my_qfull = bar_qfull + 8 * w, my_ostg = bar_ostg + 8 * w;

    uint32_t empty_remote;
    asm("mapa.shared::cluster.u32 %0, %1, %2;" : "=r"(empty_remote) : "r"(bar_empty), "r"(threadIdx.x & 1));
    const bool releaser = (threadIdx.x & 127) < 2;
    auto release = [&](uint32_t s) {
      if (releaser) asm volatile("mbarrier.arrive.shared::cluster.b64 _, [%0];" ::"r"(empty_remote + s) : "memory");
    };
    uint32_t ks = 8, vs = 16, kp = 0, vp = 0;
    const uint32_t kd0 = kdesc0(s_kv), vd0 = vdesc0(s_kv);
    uint32_t kd = kd0 + ks * (SLOT / 128), vd = vd0 + vs * (SLOT / 128);
    auto advance = [&]() {
      kp = ks; vp = vs;
      ks = ks >= 8 * (NSLOT - 2) ? ks - 8 * (NSLOT - 2) : ks + 16;
      vs = vs >= 8 * (NSLOT - 2) ? vs - 8 * (NSLOT - 2) : vs + 16;
      kd = kd0 + ks * (SLOT / 128); vd = vd0 + vs * (SLOT / 128);
      asm volatile("" : "+r"(ks), "+r"(vs), "+r"(kd), "+r"(vd));
    };

    uint32_t tails = w == 1 ? sched.tails[cluster] : 0u;
    auto turn_wait = [&]() { asm volatile("bar.sync %0, 288;" ::"r"(1 + w) : "memory"); };
    auto turn_pass = [&]() { asm volatile("bar.arrive %0, 288;" ::"r"(2 - w) : "memory"); };
    if (w == 1) turn_pass();

    mbar_wait(my_qfull, 0);
    load_q(Q, lane_addr);
    mbar_wait(bar_full, 0);
    wg_fence();
    issue_qk(S, Q, kd0);
    wg_commit();
    wg_wait<0>();
    fence_regs(S);
    release(0);
    __syncwarp();
    if (lane == 0) mbar_arrive(my_ostg);
    bool pending = false;

    int n = 0;
    auto finish_sums = [&]() {
      float s0, s1;
      sums_get(sum_addr, s0, s1);
      if (!(sum_ok(s0) && sum_ok(s1))) redo |= 1u << ((n >> 3) & 31);
      inv0 = rcp(s0); inv1 = rcp(s1);
      l0 = l1 = 0.f;
      asm volatile("" : "+f"(inv0), "+f"(inv1), "+r"(redo)::"memory");
    };

    int exit_n = -1;
#pragma unroll 1
    while (true) {
      bool to_tail;
#pragma unroll 1
      do {
        const int j = n & 7;
        softmax_block(S, P0, l0, l1);
        asm volatile("" : "+f"(l0), "+f"(l1)::"memory");
        if (j != 0) {
          wg_wait<0>();
          release(vp);
          turn_wait();
          wg_fence();
          issue_qk3(S, Q, kd);
          wg_commit();
          issue_pv<true>(O, P0, vd);
          wg_commit();
          turn_pass();
          advance();
          if (j == QDELAY && releaser) mbar_arrive(bar_qreq + 8 * w);
          if (j == 6) {
            mbar_wait(my_qfull, ((n >> 3) + 1) & 1);
            wg_wait<3>();
            load_q<0, 4>(Q, lane_addr);
            wg_wait<2>();
            load_q<4, 8>(Q, lane_addr);
          }
          wg_wait<1>();
          fence_regs(S);
          fence_regs(P1);
        } else {
          wg_wait<0>();
          fence_regs(O);
          fence_regs(P1);
          if (pending) {
            release(vp);
            epilogue_part<0, ESPLIT>(O, inv0, inv1, lane_addr);
          }
          turn_wait();
          wg_fence();
          issue_qk32(S, Q, kd);
          wg_commit();
          if (pending) {
            epilogue_part<ESPLIT, 12>(O, inv0, inv1, lane_addr);
            epilogue_done(my_ostg, lane);
          }
          wg_fence();
          issue_pv<false>(O, P0, vd);
          wg_commit();
          turn_pass();
          advance();
          exit_n = (tails & 2) ? n + 6 : -1;
          tails >>= 1;
          asm volatile("" : "+r"(exit_n), "+r"(tails));
          wg_wait<1>();
          fence_regs(S);
          pending = true;
        }
        release(kp);
        const bool last = n + 2 == nblocks;
        to_tail = n == exit_n;
        if (j == 6) load_q<8, 12>(Q, lane_addr);
        softmax_block(S, P1, l0, l1);
        sums_put(sum_addr, l0, l1, j == 6);
        wg_wait<0>();
        release(vp);
        turn_wait();
        if (to_tail) {
          wg_fence();
          issue_pv<true>(O, P1, vd);
          wg_commit();
          break;
        }
        wg_fence();
        issue_qk(S, Q, kd);
        wg_commit();
        issue_pv<true>(O, P1, vd);
        wg_commit();
        if (w == 0 || !last) turn_pass();
        advance();
        if (j == 6) finish_sums();
        wg_wait<1>();
        fence_regs(S);
        fence_regs(P0);
        release(kp);
        n += 2;
      } while (n < nblocks);
      if (!to_tail) break;
      {
        const int t = n >> 3;
        const uint32_t qt = sbase + OFF_QT, pt = sbase + OFF_PT, red = sbase + OFF_RED;
        const uint32_t tl = ((lane & 7) + (lane >> 4) * 8) * 128 + (((warp * 2 + ((lane >> 3) & 1)) ^ (lane & 7)) << 4);
        const bool tlast = t + 2 == nrounds;
        float lt[4] = {0.f, 0.f, 0.f, 0.f};
        float ST[8], OT[3][8];
        wg_fence();
        issue_qkT(ST, kd, qt);
        wg_commit();
        turn_pass();
        finish_sums();
        wg_wait<0>();
        fence_regs(ST);
        fence_regs(O);
        release(ks);
        release(vs);
        advance();
        epilogue_part<0, 12>(O, inv0, inv1, lane_addr);
        epilogue_done(my_ostg, lane);
        auto tail_step = [&](auto first_c, auto last_c, int jj) {
          constexpr bool FIRST = decltype(first_c)::value, LAST = decltype(last_c)::value;
          const uint32_t ptj = pt + (jj & 1) * 2048;
          tail_softmax(ST, lt, ptj + tl);
          if (LAST) {
            mbar_wait(my_qfull, t & 1);
            load_q(Q, lane_addr);
          }
          turn_wait();
          wg_fence();
          if (!LAST) issue_qkT(ST, kd, qt);
          else issue_qk(S, Q, kd);
          wg_commit();
          issue_pvT<!FIRST>(OT, vd, ptj);
          wg_commit();
          if (!LAST || !tlast) turn_pass();
          if (jj == QDELAY && releaser) mbar_arrive(bar_qreq + 8 * w);
          if (LAST) {
            wg_wait<0>();
            fence_regs(S);
            fence_regs(OT[0]); fence_regs(OT[1]); fence_regs(OT[2]);
            release(vs);
          } else {
            wg_wait<1>();
            fence_regs(ST);
          }
          release(ks);
          if (!FIRST) release(vp);
          advance();
        };
        tail_step(Bool<true>(), Bool<false>(), 0);
#pragma unroll 1
        for (int jj = 1; jj < 7; jj++) tail_step(Bool<false>(), Bool<false>(), jj);
        tail_step(Bool<false>(), Bool<true>(), 7);
        tail_reduce(lt, red, warp, lane);
        if (!(sum_ok(lt[0]) && sum_ok(lt[1]) && sum_ok(lt[2]) && sum_ok(lt[3]))) redo |= 1u << ((t + 1) & 31);
#pragma unroll
        for (int i = 0; i < 4; i++) lt[i] = rcp(lt[i]);
#pragma unroll
        for (int b = 0; b < 3; b++)
          stsm_x4_trans(s_qo + SLOT + b * SLAB + tl + (lane >> 4) * (RGRP - 1024),
                        pack_bf16(OT[b][0] * lt[0], OT[b][1] * lt[1]), pack_bf16(OT[b][2] * lt[0], OT[b][3] * lt[1]),
                        pack_bf16(OT[b][4] * lt[2], OT[b][5] * lt[3]), pack_bf16(OT[b][6] * lt[2], OT[b][7] * lt[3]));
        epilogue_done(my_ostg, lane);
#pragma unroll
        for (int i = 0; i < 96; i++) O[i] = 0.f;
        pending = false;
        n += 10;
        tails >>= 1;
        if (n >= nblocks) break;
      }
    }
    wg_wait<0>();
    fence_regs(O);
    if (pending) {
      release(vp);
      epilogue_part<0, 12>(O, inv0, inv1, lane_addr);
      epilogue_done(my_ostg, lane);
    }
    if (redo) asm volatile("red.shared.or.b32 [%0], %1;" ::"r"(s_redo + 4 * w), "r"(redo) : "memory");
    asm volatile("bar.sync 4, 256;" ::: "memory");
    asm volatile("ld.shared.u32 %0, [%1];" : "=r"(redo) : "r"(s_redo + 4 * w) : "memory");
    redo = __shfl_sync(0xffffffffu, redo, 0);
    if (redo) {
      mbar_wait_sleep(bar_redo + 8 * w, 0);
      asm volatile("bar.sync %0, 128;" ::"r"(5 + w) : "memory");
      uint32_t phase = 1;
#pragma unroll 1
      for (int t = 0; t < nrounds; t++) {
        if (!(redo >> (t & 31) & 1)) continue;
        const Round r = decode_round(sched.list[first_round + t] & 0x7ff, rank);
        redo_tile(&tmQ, &tmK, &tmV, &tmO, r.head, r.qrow + w * 64, s_qo + w * SLOT, s_kv + 2 * w * SLOT, lane_addr, bar_redo + 8 * w, phase, 5 + w);
      }
    }
  }
}

typedef CUresult (*EncodeFn)(CUtensorMap*, CUtensorMapDataType, cuuint32_t, void*, const cuuint64_t*, const cuuint64_t*,
                             const cuuint32_t*, const cuuint32_t*, CUtensorMapInterleave, CUtensorMapSwizzle,
                             CUtensorMapL2promotion, CUtensorMapFloatOOBfill);

void make_map(EncodeFn fn, CUtensorMap* tm, const void* ptr, int rows, int box_rows) {
  cuuint64_t dims[5] = {64, 8, 3, (cuuint64_t)rows / 8, (cuuint64_t)NHEADS};
  cuuint64_t strides[4] = {HD * 2, 128, 8 * HD * 2, (cuuint64_t)rows * HD * 2};
  cuuint32_t box[5] = {64, 8, 3, (cuuint32_t)box_rows / 8, 1};
  cuuint32_t estr[5] = {1, 1, 1, 1, 1};
  fn(tm, CU_TENSOR_MAP_DATA_TYPE_BFLOAT16, 5, const_cast<void*>(ptr), dims, strides, box, estr,
     CU_TENSOR_MAP_INTERLEAVE_NONE, CU_TENSOR_MAP_SWIZZLE_128B, CU_TENSOR_MAP_L2_PROMOTION_L2_128B, CU_TENSOR_MAP_FLOAT_OOB_FILL_NONE);
}

#define COST_N 1308
#define COST_T 1203
#define COST_TN 1322
#define TAIL_LATE 36
void make_schedule(Schedule& s, int nclusters) {
  static uint16_t lists[MAX_CLUSTERS][NROUNDS];
  int cnt[MAX_CLUSTERS] = {0}, len[MAX_CLUSTERS], ntail[MAX_CLUSTERS] = {0}, first_t[MAX_CLUSTERS];
  long long busy[MAX_CLUSTERS] = {0};
  const int ntails = NROUNDS / 7, base = NROUNDS / nclusters, nheavy = NROUNDS % nclusters, nlight = nclusters - nheavy;
  int for_light = ntails, light_tails = 0;
  for (int c = 0; c < nclusters; c++) {
    const bool heavy = (c + 1) * nheavy / nclusters != c * nheavy / nclusters;
    len[c] = base + heavy;
    first_t[c] = heavy ? 1 + (c * nheavy / nclusters & 1) : 0;
    if (heavy) for_light -= (len[c] - first_t[c] + 1) / 2;
  }
  int gn = 0, gt = 3;
  for (int k = 0; k < NROUNDS; k++) {
    int c = -1;
    for (int i = 0; i < nclusters; i++)
      if (cnt[i] < len[i] && (c < 0 || busy[i] < busy[c])) c = i;
    const bool after_tail = cnt[c] > 0 && (lists[c][cnt[c] - 1] & 0x8000);
    const bool may_t = cnt[c] > 0 && !after_tail;
    bool tail;
    if (first_t[c]) tail = cnt[c] >= first_t[c] && (cnt[c] - first_t[c]) % 2 == 0;
    else tail = may_t && light_tails < for_light &&
                ((gn - gt >= TAIL_LATE && ntail[c] * nlight <= light_tails) || cnt[c] == len[c] - 1);
    if (gt >= NROUNDS) tail = false;
    if (gn >= NROUNDS) tail = true;
    const int g = tail ? gt : gn;
    if (tail) { gt += 7; ntail[c]++; if (!first_t[c]) light_tails++; }
    else { gn++; if (gn % 7 == 3) gn++; }
    const bool form_t = tail && may_t;
    lists[c][cnt[c]++] = (uint16_t)(g | (form_t ? 0x8000 : 0));
    busy[c] += form_t ? COST_T : after_tail ? COST_TN : COST_N;
  }
  bool use_tail = true;
  for (int c = 0; c < nclusters; c++) if (cnt[c] > MAX_ROUNDS) use_tail = false;
  if (!use_tail) for (int c = 0; c < nclusters; c++) for (int i = 0; i < cnt[c]; i++) lists[c][i] &= 0x7fff;
  int pos = 0;
  for (int c = 0; c < nclusters; c++) {
    s.start[c] = (uint16_t)pos;
    s.tails[c] = 0;
    for (int i = 0; i < cnt[c]; i++) {
      if (lists[c][i] & 0x8000) s.tails[c] |= 1u << i;
      s.list[pos++] = lists[c][i];
    }
  }
  for (int c = nclusters; c <= MAX_CLUSTERS; c++) s.start[c] = (uint16_t)pos;
}

}

extern "C" void kernel_launch(void* const* d_in, const int* in_sizes, int n_in, void* d_out, int out_size) {
  static EncodeFn encode = nullptr;
  static int nclusters = 0;
  static Schedule sched;
  if (!encode) {
    void* fn = nullptr;
    cudaDriverEntryPointQueryResult qr;
    cudaGetDriverEntryPoint("cuTensorMapEncodeTiled", &fn, cudaEnableDefault, &qr);
    encode = (EncodeFn)fn;
    int dev = 0, nsm = 0;
    cudaGetDevice(&dev);
    cudaDeviceGetAttribute(&nsm, cudaDevAttrMultiProcessorCount, dev);
    nclusters = nsm / 2 < MAX_CLUSTERS ? nsm / 2 : MAX_CLUSTERS;
    make_schedule(sched, nclusters);
    cudaFuncSetAttribute(attn_kernel, cudaFuncAttributeMaxDynamicSharedMemorySize, SMEM_BYTES);
  }
  CUtensorMap tmQ, tmQT, tmK, tmV, tmO;
  make_map(encode, &tmQ, d_in[0], SQ, 64);
  make_map(encode, &tmQT, d_in[0], SQ, 16);
  make_map(encode, &tmK, d_in[1], SK, 64);
  make_map(encode, &tmV, d_in[2], SK, 64);
  make_map(encode, &tmO, d_out, SQ, 64);
  attn_kernel<<<2 * nclusters, NTHREADS, SMEM_BYTES>>>(tmQ, tmQT, tmK, tmV, tmO, sched);
}
```

```cpp
#include <cuda_runtime.h>
#include <cuda_bf16.h>
#include <cuda.h>
#include <stdint.h>

namespace {

constexpr int NHEADS = 512;
constexpr int SQ = 848;
constexpr int SK = 512;
constexpr int HD = 192;
constexpr int BN = 64;
constexpr int NBLK = SK / BN;
constexpr int SLOT = 64 * HD * 2;
constexpr int SLAB = 1024;
constexpr int RGRP = 3 * SLAB;
constexpr int NSLOT = 7;
constexpr int NROUNDS = (NHEADS / 2) * 7;
constexpr int NTHREADS = 384;
constexpr int OFF_QO = 0;
constexpr int OFF_KV = 2 * SLOT;
constexpr int OFF_QT = (2 + NSLOT) * SLOT;
constexpr int OFF_PT = OFF_QT + 3 * 2048;
constexpr int OFF_RED = OFF_PT + 2 * 2048;
constexpr int OFF_BAR = OFF_RED + 256;
constexpr int SMEM_BYTES = OFF_BAR + 256;

#define ESPLIT 8
#define OROWS 16
#define QDELAY 4
constexpr uint32_t WAIT_LIMIT = 1u << 18;
#define SUSPEND 20000
constexpr uint32_t SUSPEND_NS = SUSPEND;

constexpr float SCALE_LOG2 = 0.07216878364870322f * 1.4426950408889634f;
constexpr float SUM_MIN = 9.313225746154785e-10f;
constexpr float SUM_MAX = 1.152921504606847e+18f;
__device__ __forceinline__ bool sum_ok(float l) { return l >= SUM_MIN && l <= SUM_MAX; }

__device__ __forceinline__ uint32_t smem_u32(const void* p) { return (uint32_t)__cvta_generic_to_shared(p); }
__device__ __forceinline__ void wg_fence() { asm volatile("wgmma.fence.sync.aligned;" ::: "memory"); }
__device__ __forceinline__ void wg_commit() { asm volatile("wgmma.commit_group.sync.aligned;" ::: "memory"); }
template <int N> __device__ __forceinline__ void wg_wait() { asm volatile("wgmma.wait_group.sync.aligned %0;" ::"n"(N) : "memory"); }
template <int N> __device__ __forceinline__ void fence_regs(float (&r)[N]) {
#pragma unroll
  for (int i = 0; i < N; i++) asm volatile("" : "+f"(r[i])::"memory");
}
template <int N> __device__ __forceinline__ void fence_regs(uint32_t (&r)[N]) {
#pragma unroll
  for (int i = 0; i < N; i++) asm volatile("" : "+r"(r[i])::"memory");
}

__device__ __forceinline__ void mbar_init(uint32_t bar, uint32_t cnt) {
  asm volatile("mbarrier.init.shared::cta.b64 [%0], %1;" ::"r"(bar), "r"(cnt));
}
__device__ __forceinline__ void mbar_expect_tx(uint32_t bar, uint32_t bytes) {
  asm volatile("mbarrier.arrive.expect_tx.shared::cta.b64 _, [%0], %1;" ::"r"(bar), "r"(bytes) : "memory");
}
__device__ __forceinline__ void mbar_arrive(uint32_t bar) {
  asm volatile("mbarrier.arrive.shared::cta.b64 _, [%0];" ::"r"(bar) : "memory");
}
__device__ __forceinline__ bool mbar_try(uint32_t bar, uint32_t parity) {
  uint32_t ok;
  asm volatile(
      "{\n.reg .pred p;\nmbarrier.try_wait.parity.shared::cta.b64 p, [%1], %2;\nselp.b32 %0, 1, 0, p;\n}\n"
      : "=r"(ok)
      : "r"(bar), "r"(parity)
      : "memory");
  return ok;
}
__device__ __forceinline__ bool mbar_try_sleep(uint32_t bar, uint32_t parity) {
  uint32_t ok;
  asm volatile(
      "{\n.reg .pred p;\nmbarrier.try_wait.parity.shared::cta.b64 p, [%1], %2, %3;\nselp.b32 %0, 1, 0, p;\n}\n"
      : "=r"(ok)
      : "r"(bar), "r"(parity), "r"(SUSPEND_NS)
      : "memory");
  return ok;
}
__device__ __forceinline__ void mbar_wait(uint32_t bar, uint32_t parity) {
  if (mbar_try(bar, parity)) return;
  for (uint32_t n = 0; n < WAIT_LIMIT; n++)
    if (mbar_try(bar, parity)) break;
}
__device__ __forceinline__ void mbar_wait_sleep(uint32_t bar, uint32_t parity) {
  for (uint32_t n = 0; n < WAIT_LIMIT; n++) {
    if (mbar_try_sleep(bar, parity)) break;
  }
}

__device__ __forceinline__ void tma_load(uint32_t dst, const CUtensorMap* tm, uint32_t bar, int row, int head, uint64_t pol) {
  asm volatile(
      "cp.async.bulk.tensor.5d.shared::cluster.global.mbarrier::complete_tx::bytes.L2::cache_hint"
      " [%0], [%1, {%3, %3, %3, %4, %5}], [%2], %6;" ::"r"(dst),
      "l"(tm), "r"(bar), "r"(0), "r"(row >> 3), "r"(head), "l"(pol)
      : "memory");
}
__device__ __forceinline__ void tma_load_mc(uint32_t dst, const CUtensorMap* tm, uint32_t bar, int row, int head, uint64_t pol) {
  asm volatile(
      "cp.async.bulk.tensor.5d.shared::cluster.global.mbarrier::complete_tx::bytes.multicast::cluster.L2::cache_hint"
      " [%0], [%1, {%3, %3, %3, %4, %5}], [%2], %7, %6;" ::"r"(dst),
      "l"(tm), "r"(bar), "r"(0), "r"(row >> 3), "r"(head), "l"(pol), "h"((uint16_t)3)
      : "memory");
}
__device__ __forceinline__ void tma_store(const CUtensorMap* tm, uint32_t src, int row, int head, uint64_t pol) {
  asm volatile(
      "cp.async.bulk.tensor.5d.global.shared::cta.bulk_group.L2::cache_hint"
      " [%0, {%2, %2, %2, %3, %4}], [%1], %5;" ::"l"(tm),
      "r"(src), "r"(0), "r"(row >> 3), "r"(head), "l"(pol)
      : "memory");
}
__device__ __forceinline__ void ldsm_x4(uint32_t addr, uint32_t& r0, uint32_t& r1, uint32_t& r2, uint32_t& r3) {
  asm volatile("ldmatrix.sync.aligned.m8n8.x4.shared.b16 {%0, %1, %2, %3}, [%4];"
               : "=r"(r0), "=r"(r1), "=r"(r2), "=r"(r3)
               : "r"(addr)
               : "memory");
}
__device__ __forceinline__ void stsm_x4(uint32_t addr, uint32_t r0, uint32_t r1, uint32_t r2, uint32_t r3) {
  asm volatile("stmatrix.sync.aligned.m8n8.x4.shared.b16 [%0], {%1, %2, %3, %4};" ::"r"(addr), "r"(r0), "r"(r1), "r"(r2), "r"(r3)
               : "memory");
}
__device__ __forceinline__ void stsm_x4_trans(uint32_t addr, uint32_t r0, uint32_t r1, uint32_t r2, uint32_t r3) {
  asm volatile("stmatrix.sync.aligned.m8n8.x4.trans.shared.b16 [%0], {%1, %2, %3, %4};" ::"r"(addr), "r"(r0), "r"(r1), "r"(r2), "r"(r3)
               : "memory");
}
__device__ __forceinline__ float ex2(float x) {
  float y;
  asm("ex2.approx.ftz.f32 %0, %1;" : "=f"(y) : "f"(x));
  return y;
}
__device__ __forceinline__ float rcp(float x) {
  float y;
  asm("rcp.approx.ftz.f32 %0, %1;" : "=f"(y) : "f"(x));
  return y;
}
__device__ __forceinline__ uint32_t pack_bf16(float lo, float hi) {
  uint32_t r;
  asm("cvt.rn.bf16x2.f32 %0, %1, %2;" : "=r"(r) : "f"(hi), "f"(lo));
  return r;
}
__device__ __forceinline__ void wgmma_qk(float (&d)[32], uint32_t a0, uint32_t a1, uint32_t a2, uint32_t a3, uint64_t db, int scale_d) {
  asm volatile("{\n.reg .pred p;\nsetp.ne.b32 p, %37, 0;\n"
    "wgmma.mma_async.sync.aligned.m64n64k16.f32.bf16.bf16 "
    "{%0, %1, %2, %3, %4, %5, %6, %7, %8, %9, %10, %11, %12, %13, %14, %15, %16, %17, %18, %19, %20, %21, %22, %23, %24, %25, %26, %27, %28, %29, %30, %31}, "
    "{%32, %33, %34, %35}, %36, p, 1, 1, 0;\n}\n"
    : "+f"(d[0]), "+f"(d[1]), "+f"(d[2]), "+f"(d[3]), "+f"(d[4]), "+f"(d[5]), "+f"(d[6]), "+f"(d[7]), "+f"(d[8]), "+f"(d[9]), "+f"(d[10]), "+f"(d[11]), "+f"(d[12]), "+f"(d[13]), "+f"(d[14]), "+f"(d[15]), "+f"(d[16]), "+f"(d[17]), "+f"(d[18]), "+f"(d[19]), "+f"(d[20]), "+f"(d[21]), "+f"(d[22]), "+f"(d[23]), "+f"(d[24]), "+f"(d[25]), "+f"(d[26]), "+f"(d[27]), "+f"(d[28]), "+f"(d[29]), "+f"(d[30]), "+f"(d[31])
    : "r"(a0), "r"(a1), "r"(a2), "r"(a3), "l"(db), "r"(scale_d));
}

__device__ __forceinline__ void wgmma_pv(float (&d)[96], uint32_t a0, uint32_t a1, uint32_t a2, uint32_t a3, uint64_t db, int scale_d) {
  asm volatile("{\n.reg .pred p;\nsetp.ne.b32 p, %101, 0;\n"
    "wgmma.mma_async.sync.aligned.m64n192k16.f32.bf16.bf16 "
    "{%0, %1, %2, %3, %4, %5, %6, %7, %8, %9, %10, %11, %12, %13, %14, %15, %16, %17, %18, %19, %20, %21, %22, %23, %24, %25, %26, %27, %28, %29, %30, %31, %32, %33, %34, %35, %36, %37, %38, %39, %40, %41, %42, %43, %44, %45, %46, %47, %48, %49, %50, %51, %52, %53, %54, %55, %56, %57, %58, %59, %60, %61, %62, %63, %64, %65, %66, %67, %68, %69, %70, %71, %72, %73, %74, %75, %76, %77, %78, %79, %80, %81, %82, %83, %84, %85, %86, %87, %88, %89, %90, %91, %92, %93, %94, %95}, "
    "{%96, %97, %98, %99}, %100, p, 1, 1, 1;\n}\n"
    : "+f"(d[0]), "+f"(d[1]), "+f"(d[2]), "+f"(d[3]), "+f"(d[4]), "+f"(d[5]), "+f"(d[6]), "+f"(d[7]), "+f"(d[8]), "+f"(d[9]), "+f"(d[10]), "+f"(d[11]), "+f"(d[12]), "+f"(d[13]), "+f"(d[14]), "+f"(d[15]), "+f"(d[16]), "+f"(d[17]), "+f"(d[18]), "+f"(d[19]), "+f"(d[20]), "+f"(d[21]), "+f"(d[22]), "+f"(d[23]), "+f"(d[24]), "+f"(d[25]), "+f"(d[26]), "+f"(d[27]), "+f"(d[28]), "+f"(d[29]), "+f"(d[30]), "+f"(d[31]), "+f"(d[32]), "+f"(d[33]), "+f"(d[34]), "+f"(d[35]), "+f"(d[36]), "+f"(d[37]), "+f"(d[38]), "+f"(d[39]), "+f"(d[40]), "+f"(d[41]), "+f"(d[42]), "+f"(d[43]), "+f"(d[44]), "+f"(d[45]), "+f"(d[46]), "+f"(d[47]), "+f"(d[48]), "+f"(d[49]), "+f"(d[50]), "+f"(d[51]), "+f"(d[52]), "+f"(d[53]), "+f"(d[54]), "+f"(d[55]), "+f"(d[56]), "+f"(d[57]), "+f"(d[58]), "+f"(d[59]), "+f"(d[60]), "+f"(d[61]), "+f"(d[62]), "+f"(d[63]), "+f"(d[64]), "+f"(d[65]), "+f"(d[66]), "+f"(d[67]), "+f"(d[68]), "+f"(d[69]), "+f"(d[70]), "+f"(d[71]), "+f"(d[72]), "+f"(d[73]), "+f"(d[74]), "+f"(d[75]), "+f"(d[76]), "+f"(d[77]), "+f"(d[78]), "+f"(d[79]), "+f"(d[80]), "+f"(d[81]), "+f"(d[82]), "+f"(d[83]), "+f"(d[84]), "+f"(d[85]), "+f"(d[86]), "+f"(d[87]), "+f"(d[88]), "+f"(d[89]), "+f"(d[90]), "+f"(d[91]), "+f"(d[92]), "+f"(d[93]), "+f"(d[94]), "+f"(d[95])
    : "r"(a0), "r"(a1), "r"(a2), "r"(a3), "l"(db), "r"(scale_d));
}

__device__ __forceinline__ void wgmma_qkT(float (&d)[8], uint64_t da, uint64_t db, int scale_d) {
  asm volatile("{\n.reg .pred p;\nsetp.ne.b32 p, %10, 0;\n"
    "wgmma.mma_async.sync.aligned.m64n16k16.f32.bf16.bf16 "
    "{%0, %1, %2, %3, %4, %5, %6, %7}, "
    "%8, %9, p, 1, 1, 0, 0;\n}\n"
    : "+f"(d[0]), "+f"(d[1]), "+f"(d[2]), "+f"(d[3]), "+f"(d[4]), "+f"(d[5]), "+f"(d[6]), "+f"(d[7])
    : "l"(da), "l"(db), "r"(scale_d));
}
__device__ __forceinline__ void wgmma_pvT(float (&d)[8], uint64_t da, uint64_t db, int scale_d) {
  asm volatile("{\n.reg .pred p;\nsetp.ne.b32 p, %10, 0;\n"
    "wgmma.mma_async.sync.aligned.m64n16k16.f32.bf16.bf16 "
    "{%0, %1, %2, %3, %4, %5, %6, %7}, "
    "%8, %9, p, 1, 1, 1, 0;\n}\n"
    : "+f"(d[0]), "+f"(d[1]), "+f"(d[2]), "+f"(d[3]), "+f"(d[4]), "+f"(d[5]), "+f"(d[6]), "+f"(d[7])
    : "l"(da), "l"(db), "r"(scale_d));
}

__device__ __forceinline__ void wgmma_qk0(float (&d)[32], uint32_t a0, uint32_t a1, uint32_t a2, uint32_t a3, uint64_t db) {
  asm volatile("{\n.reg .pred p;\nsetp.ne.b32 p, 0, 0;\n"
    "wgmma.mma_async.sync.aligned.m64n64k16.f32.bf16.bf16 "
    "{%0, %1, %2, %3, %4, %5, %6, %7, %8, %9, %10, %11, %12, %13, %14, %15, %16, %17, %18, %19, %20, %21, %22, %23, %24, %25, %26, %27, %28, %29, %30, %31}, "
    "{%32, %33, %34, %35}, %36, p, 1, 1, 0;\n}\n"
    : "=f"(d[0]), "=f"(d[1]), "=f"(d[2]), "=f"(d[3]), "=f"(d[4]), "=f"(d[5]), "=f"(d[6]), "=f"(d[7]), "=f"(d[8]), "=f"(d[9]), "=f"(d[10]), "=f"(d[11]), "=f"(d[12]), "=f"(d[13]), "=f"(d[14]), "=f"(d[15]), "=f"(d[16]), "=f"(d[17]), "=f"(d[18]), "=f"(d[19]), "=f"(d[20]), "=f"(d[21]), "=f"(d[22]), "=f"(d[23]), "=f"(d[24]), "=f"(d[25]), "=f"(d[26]), "=f"(d[27]), "=f"(d[28]), "=f"(d[29]), "=f"(d[30]), "=f"(d[31])
    : "r"(a0), "r"(a1), "r"(a2), "r"(a3), "l"(db));
}
__device__ __forceinline__ void wgmma_pv0(float (&d)[96], uint32_t a0, uint32_t a1, uint32_t a2, uint32_t a3, uint64_t db) {
  asm volatile("{\n.reg .pred p;\nsetp.ne.b32 p, 0, 0;\n"
    "wgmma.mma_async.sync.aligned.m64n192k16.f32.bf16.bf16 "
    "{%0, %1, %2, %3, %4, %5, %6, %7, %8, %9, %10, %11, %12, %13, %14, %15, %16, %17, %18, %19, %20, %21, %22, %23, %24, %25, %26, %27, %28, %29, %30, %31, %32, %33, %34, %35, %36, %37, %38, %39, %40, %41, %42, %43, %44, %45, %46, %47, %48, %49, %50, %51, %52, %53, %54, %55, %56, %57, %58, %59, %60, %61, %62, %63, %64, %65, %66, %67, %68, %69, %70, %71, %72, %73, %74, %75, %76, %77, %78, %79, %80, %81, %82, %83, %84, %85, %86, %87, %88, %89, %90, %91, %92, %93, %94, %95}, "
    "{%96, %97, %98, %99}, %100, p, 1, 1, 1;\n}\n"
    : "=f"(d[0]), "=f"(d[1]), "=f"(d[2]), "=f"(d[3]), "=f"(d[4]), "=f"(d[5]), "=f"(d[6]), "=f"(d[7]), "=f"(d[8]), "=f"(d[9]), "=f"(d[10]), "=f"(d[11]), "=f"(d[12]), "=f"(d[13]), "=f"(d[14]), "=f"(d[15]), "=f"(d[16]), "=f"(d[17]), "=f"(d[18]), "=f"(d[19]), "=f"(d[20]), "=f"(d[21]), "=f"(d[22]), "=f"(d[23]), "=f"(d[24]), "=f"(d[25]), "=f"(d[26]), "=f"(d[27]), "=f"(d[28]), "=f"(d[29]), "=f"(d[30]), "=f"(d[31]), "=f"(d[32]), "=f"(d[33]), "=f"(d[34]), "=f"(d[35]), "=f"(d[36]), "=f"(d[37]), "=f"(d[38]), "=f"(d[39]), "=f"(d[40]), "=f"(d[41]), "=f"(d[42]), "=f"(d[43]), "=f"(d[44]), "=f"(d[45]), "=f"(d[46]), "=f"(d[47]), "=f"(d[48]), "=f"(d[49]), "=f"(d[50]), "=f"(d[51]), "=f"(d[52]), "=f"(d[53]), "=f"(d[54]), "=f"(d[55]), "=f"(d[56]), "=f"(d[57]), "=f"(d[58]), "=f"(d[59]), "=f"(d[60]), "=f"(d[61]), "=f"(d[62]), "=f"(d[63]), "=f"(d[64]), "=f"(d[65]), "=f"(d[66]), "=f"(d[67]), "=f"(d[68]), "=f"(d[69]), "=f"(d[70]), "=f"(d[71]), "=f"(d[72]), "=f"(d[73]), "=f"(d[74]), "=f"(d[75]), "=f"(d[76]), "=f"(d[77]), "=f"(d[78]), "=f"(d[79]), "=f"(d[80]), "=f"(d[81]), "=f"(d[82]), "=f"(d[83]), "=f"(d[84]), "=f"(d[85]), "=f"(d[86]), "=f"(d[87]), "=f"(d[88]), "=f"(d[89]), "=f"(d[90]), "=f"(d[91]), "=f"(d[92]), "=f"(d[93]), "=f"(d[94]), "=f"(d[95])
    : "r"(a0), "r"(a1), "r"(a2), "r"(a3), "l"(db));
}
__device__ __forceinline__ void wgmma_qkT0(float (&d)[8], uint64_t da, uint64_t db) {
  asm volatile("{\n.reg .pred p;\nsetp.ne.b32 p, 0, 0;\n"
    "wgmma.mma_async.sync.aligned.m64n16k16.f32.bf16.bf16 "
    "{%0, %1, %2, %3, %4, %5, %6, %7}, "
    "%8, %9, p, 1, 1, 0, 0;\n}\n"
    : "=f"(d[0]), "=f"(d[1]), "=f"(d[2]), "=f"(d[3]), "=f"(d[4]), "=f"(d[5]), "=f"(d[6]), "=f"(d[7])
    : "l"(da), "l"(db));
}
__device__ __forceinline__ void wgmma_pvT0(float (&d)[8], uint64_t da, uint64_t db) {
  asm volatile("{\n.reg .pred p;\nsetp.ne.b32 p, 0, 0;\n"
    "wgmma.mma_async.sync.aligned.m64n16k16.f32.bf16.bf16 "
    "{%0, %1, %2, %3, %4, %5, %6, %7}, "
    "%8, %9, p, 1, 1, 1, 0;\n}\n"
    : "=f"(d[0]), "=f"(d[1]), "=f"(d[2]), "=f"(d[3]), "=f"(d[4]), "=f"(d[5]), "=f"(d[6]), "=f"(d[7])
    : "l"(da), "l"(db));
}

struct Round { int head, qrow, mc; };
__device__ __forceinline__ Round decode_round(int g, int rank) {
  int p = g / 7, r = g - p * 7;
  Round o;
  if (r < 3) { o.head = 2 * p; o.qrow = r * 256 + rank * 128; o.mc = 1; }
  else if (r == 3) { o.head = 2 * p + rank; o.qrow = 768; o.mc = 0; }
  else { o.head = 2 * p + 1; o.qrow = (r - 4) * 256 + rank * 128; o.mc = 1; }
  return o;
}

__device__ __forceinline__ uint32_t kdesc0(uint32_t s_kv) { return ((s_kv & 0x3FFFFu) >> 4) | (1u << 16); }
__device__ __forceinline__ uint32_t vdesc0(uint32_t s_kv) { return ((s_kv & 0x3FFFFu) >> 4) | ((uint32_t)(SLAB >> 4) << 16); }
constexpr uint64_t DESC_HI = ((uint64_t)(RGRP >> 4) << 32) | ((uint64_t)1 << 62);
constexpr uint64_t DESC_HI_PT = ((uint64_t)(1024 >> 4) << 32) | ((uint64_t)1 << 62);

__device__ __forceinline__ void issue_qk(float (&S)[32], const uint32_t (&Q)[48], uint32_t kdesc) {
  const uint64_t d = DESC_HI | kdesc;
  wgmma_qk0(S, Q[0], Q[1], Q[2], Q[3], d);
#pragma unroll
  for (int kk = 1; kk < 12; kk++)
    wgmma_qk(S, Q[kk * 4], Q[kk * 4 + 1], Q[kk * 4 + 2], Q[kk * 4 + 3], d + (uint64_t)((kk / 4) * (SLAB / 16) + (kk % 4) * 2), 1);
}
__device__ __forceinline__ void issue_qk32(float (&S)[32], const uint32_t (&Q)[48], uint32_t kdesc) {
  uint32_t d[12];
#pragma unroll
  for (int kk = 0; kk < 12; kk++) {
    d[kk] = kdesc + ((kk / 4) * (SLAB / 16) + (kk % 4) * 2);
    asm volatile("" : "+r"(d[kk]));
  }
  wgmma_qk0(S, Q[0], Q[1], Q[2], Q[3], DESC_HI | d[0]);
#pragma unroll
  for (int kk = 1; kk < 12; kk++) wgmma_qk(S, Q[kk * 4], Q[kk * 4 + 1], Q[kk * 4 + 2], Q[kk * 4 + 3], DESC_HI | d[kk], 1);
}
__device__ __forceinline__ void issue_qk3(float (&S)[32], const uint32_t (&Q)[48], uint32_t kdesc) {
  const uint64_t d = DESC_HI | kdesc;
  wgmma_qk0(S, Q[0], Q[1], Q[2], Q[3], d);
#pragma unroll
  for (int kk = 1; kk < 12; kk++) {
    if (kk % 4 == 0) wg_commit();
    wgmma_qk(S, Q[kk * 4], Q[kk * 4 + 1], Q[kk * 4 + 2], Q[kk * 4 + 3], d + (uint64_t)((kk / 4) * (SLAB / 16) + (kk % 4) * 2), 1);
  }
}
template <bool ACCUMULATE>
__device__ __forceinline__ void issue_pv(float (&O)[96], const uint32_t (&P)[16], uint32_t vdesc) {
  const uint64_t d = DESC_HI | vdesc;
  if (ACCUMULATE) wgmma_pv(O, P[0], P[1], P[2], P[3], d, 1);
  else wgmma_pv0(O, P[0], P[1], P[2], P[3], d);
#pragma unroll
  for (int kk = 1; kk < 4; kk++)
    wgmma_pv(O, P[kk * 4], P[kk * 4 + 1], P[kk * 4 + 2], P[kk * 4 + 3], d + (uint64_t)(kk * (2 * RGRP / 16)), 1);
}

template <int K0 = 0, int K1 = 12>
__device__ __forceinline__ void load_q(uint32_t (&Q)[48], uint32_t lane_addr) {
#pragma unroll
  for (int kk = K0; kk < K1; kk++)
    ldsm_x4((lane_addr ^ ((kk % 4) << 5)) + (kk / 4) * SLAB, Q[kk * 4], Q[kk * 4 + 1], Q[kk * 4 + 2], Q[kk * 4 + 3]);
}

__device__ __forceinline__ void softmax_block(const float (&S)[32], uint32_t (&P)[16], float& l0, float& l1) {
#pragma unroll
  for (int i = 0; i < 8; i++) {
    const float a = ex2(S[4 * i + 0] * SCALE_LOG2);
    const float b = ex2(S[4 * i + 1] * SCALE_LOG2);
    const float c = ex2(S[4 * i + 2] * SCALE_LOG2);
    const float d = ex2(S[4 * i + 3] * SCALE_LOG2);
    l0 += a + b;
    l1 += c + d;
    P[2 * i] = pack_bf16(a, b);
    P[2 * i + 1] = pack_bf16(c, d);
  }
  fence_regs(P);
}

__device__ __forceinline__ void sums_put(uint32_t addr, float l0, float l1, uint32_t on) {
  asm volatile("{\n.reg .pred p;\nsetp.ne.u32 p, %3, 0;\n@p st.shared.v2.f32 [%0], {%1, %2};\n}\n" ::"r"(addr), "f"(l0), "f"(l1), "r"(on) : "memory");
}
__device__ __forceinline__ void sums_get(uint32_t addr, float& s0, float& s1) {
  float a, b, c, d, e, f, g, h;
  asm volatile("ld.shared.v4.f32 {%0, %1, %2, %3}, [%8];\nld.shared.v4.f32 {%4, %5, %6, %7}, [%8 + 16];\n"
               : "=f"(a), "=f"(b), "=f"(c), "=f"(d), "=f"(e), "=f"(f), "=f"(g), "=f"(h) : "r"(addr & ~31u) : "memory");
  s0 = (a + c) + (e + g);
  s1 = (b + d) + (f + h);
}

template <int K0, int K1>
__device__ __forceinline__ void epilogue_part(const float (&O)[96], float i0, float i1, uint32_t lane_addr) {
#pragma unroll
  for (int kk = K0; kk < K1; kk++) {
    const int b = kk * 8;
    stsm_x4((lane_addr ^ ((kk % 4) << 5)) + (kk / 4) * SLAB,
            pack_bf16(O[b] * i0, O[b + 1] * i0), pack_bf16(O[b + 2] * i1, O[b + 3] * i1),
            pack_bf16(O[b + 4] * i0, O[b + 5] * i0), pack_bf16(O[b + 6] * i1, O[b + 7] * i1));
  }
}
__device__ __forceinline__ void epilogue_done(uint32_t bar, int lane) {
  __syncwarp();
  if (lane == 0) mbar_arrive(bar);
}

__device__ __forceinline__ void redo_tile(const CUtensorMap* tmQ, const CUtensorMap* tmK, const CUtensorMap* tmV, const CUtensorMap* tmO,
                                          int head, int row, uint32_t qo, uint32_t kv, uint32_t lane_addr, uint32_t bar, uint32_t& phase,
                                          uint32_t wg_bar) {
  float O[96], S[32];
  uint32_t Q[48], P[16];
  uint64_t pol;
  asm volatile("createpolicy.fractional.L2::evict_normal.b64 %0, 1.0;" : "=l"(pol));
  const bool leader = (threadIdx.x & 127) == 0;
  if (leader) {
    mbar_expect_tx(bar, SLOT);
    tma_load(qo, tmQ, bar, row, head, pol);
  }
  mbar_wait(bar, phase);
  phase ^= 1;
  load_q(Q, lane_addr);
  float m0 = -INFINITY, m1 = -INFINITY, l0 = 0.f, l1 = 0.f;
#pragma unroll
  for (int i = 0; i < 96; i++) O[i] = 0.f;
#pragma unroll 1
  for (int j = 0; j < NBLK; j++) {
    asm volatile("bar.sync %0, 128;" ::"r"(wg_bar) : "memory");
    if (leader) {
      mbar_expect_tx(bar, 2 * SLOT);
      tma_load(kv, tmK, bar, j * BN, head, pol);
      tma_load(kv + SLOT, tmV, bar, j * BN, head, pol);
    }
    mbar_wait(bar, phase);
    phase ^= 1;
    wg_fence();
    issue_qk(S, Q, kdesc0(kv));
    wg_commit();
    wg_wait<0>();
    fence_regs(S);
    float n0 = m0, n1 = m1;
#pragma unroll
    for (int i = 0; i < 8; i++) {
      n0 = fmaxf(n0, fmaxf(S[4 * i], S[4 * i + 1]));
      n1 = fmaxf(n1, fmaxf(S[4 * i + 2], S[4 * i + 3]));
    }
#pragma unroll
    for (int o = 1; o < 4; o <<= 1) {
      n0 = fmaxf(n0, __shfl_xor_sync(0xffffffffu, n0, o));
      n1 = fmaxf(n1, __shfl_xor_sync(0xffffffffu, n1, o));
    }
    const float f0 = ex2((m0 - n0) * SCALE_LOG2), f1 = ex2((m1 - n1) * SCALE_LOG2);
    m0 = n0; m1 = n1;
    l0 *= f0; l1 *= f1;
#pragma unroll
    for (int i = 0; i < 24; i++) {
      O[4 * i] *= f0; O[4 * i + 1] *= f0; O[4 * i + 2] *= f1; O[4 * i + 3] *= f1;
    }
#pragma unroll
    for (int i = 0; i < 8; i++) {
      S[4 * i] -= m0; S[4 * i + 1] -= m0; S[4 * i + 2] -= m1; S[4 * i + 3] -= m1;
    }
    softmax_block(S, P, l0, l1);
    fence_regs(O);
    wg_fence();
    issue_pv<true>(O, P, vdesc0(kv + SLOT));
    wg_commit();
    wg_wait<0>();
    fence_regs(O);
  }
#pragma unroll
  for (int o = 1; o < 4; o <<= 1) {
    l0 += __shfl_xor_sync(0xffffffffu, l0, o);
    l1 += __shfl_xor_sync(0xffffffffu, l1, o);
  }
  epilogue_part<0, 12>(O, rcp(l0), rcp(l1), lane_addr);
  asm volatile("fence.proxy.async.shared::cta;" ::: "memory");
  asm volatile("bar.sync %0, 128;" ::"r"(wg_bar) : "memory");
  if (leader) {
    for (int i = 0; i < 64 && row + i < SQ; i += OROWS) tma_store(tmO, qo + i / 8 * RGRP, row + i, head, pol);
    asm volatile("cp.async.bulk.commit_group;" ::: "memory");
    asm volatile("cp.async.bulk.wait_group 0;" ::: "memory");
  }
}

__device__ __forceinline__ void wg_barrier() { asm volatile("bar.sync 3, 128;" ::: "memory"); }

__device__ __forceinline__ void tail_reduce(float (&v)[4], uint32_t red, int warp, int lane) {
#pragma unroll
  for (int o = 4; o < 32; o <<= 1)
#pragma unroll
    for (int i = 0; i < 4; i++) v[i] += __shfl_xor_sync(0xffffffffu, v[i], o);
  if (lane < 4)
    asm volatile("st.shared.v4.f32 [%0], {%1, %2, %3, %4};" ::"r"(red + (warp * 4 + lane) * 16), "f"(v[0]), "f"(v[1]), "f"(v[2]), "f"(v[3]) : "memory");
  wg_barrier();
#pragma unroll
  for (int ww = 0; ww < 4; ww++) {
    float x0, x1, x2, x3;
    asm volatile("ld.shared.v4.f32 {%0, %1, %2, %3}, [%4];" : "=f"(x0), "=f"(x1), "=f"(x2), "=f"(x3) : "r"(red + (ww * 4 + (lane & 3)) * 16) : "memory");
    if (ww == 0) { v[0] = x0; v[1] = x1; v[2] = x2; v[3] = x3; }
    else { v[0] += x0; v[1] += x1; v[2] += x2; v[3] += x3; }
  }
}

__device__ __forceinline__ void tail_softmax(const float (&S)[8], float (&l)[4], uint32_t pt_addr) {
  float e[8];
#pragma unroll
  for (int i = 0; i < 8; i++) e[i] = ex2(S[i] * SCALE_LOG2);
  stsm_x4_trans(pt_addr, pack_bf16(e[0], e[1]), pack_bf16(e[2], e[3]), pack_bf16(e[4], e[5]), pack_bf16(e[6], e[7]));
  asm volatile("fence.proxy.async.shared::cta;" ::: "memory");
  l[0] += e[0] + e[2]; l[1] += e[1] + e[3]; l[2] += e[4] + e[6]; l[3] += e[5] + e[7];
  wg_barrier();
}

__device__ __forceinline__ void issue_qkT(float (&S8)[8], uint32_t kdesc, uint32_t qt_addr) {
  const uint64_t da = DESC_HI | kdesc;
  const uint64_t db = DESC_HI | (uint64_t)(((qt_addr & 0x3FFFFu) >> 4) | (1u << 16));
  wgmma_qkT0(S8, da, db);
#pragma unroll
  for (int kk = 1; kk < 12; kk++)
    wgmma_qkT(S8, da + (uint64_t)((kk / 4) * (SLAB / 16) + (kk % 4) * 2), db + (uint64_t)((kk / 4) * (SLAB / 16) + (kk % 4) * 2), 1);
}
template <bool ACCUMULATE>
__device__ __forceinline__ void issue_pvT(float (&O)[3][8], uint32_t vdesc, uint32_t pt_base) {
  const uint64_t da = DESC_HI | vdesc;
  const uint64_t db = DESC_HI_PT | (uint64_t)(((pt_base & 0x3FFFFu) >> 4) | (1u << 16));
#pragma unroll
  for (int kk = 0; kk < 4; kk++)
#pragma unroll
    for (int b = 0; b < 3; b++) {
      if (kk == 0 && !ACCUMULATE) wgmma_pvT0(O[b], da + (uint64_t)(b * (SLAB / 16)), db);
      else wgmma_pvT(O[b], da + (uint64_t)(b * (SLAB / 16) + kk * (2 * RGRP / 16)), db + (uint64_t)(kk * 2), 1);
    }
}

template <bool B> struct Bool { static constexpr bool value = B; };

constexpr int MAX_CLUSTERS = 72;
constexpr int MAX_ROUNDS = 32;
struct Schedule {
  uint32_t first[MAX_CLUSTERS];
  uint32_t tails[MAX_CLUSTERS];
  uint16_t start[MAX_CLUSTERS + 1];
  uint16_t list[NROUNDS + 1];
};

#define TRACE_TILE()

__global__ void __cluster_dims__(2, 1, 1) __launch_bounds__(NTHREADS, 1)
attn_kernel(const __grid_constant__ CUtensorMap tmQ, const __grid_constant__ CUtensorMap tmQT, const __grid_constant__ CUtensorMap tmK,
            const __grid_constant__ CUtensorMap tmV, const __grid_constant__ CUtensorMap tmO, const __grid_constant__ Schedule sched) {
  extern __shared__ __align__(1024) uint8_t smem_raw[];
  const uint32_t c_entry = (uint32_t)clock();
  const uint32_t sbase = smem_u32(smem_raw);
  const uint32_t s_qo = sbase + OFF_QO;
  const uint32_t s_kv = sbase + OFF_KV;
  const uint32_t s_bar = sbase + OFF_BAR;
  const uint32_t bar_full = s_bar;
  const uint32_t bar_empty = s_bar + 8 * NSLOT;
  const uint32_t bar_qfull = s_bar + 16 * NSLOT;
  const uint32_t bar_ostg = bar_qfull + 16;
  const uint32_t bar_qreq = bar_ostg + 16;
  const uint32_t bar_redo = bar_qreq + 16;
  const uint32_t s_redo = bar_redo + 16;

  uint32_t rank;
  asm("mov.u32 %0, %%cluster_ctarank;" : "=r"(rank));
  const int cluster = blockIdx.x >> 1;
  const int first_round = sched.start[cluster];
  const int nrounds = sched.start[cluster + 1] - first_round;
  const int nblocks = nrounds * NBLK;

  if (threadIdx.x == 32) {
    asm volatile("prefetch.tensormap [%0];" ::"l"(&tmK) : "memory");
    asm volatile("prefetch.tensormap [%0];" ::"l"(&tmQ) : "memory");
    asm volatile("prefetch.tensormap [%0];" ::"l"(&tmV) : "memory");
  }
  if (threadIdx.x == 0) {
    for (int i = 0; i < NSLOT; i++) {
      mbar_init(bar_full + 8 * i, 1);
      mbar_init(bar_empty + 8 * i, 4);
    }
    for (int i = 0; i < 2; i++) {
      mbar_init(bar_qfull + 8 * i, 1);
      mbar_init(bar_ostg + 8 * i, 4);
      mbar_init(bar_qreq + 8 * i, 2);
      mbar_init(bar_redo + 8 * i, 1);
      asm volatile("st.shared.u32 [%0], %1;" ::"r"(s_redo + 4 * i), "r"(0) : "memory");
    }
    asm volatile("fence.mbarrier_init.release.cluster;" ::: "memory");
    asm volatile("fence.proxy.async.shared::cta;" ::: "memory");
    const uint32_t e = sched.first[cluster];
    const Round r = decode_round(e & 0x7ff, rank);
    uint64_t polq, polk;
    asm volatile("createpolicy.fractional.L2::evict_first.b64 %0, 1.0;" : "=l"(polq));
    asm volatile("createpolicy.fractional.L2::evict_unchanged.b64 %0, 1.0;" : "=l"(polk));
    while ((uint32_t)clock() - c_entry < (e >> 16)) {}
    mbar_expect_tx(bar_full, SLOT);
    tma_load(s_kv, &tmK, bar_full, 0, r.head, polk);
    mbar_expect_tx(bar_qfull, SLOT);
    tma_load(s_qo, &tmQ, bar_qfull, r.qrow, r.head, polq);
    mbar_expect_tx(bar_full + 8, SLOT);
    tma_load(s_kv + SLOT, &tmK, bar_full + 8, BN, r.head, polk);
    mbar_expect_tx(bar_full + 16, SLOT);
    tma_load(s_kv + 2 * SLOT, &tmV, bar_full + 16, 0, r.head, polk);
    mbar_expect_tx(bar_qfull + 8, SLOT);
    tma_load(s_qo + SLOT, &tmQ, bar_qfull + 8, r.qrow + 64, r.head, polq);
  }
  __syncthreads();
  asm volatile("barrier.cluster.arrive.relaxed.aligned;\nbarrier.cluster.wait.aligned;" ::: "memory");

  const int wg = __shfl_sync(0xffffffffu, threadIdx.x >> 7, 0);
  const int warp = __shfl_sync(0xffffffffu, (threadIdx.x >> 5) & 3, 0);
  const int lane = threadIdx.x & 31;

  if (wg == 0) {
    asm volatile("setmaxnreg.dec.sync.aligned.u32 24;");
    if (warp == 0 && lane == 0) {
      uint64_t pol;
      asm volatile("createpolicy.fractional.L2::evict_unchanged.b64 %0, 1.0;" : "=l"(pol));
      uint32_t slot = 3, phase = 1;
      auto load = [&](const CUtensorMap* tm, int n, uint32_t owner) {
        const Round r = decode_round(sched.list[first_round + (n >> 3)] & 0x7ff, rank);
        mbar_wait_sleep(bar_empty + 8 * slot, phase);
        if (n < nblocks) {
          mbar_expect_tx(bar_full + 8 * slot, SLOT);
          if (!r.mc) tma_load(s_kv + slot * SLOT, tm, bar_full + 8 * slot, (n & 7) * BN, r.head, pol);
          else if (rank == owner) tma_load_mc(s_kv + slot * SLOT, tm, bar_full + 8 * slot, (n & 7) * BN, r.head, pol);
        }
        if (++slot == NSLOT) { slot = 0; phase ^= 1; }
      };
      for (int n = 1; n < nblocks; n++) {
        load(&tmK, n + 1, 0);
        load(&tmV, n, 1);
      }
      for (int i = 0; i < NSLOT; i++) {
        if (i != NSLOT - 2) mbar_wait_sleep(bar_empty + 8 * slot, phase);
        if (++slot == NSLOT) { slot = 0; phase ^= 1; }
      }
    } else if ((warp == 1 || warp == 2) && lane == 0) {
      const int w = warp - 1;
      uint64_t pol;
      asm volatile("createpolicy.fractional.L2::evict_first.b64 %0, 1.0;" : "=l"(pol));
      const uint32_t buf = s_qo + w * SLOT;
      Round r = decode_round(sched.list[first_round] & 0x7ff, rank);
      Round prev = r;
      for (int t = 0; t <= nrounds; t++) {
        mbar_wait_sleep(bar_ostg + 8 * w, t & 1);
        if (t > 0) {
          asm volatile("fence.proxy.async.shared::cta;" ::: "memory");
          const int row0 = prev.qrow + w * 64;
          const int nrows = row0 + 64 <= SQ ? 64 : SQ - row0;
#pragma unroll 1
          for (int i = 0; i < nrows; i += OROWS) {
            tma_store(&tmO, buf + i / 8 * RGRP, row0 + i, prev.head, pol);
            asm volatile("cp.async.bulk.commit_group;" ::: "memory");
            if (t < nrounds) asm volatile("cp.async.bulk.wait_group.read 0;" ::: "memory");
          }
          prev = r;
        }
        if (t + 1 < nrounds) {
          mbar_wait_sleep(bar_qreq + 8 * w, t & 1);
          const uint32_t e = sched.list[first_round + t + 1];
          r = decode_round(e & 0x7ff, rank);
          if (w == 1 && (e & 0x8000)) {
            mbar_expect_tx(bar_qfull + 8 * w, 3 * 2048);
            tma_load(sbase + OFF_QT, &tmQT, bar_qfull + 8 * w, r.qrow + 64, r.head, pol);
          } else {
            mbar_expect_tx(bar_qfull + 8 * w, SLOT);
            tma_load(buf, &tmQ, bar_qfull + 8 * w, r.qrow + w * 64, r.head, pol);
          }
        } else if (t < nrounds) {
          mbar_arrive(bar_qfull + 8 * w);
        }
      }
      asm volatile("cp.async.bulk.wait_group 0;" ::: "memory");
      mbar_arrive(bar_redo + 8 * w);
    } else if (warp == 3) {
      uint32_t slot = 1, phase = 0;
      for (int n = 0; n < nblocks; n++) {
        if (n + 1 < nblocks) mbar_wait(bar_full + 8 * slot, phase);
        if (++slot == NSLOT) { slot = 0; phase ^= 1; }
        mbar_wait(bar_full + 8 * slot, phase);
        if (++slot == NSLOT) { slot = 0; phase ^= 1; }
        asm volatile("bar.sync 1, 288;" ::: "memory");
        asm volatile("bar.arrive 2, 288;" ::: "memory");
        TRACE_TILE();
      }
    }
  } else {
    asm volatile("setmaxnreg.inc.sync.aligned.u32 240;");
    const int w = wg - 1;
    float O[96], S[32];
    uint32_t Q[48], P0[16], P1[16];
    float l0 = 0.f, l1 = 0.f, inv0 = 0.f, inv1 = 0.f;
    uint32_t redo = 0;
    const uint32_t lane_addr = s_qo + w * SLOT + (warp * 2 + ((lane >> 3) & 1)) * RGRP + (lane & 7) * 128 + (((lane >> 4) ^ (lane & 7)) << 4);
    const uint32_t sum_addr = s_qo + w * SLOT + warp * 2 * RGRP + lane * 8;
    const uint32_t my_qfull = bar_qfull + 8 * w, my_ostg = bar_ostg + 8 * w;

    uint32_t empty_remote;
    asm("mapa.shared::cluster.u32 %0, %1, %2;" : "=r"(empty_remote) : "r"(bar_empty), "r"(threadIdx.x & 1));
    const bool releaser = (threadIdx.x & 127) < 2;
    auto release = [&](uint32_t s) {
      if (releaser) asm volatile("mbarrier.arrive.shared::cluster.b64 _, [%0];" ::"r"(empty_remote + s) : "memory");
    };
    uint32_t ks = 8, vs = 16, kp = 0, vp = 0;
    const uint32_t kd0 = kdesc0(s_kv), vd0 = vdesc0(s_kv);
    uint32_t kd = kd0 + ks * (SLOT / 128), vd = vd0 + vs * (SLOT / 128);
    auto advance = [&]() {
      kp = ks; vp = vs;
      ks = ks >= 8 * (NSLOT - 2) ? ks - 8 * (NSLOT - 2) : ks + 16;
      vs = vs >= 8 * (NSLOT - 2) ? vs - 8 * (NSLOT - 2) : vs + 16;
      kd = kd0 + ks * (SLOT / 128); vd = vd0 + vs * (SLOT / 128);
      asm volatile("" : "+r"(ks), "+r"(vs), "+r"(kd), "+r"(vd));
    };

    uint32_t tails = w == 1 ? sched.tails[cluster] : 0u;
    auto turn_wait = [&]() { asm volatile("bar.sync %0, 288;" ::"r"(1 + w) : "memory"); };
    auto turn_pass = [&]() { asm volatile("bar.arrive %0, 288;" ::"r"(2 - w) : "memory"); };
    if (w == 1) turn_pass();

    mbar_wait(my_qfull, 0);
    load_q(Q, lane_addr);
    mbar_wait(bar_full, 0);
    wg_fence();
    issue_qk(S, Q, kd0);
    wg_commit();
    wg_wait<0>();
    fence_regs(S);
    release(0);
    __syncwarp();
    if (lane == 0) mbar_arrive(my_ostg);
    bool pending = false;

    int n = 0;
    auto finish_sums = [&]() {
      float s0, s1;
      sums_get(sum_addr, s0, s1);
      if (!(sum_ok(s0) && sum_ok(s1))) redo |= 1u << ((n >> 3) & 31);
      inv0 = rcp(s0); inv1 = rcp(s1);
      l0 = l1 = 0.f;
      asm volatile("" : "+f"(inv0), "+f"(inv1), "+r"(redo)::"memory");
    };

    int exit_n = -1;
#pragma unroll 1
    while (true) {
#pragma unroll 1
      while (true) {
        const int j = n & 7;
        softmax_block(S, P0, l0, l1);
        asm volatile("" : "+f"(l0), "+f"(l1)::"memory");
        if (j != 0) {
          wg_wait<0>();
          release(vp);
          turn_wait();
          wg_fence();
          issue_qk3(S, Q, kd);
          wg_commit();
          issue_pv<true>(O, P0, vd);
          wg_commit();
          turn_pass();
          advance();
          if (!(QDELAY & 1) && j == QDELAY && releaser) mbar_arrive(bar_qreq + 8 * w);
          if (j == 6) {
            mbar_wait(my_qfull, ((n >> 3) + 1) & 1);
            wg_wait<3>();
            load_q<0, 4>(Q, lane_addr);
            wg_wait<2>();
            load_q<4, 8>(Q, lane_addr);
          }
          wg_wait<1>();
          fence_regs(S);
          fence_regs(P1);
        } else {
          wg_wait<0>();
          fence_regs(O);
          fence_regs(P1);
          if (pending) {
            release(vp);
            epilogue_part<0, ESPLIT>(O, inv0, inv1, lane_addr);
          }
          turn_wait();
          wg_fence();
          issue_qk32(S, Q, kd);
          wg_commit();
          if (pending) {
            epilogue_part<ESPLIT, 12>(O, inv0, inv1, lane_addr);
            epilogue_done(my_ostg, lane);
          }
          wg_fence();
          issue_pv<false>(O, P0, vd);
          wg_commit();
          turn_pass();
          advance();
          exit_n = ((tails & 2) || n + 8 == nblocks) ? n + 6 : -1;
          tails >>= 1;
          asm volatile("" : "+r"(exit_n), "+r"(tails));
          wg_wait<1>();
          fence_regs(S);
          pending = true;
        }
        release(kp);
        if (j == 6) load_q<8, 12>(Q, lane_addr);
        softmax_block(S, P1, l0, l1);
        sums_put(sum_addr, l0, l1, j == 6);
        wg_wait<0>();
        release(vp);
        turn_wait();
        if (n == exit_n) {
          wg_fence();
          issue_pv<true>(O, P1, vd);
          wg_commit();
          break;
        }
        wg_fence();
        issue_qk(S, Q, kd);
        wg_commit();
        issue_pv<true>(O, P1, vd);
        wg_commit();
        turn_pass();
        advance();
        if ((QDELAY & 1) && j + 1 == QDELAY && releaser) mbar_arrive(bar_qreq + 8 * w);
        if (j == 6) finish_sums();
        wg_wait<1>();
        fence_regs(S);
        fence_regs(P0);
        release(kp);
        n += 2;
      }
      if (n + 2 == nblocks) {
        if (w == 0) turn_pass();
        finish_sums();
        wg_wait<0>();
        fence_regs(O);
        release(vs);
        epilogue_part<0, 12>(O, inv0, inv1, lane_addr);
        epilogue_done(my_ostg, lane);
        break;
      }
      const int t = n >> 3;
      const uint32_t qt = sbase + OFF_QT, pt = sbase + OFF_PT, red = sbase + OFF_RED;
      const uint32_t tl = ((lane & 7) + (lane >> 4) * 8) * 128 + (((warp * 2 + ((lane >> 3) & 1)) ^ (lane & 7)) << 4);
      const bool tlast = t + 2 == nrounds;
      float lt[4] = {0.f, 0.f, 0.f, 0.f};
      float ST[8], OT[3][8];
      wg_fence();
      issue_qkT(ST, kd, qt);
      wg_commit();
      turn_pass();
      finish_sums();
      wg_wait<0>();
      fence_regs(ST);
      fence_regs(O);
      release(ks);
      release(vs);
      advance();
      epilogue_part<0, 12>(O, inv0, inv1, lane_addr);
      epilogue_done(my_ostg, lane);
      auto tail_step = [&](auto first_c, int jj) {
        constexpr bool FIRST = decltype(first_c)::value;
        const uint32_t ptj = pt + (jj & 1) * 2048;
        tail_softmax(ST, lt, ptj + tl);
        turn_wait();
        wg_fence();
        issue_qkT(ST, kd, qt);
        wg_commit();
        issue_pvT<!FIRST>(OT, vd, ptj);
        wg_commit();
        turn_pass();
        if (jj == QDELAY && releaser) mbar_arrive(bar_qreq + 8 * w);
        wg_wait<1>();
        fence_regs(ST);
        release(ks);
        if (!FIRST) release(vp);
        advance();
      };
      tail_step(Bool<true>(), 0);
#pragma unroll 1
      for (int jj = 1; jj < 7; jj++) tail_step(Bool<false>(), jj);
      tail_softmax(ST, lt, pt + 2048 + tl);
      mbar_wait(my_qfull, t & 1);
      load_q(Q, lane_addr);
      tail_reduce(lt, red, warp, lane);
      if (!(sum_ok(lt[0]) && sum_ok(lt[1]) && sum_ok(lt[2]) && sum_ok(lt[3]))) redo |= 1u << ((t + 1) & 31);
#pragma unroll
      for (int i = 0; i < 4; i++) lt[i] = rcp(lt[i]);
      wg_wait<0>();
      fence_regs(OT[0]); fence_regs(OT[1]); fence_regs(OT[2]);
      release(vp);
      turn_wait();
      wg_fence();
      issue_pvT<true>(OT, vd, pt + 2048);
      wg_commit();
      issue_qk(S, Q, kd);
      wg_commit();
      if (!tlast) turn_pass();
      wg_wait<1>();
      fence_regs(OT[0]); fence_regs(OT[1]); fence_regs(OT[2]);
      release(vs);
#pragma unroll
      for (int b = 0; b < 3; b++)
        stsm_x4_trans(s_qo + SLOT + b * SLAB + tl + (lane >> 4) * (RGRP - 1024),
                      pack_bf16(OT[b][0] * lt[0], OT[b][1] * lt[1]), pack_bf16(OT[b][2] * lt[0], OT[b][3] * lt[1]),
                      pack_bf16(OT[b][4] * lt[2], OT[b][5] * lt[3]), pack_bf16(OT[b][6] * lt[2], OT[b][7] * lt[3]));
      epilogue_done(my_ostg, lane);
      wg_wait<0>();
      fence_regs(S);
      if (tlast) break;
      release(ks);
      advance();
#pragma unroll
      for (int i = 0; i < 96; i++) O[i] = 0.f;
      pending = false;
      n += 10;
      tails >>= 1;
    }
    if (redo) asm volatile("red.shared.or.b32 [%0], %1;" ::"r"(s_redo + 4 * w), "r"(redo) : "memory");
    asm volatile("bar.sync 4, 256;" ::: "memory");
    asm volatile("ld.shared.u32 %0, [%1];" : "=r"(redo) : "r"(s_redo + 4 * w) : "memory");
    redo = __shfl_sync(0xffffffffu, redo, 0);
    if (redo) {
      mbar_wait_sleep(bar_redo + 8 * w, 0);
      asm volatile("bar.sync %0, 128;" ::"r"(5 + w) : "memory");
      uint32_t phase = 1;
#pragma unroll 1
      for (int t = 0; t < nrounds; t++) {
        if (!(redo >> (t & 31) & 1)) continue;
        const Round r = decode_round(sched.list[first_round + t] & 0x7ff, rank);
        redo_tile(&tmQ, &tmK, &tmV, &tmO, r.head, r.qrow + w * 64, s_qo + w * SLOT, s_kv + 2 * w * SLOT, lane_addr, bar_redo + 8 * w, phase, 5 + w);
      }
    }
  }
}

typedef CUresult (*EncodeFn)(CUtensorMap*, CUtensorMapDataType, cuuint32_t, void*, const cuuint64_t*, const cuuint64_t*,
                             const cuuint32_t*, const cuuint32_t*, CUtensorMapInterleave, CUtensorMapSwizzle,
                             CUtensorMapL2promotion, CUtensorMapFloatOOBfill);

void make_map(EncodeFn fn, CUtensorMap* tm, const void* ptr, int rows, int box_rows) {
  cuuint64_t dims[5] = {64, 8, 3, (cuuint64_t)rows / 8, (cuuint64_t)NHEADS};
  cuuint64_t strides[4] = {HD * 2, 128, 8 * HD * 2, (cuuint64_t)rows * HD * 2};
  cuuint32_t box[5] = {64, 8, 3, (cuuint32_t)box_rows / 8, 1};
  cuuint32_t estr[5] = {1, 1, 1, 1, 1};
  fn(tm, CU_TENSOR_MAP_DATA_TYPE_BFLOAT16, 5, const_cast<void*>(ptr), dims, strides, box, estr,
     CU_TENSOR_MAP_INTERLEAVE_NONE, CU_TENSOR_MAP_SWIZZLE_128B, CU_TENSOR_MAP_L2_PROMOTION_L2_128B, CU_TENSOR_MAP_FLOAT_OOB_FILL_NONE);
}

#define STAGGER 250
#define COST_N 12690
#define COST_T 11400
#define COST_TN 12720
#define TAIL_LATE 36
#define TAIL_MAX 60
#define HEAVY_STEP 3
void make_schedule(Schedule& s, int nclusters) {
  static uint16_t lists[MAX_CLUSTERS][NROUNDS];
  int cnt[MAX_CLUSTERS] = {0}, len[MAX_CLUSTERS], ntail[MAX_CLUSTERS] = {0}, quota[MAX_CLUSTERS] = {0};
  long long busy[MAX_CLUSTERS], fin[MAX_CLUSTERS];
  const int ntails = NROUNDS / 7, base = NROUNDS / nclusters, nheavy = NROUNDS % nclusters;
  const int step = nheavy * HEAVY_STEP <= nclusters ? HEAVY_STEP : 1;
  for (int c = 0; c < nclusters; c++) {
    len[c] = base + (c % step == 0 && c / step < nheavy);
    busy[c] = c / 3 * STAGGER;
    fin[c] = busy[c] + (long long)len[c] * COST_N;
  }
  for (int k = 0; k < ntails; k++) {
    int c = -1;
    for (int i = 0; i < nclusters; i++)
      if (quota[i] < len[i] / 2 && (c < 0 || fin[i] > fin[c])) c = i;
    quota[c]++;
    fin[c] -= 2 * COST_N - COST_T - COST_TN;
  }
  int gn = 0, gt = 3;
  for (int k = 0; k < NROUNDS; k++) {
    int c = -1;
    for (int i = 0; i < nclusters; i++)
      if (cnt[i] < len[i] && (c < 0 || busy[i] < busy[c])) c = i;
    const bool after_tail = cnt[c] > 0 && (lists[c][cnt[c] - 1] & 0x8000);
    const bool may_t = cnt[c] > 0 && !after_tail;
    const int left = len[c] - cnt[c], q = quota[c] - ntail[c];
    const bool due = (long long)(gt / 7) * quota[c] * 8 >= (long long)(ntail[c] * 8 + (c * 5 & 7)) * ntails;
    bool tail = may_t && q > 0 && (2 * q > left || (gn - gt >= TAIL_LATE && due) || gn - gt >= TAIL_MAX);
    if (4 * quota[c] >= len[c]) {
      const int m = len[c] - 1, phase = c / step * 11 % m;
      tail = may_t && q > 0 && (2 * q > left || (cnt[c] * quota[c] + phase) / m > ntail[c]);
    }
    if (gt >= NROUNDS) tail = false;
    if (gn >= NROUNDS) tail = true;
    const int g = tail ? gt : gn;
    if (tail) { gt += 7; ntail[c]++; }
    else { gn++; if (gn % 7 == 3) gn++; }
    const bool form_t = tail && may_t;
    lists[c][cnt[c]++] = (uint16_t)(g | (form_t ? 0x8000 : 0));
    busy[c] += form_t ? COST_T : after_tail ? COST_TN : COST_N;
  }
  bool use_tail = true;
  for (int c = 0; c < nclusters; c++) if (cnt[c] > MAX_ROUNDS) use_tail = false;
  if (!use_tail) for (int c = 0; c < nclusters; c++) for (int i = 0; i < cnt[c]; i++) lists[c][i] &= 0x7fff;
  int pos = 0;
  for (int c = 0; c < nclusters; c++) {
    s.start[c] = (uint16_t)pos;
    s.tails[c] = 0;
    s.first[c] = (lists[c][0] & 0x7ff) | (uint32_t)(c / 3 * STAGGER) << 16;
    for (int i = 0; i < cnt[c]; i++) {
      if (lists[c][i] & 0x8000) s.tails[c] |= 1u << i;
      s.list[pos++] = lists[c][i];
    }
  }
  for (int c = nclusters; c <= MAX_CLUSTERS; c++) s.start[c] = (uint16_t)pos;
  s.list[NROUNDS] = 0;
}

}

extern "C" void kernel_launch(void* const* d_in, const int* in_sizes, int n_in, void* d_out, int out_size) {
  static EncodeFn encode = nullptr;
  static int nclusters = 0;
  static Schedule sched;
  if (!encode) {
    void* fn = nullptr;
    cudaDriverEntryPointQueryResult qr;
    cudaGetDriverEntryPoint("cuTensorMapEncodeTiled", &fn, cudaEnableDefault, &qr);
    encode = (EncodeFn)fn;
    int dev = 0, nsm = 0;
    cudaGetDevice(&dev);
    cudaDeviceGetAttribute(&nsm, cudaDevAttrMultiProcessorCount, dev);
    nclusters = nsm / 2 < MAX_CLUSTERS ? nsm / 2 : MAX_CLUSTERS;
    make_schedule(sched, nclusters);
    cudaFuncSetAttribute(attn_kernel, cudaFuncAttributeMaxDynamicSharedMemorySize, SMEM_BYTES);
  }
  CUtensorMap tmQ, tmQT, tmK, tmV, tmO;
  make_map(encode, &tmQ, d_in[0], SQ, 64);
  make_map(encode, &tmQT, d_in[0], SQ, 16);
  make_map(encode, &tmK, d_in[1], SK, 64);
  make_map(encode, &tmV, d_in[2], SK, 64);
  make_map(encode, &tmO, d_out, SQ, OROWS);
  attn_kernel<<<2 * nclusters, NTHREADS, SMEM_BYTES>>>(tmQ, tmQT, tmK, tmV, tmO, sched);
}
```

```cpp
#include <cuda_runtime.h>
#include <cuda_bf16.h>
#include <cuda.h>
#include <stdint.h>

namespace {

constexpr int NHEADS = 512;
constexpr int SQ = 848;
constexpr int SK = 512;
constexpr int HD = 192;
constexpr int BN = 64;
constexpr int NBLK = SK / BN;
constexpr int SLOT = 64 * HD * 2;
constexpr int SLAB = 1024;
constexpr int RGRP = 3 * SLAB;
constexpr int NSLOT = 7;
constexpr int NROUNDS = (NHEADS / 2) * 7;
constexpr int NTHREADS = 384;
constexpr int OFF_QO = 0;
constexpr int OFF_KV = 2 * SLOT;
constexpr int OFF_QT = (2 + NSLOT) * SLOT;
constexpr int OFF_PT = OFF_QT + 3 * 2048;
constexpr int OFF_RED = OFF_PT + 2 * 2048;
constexpr int OFF_BAR = OFF_RED + 256;
constexpr int SMEM_BYTES = OFF_BAR + 256;

#define ESPLIT 8
#define OROWS 16
#define NT_SPLIT 4
#define QREQT 1
#define QREQ0 4
#define QREQ1 4
constexpr uint32_t WAIT_LIMIT = 1u << 18;
#define SUSPEND 20000
constexpr uint32_t SUSPEND_NS = SUSPEND;

constexpr float SCALE_LOG2 = 0.07216878364870322f * 1.4426950408889634f;
constexpr float SUM_MIN = 9.313225746154785e-10f;
constexpr float SUM_MAX = 1.152921504606847e+18f;
__device__ __forceinline__ bool sum_ok(float l) { return l >= SUM_MIN && l <= SUM_MAX; }

__device__ __forceinline__ uint32_t smem_u32(const void* p) { return (uint32_t)__cvta_generic_to_shared(p); }
__device__ __forceinline__ void wg_fence() { asm volatile("wgmma.fence.sync.aligned;" ::: "memory"); }
__device__ __forceinline__ void wg_commit() { asm volatile("wgmma.commit_group.sync.aligned;" ::: "memory"); }
template <int N> __device__ __forceinline__ void wg_wait() { asm volatile("wgmma.wait_group.sync.aligned %0;" ::"n"(N) : "memory"); }
template <int N> __device__ __forceinline__ void fence_regs(float (&r)[N]) {
#pragma unroll
  for (int i = 0; i < N; i++) asm volatile("" : "+f"(r[i])::"memory");
}
template <int N> __device__ __forceinline__ void fence_regs(uint32_t (&r)[N]) {
#pragma unroll
  for (int i = 0; i < N; i++) asm volatile("" : "+r"(r[i])::"memory");
}

__device__ __forceinline__ void mbar_init(uint32_t bar, uint32_t cnt) {
  asm volatile("mbarrier.init.shared::cta.b64 [%0], %1;" ::"r"(bar), "r"(cnt));
}
__device__ __forceinline__ void mbar_expect_tx(uint32_t bar, uint32_t bytes) {
  asm volatile("mbarrier.arrive.expect_tx.shared::cta.b64 _, [%0], %1;" ::"r"(bar), "r"(bytes) : "memory");
}
__device__ __forceinline__ void mbar_arrive(uint32_t bar) {
  asm volatile("mbarrier.arrive.shared::cta.b64 _, [%0];" ::"r"(bar) : "memory");
}
__device__ __forceinline__ bool mbar_try(uint32_t bar, uint32_t parity) {
  uint32_t ok;
  asm volatile(
      "{\n.reg .pred p;\nmbarrier.try_wait.parity.shared::cta.b64 p, [%1], %2;\nselp.b32 %0, 1, 0, p;\n}\n"
      : "=r"(ok)
      : "r"(bar), "r"(parity)
      : "memory");
  return ok;
}
__device__ __forceinline__ bool mbar_try_sleep(uint32_t bar, uint32_t parity) {
  uint32_t ok;
  asm volatile(
      "{\n.reg .pred p;\nmbarrier.try_wait.parity.shared::cta.b64 p, [%1], %2, %3;\nselp.b32 %0, 1, 0, p;\n}\n"
      : "=r"(ok)
      : "r"(bar), "r"(parity), "r"(SUSPEND_NS)
      : "memory");
  return ok;
}
__device__ __forceinline__ void mbar_wait(uint32_t bar, uint32_t parity) {
  if (mbar_try(bar, parity)) return;
  for (uint32_t n = 0; n < WAIT_LIMIT; n++)
    if (mbar_try(bar, parity)) break;
}
__device__ __forceinline__ void mbar_wait_sleep(uint32_t bar, uint32_t parity) {
  for (uint32_t n = 0; n < WAIT_LIMIT; n++) {
    if (mbar_try_sleep(bar, parity)) break;
  }
}

__device__ __forceinline__ void tma_load(uint32_t dst, const CUtensorMap* tm, uint32_t bar, int row, int head, uint64_t pol) {
  asm volatile(
      "cp.async.bulk.tensor.5d.shared::cluster.global.mbarrier::complete_tx::bytes.L2::cache_hint"
      " [%0], [%1, {%3, %3, %3, %4, %5}], [%2], %6;" ::"r"(dst),
      "l"(tm), "r"(bar), "r"(0), "r"(row >> 3), "r"(head), "l"(pol)
      : "memory");
}
__device__ __forceinline__ void tma_load_mc(uint32_t dst, const CUtensorMap* tm, uint32_t bar, int row, int head, uint64_t pol) {
  asm volatile(
      "cp.async.bulk.tensor.5d.shared::cluster.global.mbarrier::complete_tx::bytes.multicast::cluster.L2::cache_hint"
      " [%0], [%1, {%3, %3, %3, %4, %5}], [%2], %7, %6;" ::"r"(dst),
      "l"(tm), "r"(bar), "r"(0), "r"(row >> 3), "r"(head), "l"(pol), "h"((uint16_t)3)
      : "memory");
}
__device__ __forceinline__ void tma_store(const CUtensorMap* tm, uint32_t src, int row, int head, uint64_t pol) {
  asm volatile(
      "cp.async.bulk.tensor.5d.global.shared::cta.bulk_group.L2::cache_hint"
      " [%0, {%2, %2, %2, %3, %4}], [%1], %5;" ::"l"(tm),
      "r"(src), "r"(0), "r"(row >> 3), "r"(head), "l"(pol)
      : "memory");
}
__device__ __forceinline__ void ldsm_x4(uint32_t addr, uint32_t& r0, uint32_t& r1, uint32_t& r2, uint32_t& r3) {
  asm volatile("ldmatrix.sync.aligned.m8n8.x4.shared.b16 {%0, %1, %2, %3}, [%4];"
               : "=r"(r0), "=r"(r1), "=r"(r2), "=r"(r3)
               : "r"(addr)
               : "memory");
}
__device__ __forceinline__ void stsm_x4(uint32_t addr, uint32_t r0, uint32_t r1, uint32_t r2, uint32_t r3) {
  asm volatile("stmatrix.sync.aligned.m8n8.x4.shared.b16 [%0], {%1, %2, %3, %4};" ::"r"(addr), "r"(r0), "r"(r1), "r"(r2), "r"(r3)
               : "memory");
}
__device__ __forceinline__ void stsm_x4_trans(uint32_t addr, uint32_t r0, uint32_t r1, uint32_t r2, uint32_t r3) {
  asm volatile("stmatrix.sync.aligned.m8n8.x4.trans.shared.b16 [%0], {%1, %2, %3, %4};" ::"r"(addr), "r"(r0), "r"(r1), "r"(r2), "r"(r3)
               : "memory");
}
__device__ __forceinline__ float ex2(float x) {
  float y;
  asm("ex2.approx.ftz.f32 %0, %1;" : "=f"(y) : "f"(x));
  return y;
}
__device__ __forceinline__ float rcp(float x) {
  float y;
  asm("rcp.approx.ftz.f32 %0, %1;" : "=f"(y) : "f"(x));
  return y;
}
__device__ __forceinline__ uint32_t pack_bf16(float lo, float hi) {
  uint32_t r;
  asm("cvt.rn.bf16x2.f32 %0, %1, %2;" : "=r"(r) : "f"(hi), "f"(lo));
  return r;
}
__device__ __forceinline__ void wgmma_qk(float (&d)[32], uint32_t a0, uint32_t a1, uint32_t a2, uint32_t a3, uint64_t db, int scale_d) {
  asm volatile("{\n.reg .pred p;\nsetp.ne.b32 p, %37, 0;\n"
    "wgmma.mma_async.sync.aligned.m64n64k16.f32.bf16.bf16 "
    "{%0, %1, %2, %3, %4, %5, %6, %7, %8, %9, %10, %11, %12, %13, %14, %15, %16, %17, %18, %19, %20, %21, %22, %23, %24, %25, %26, %27, %28, %29, %30, %31}, "
    "{%32, %33, %34, %35}, %36, p, 1, 1, 0;\n}\n"
    : "+f"(d[0]), "+f"(d[1]), "+f"(d[2]), "+f"(d[3]), "+f"(d[4]), "+f"(d[5]), "+f"(d[6]), "+f"(d[7]), "+f"(d[8]), "+f"(d[9]), "+f"(d[10]), "+f"(d[11]), "+f"(d[12]), "+f"(d[13]), "+f"(d[14]), "+f"(d[15]), "+f"(d[16]), "+f"(d[17]), "+f"(d[18]), "+f"(d[19]), "+f"(d[20]), "+f"(d[21]), "+f"(d[22]), "+f"(d[23]), "+f"(d[24]), "+f"(d[25]), "+f"(d[26]), "+f"(d[27]), "+f"(d[28]), "+f"(d[29]), "+f"(d[30]), "+f"(d[31])
    : "r"(a0), "r"(a1), "r"(a2), "r"(a3), "l"(db), "r"(scale_d));
}

__device__ __forceinline__ void wgmma_pv(float (&d)[96], uint32_t a0, uint32_t a1, uint32_t a2, uint32_t a3, uint64_t db, int scale_d) {
  asm volatile("{\n.reg .pred p;\nsetp.ne.b32 p, %101, 0;\n"
    "wgmma.mma_async.sync.aligned.m64n192k16.f32.bf16.bf16 "
    "{%0, %1, %2, %3, %4, %5, %6, %7, %8, %9, %10, %11, %12, %13, %14, %15, %16, %17, %18, %19, %20, %21, %22, %23, %24, %25, %26, %27, %28, %29, %30, %31, %32, %33, %34, %35, %36, %37, %38, %39, %40, %41, %42, %43, %44, %45, %46, %47, %48, %49, %50, %51, %52, %53, %54, %55, %56, %57, %58, %59, %60, %61, %62, %63, %64, %65, %66, %67, %68, %69, %70, %71, %72, %73, %74, %75, %76, %77, %78, %79, %80, %81, %82, %83, %84, %85, %86, %87, %88, %89, %90, %91, %92, %93, %94, %95}, "
    "{%96, %97, %98, %99}, %100, p, 1, 1, 1;\n}\n"
    : "+f"(d[0]), "+f"(d[1]), "+f"(d[2]), "+f"(d[3]), "+f"(d[4]), "+f"(d[5]), "+f"(d[6]), "+f"(d[7]), "+f"(d[8]), "+f"(d[9]), "+f"(d[10]), "+f"(d[11]), "+f"(d[12]), "+f"(d[13]), "+f"(d[14]), "+f"(d[15]), "+f"(d[16]), "+f"(d[17]), "+f"(d[18]), "+f"(d[19]), "+f"(d[20]), "+f"(d[21]), "+f"(d[22]), "+f"(d[23]), "+f"(d[24]), "+f"(d[25]), "+f"(d[26]), "+f"(d[27]), "+f"(d[28]), "+f"(d[29]), "+f"(d[30]), "+f"(d[31]), "+f"(d[32]), "+f"(d[33]), "+f"(d[34]), "+f"(d[35]), "+f"(d[36]), "+f"(d[37]), "+f"(d[38]), "+f"(d[39]), "+f"(d[40]), "+f"(d[41]), "+f"(d[42]), "+f"(d[43]), "+f"(d[44]), "+f"(d[45]), "+f"(d[46]), "+f"(d[47]), "+f"(d[48]), "+f"(d[49]), "+f"(d[50]), "+f"(d[51]), "+f"(d[52]), "+f"(d[53]), "+f"(d[54]), "+f"(d[55]), "+f"(d[56]), "+f"(d[57]), "+f"(d[58]), "+f"(d[59]), "+f"(d[60]), "+f"(d[61]), "+f"(d[62]), "+f"(d[63]), "+f"(d[64]), "+f"(d[65]), "+f"(d[66]), "+f"(d[67]), "+f"(d[68]), "+f"(d[69]), "+f"(d[70]), "+f"(d[71]), "+f"(d[72]), "+f"(d[73]), "+f"(d[74]), "+f"(d[75]), "+f"(d[76]), "+f"(d[77]), "+f"(d[78]), "+f"(d[79]), "+f"(d[80]), "+f"(d[81]), "+f"(d[82]), "+f"(d[83]), "+f"(d[84]), "+f"(d[85]), "+f"(d[86]), "+f"(d[87]), "+f"(d[88]), "+f"(d[89]), "+f"(d[90]), "+f"(d[91]), "+f"(d[92]), "+f"(d[93]), "+f"(d[94]), "+f"(d[95])
    : "r"(a0), "r"(a1), "r"(a2), "r"(a3), "l"(db), "r"(scale_d));
}

__device__ __forceinline__ void wgmma_qkT(float (&d)[8], uint64_t da, uint64_t db, int scale_d) {
  asm volatile("{\n.reg .pred p;\nsetp.ne.b32 p, %10, 0;\n"
    "wgmma.mma_async.sync.aligned.m64n16k16.f32.bf16.bf16 "
    "{%0, %1, %2, %3, %4, %5, %6, %7}, "
    "%8, %9, p, 1, 1, 0, 0;\n}\n"
    : "+f"(d[0]), "+f"(d[1]), "+f"(d[2]), "+f"(d[3]), "+f"(d[4]), "+f"(d[5]), "+f"(d[6]), "+f"(d[7])
    : "l"(da), "l"(db), "r"(scale_d));
}
__device__ __forceinline__ void wgmma_pvT(float (&d)[8], uint64_t da, uint64_t db, int scale_d) {
  asm volatile("{\n.reg .pred p;\nsetp.ne.b32 p, %10, 0;\n"
    "wgmma.mma_async.sync.aligned.m64n16k16.f32.bf16.bf16 "
    "{%0, %1, %2, %3, %4, %5, %6, %7}, "
    "%8, %9, p, 1, 1, 1, 0;\n}\n"
    : "+f"(d[0]), "+f"(d[1]), "+f"(d[2]), "+f"(d[3]), "+f"(d[4]), "+f"(d[5]), "+f"(d[6]), "+f"(d[7])
    : "l"(da), "l"(db), "r"(scale_d));
}

__device__ __forceinline__ void wgmma_qk0(float (&d)[32], uint32_t a0, uint32_t a1, uint32_t a2, uint32_t a3, uint64_t db) {
  asm volatile("{\n.reg .pred p;\nsetp.ne.b32 p, 0, 0;\n"
    "wgmma.mma_async.sync.aligned.m64n64k16.f32.bf16.bf16 "
    "{%0, %1, %2, %3, %4, %5, %6, %7, %8, %9, %10, %11, %12, %13, %14, %15, %16, %17, %18, %19, %20, %21, %22, %23, %24, %25, %26, %27, %28, %29, %30, %31}, "
    "{%32, %33, %34, %35}, %36, p, 1, 1, 0;\n}\n"
    : "=f"(d[0]), "=f"(d[1]), "=f"(d[2]), "=f"(d[3]), "=f"(d[4]), "=f"(d[5]), "=f"(d[6]), "=f"(d[7]), "=f"(d[8]), "=f"(d[9]), "=f"(d[10]), "=f"(d[11]), "=f"(d[12]), "=f"(d[13]), "=f"(d[14]), "=f"(d[15]), "=f"(d[16]), "=f"(d[17]), "=f"(d[18]), "=f"(d[19]), "=f"(d[20]), "=f"(d[21]), "=f"(d[22]), "=f"(d[23]), "=f"(d[24]), "=f"(d[25]), "=f"(d[26]), "=f"(d[27]), "=f"(d[28]), "=f"(d[29]), "=f"(d[30]), "=f"(d[31])
    : "r"(a0), "r"(a1), "r"(a2), "r"(a3), "l"(db));
}
__device__ __forceinline__ void wgmma_pv0(float (&d)[96], uint32_t a0, uint32_t a1, uint32_t a2, uint32_t a3, uint64_t db) {
  asm volatile("{\n.reg .pred p;\nsetp.ne.b32 p, 0, 0;\n"
    "wgmma.mma_async.sync.aligned.m64n192k16.f32.bf16.bf16 "
    "{%0, %1, %2, %3, %4, %5, %6, %7, %8, %9, %10, %11, %12, %13, %14, %15, %16, %17, %18, %19, %20, %21, %22, %23, %24, %25, %26, %27, %28, %29, %30, %31, %32, %33, %34, %35, %36, %37, %38, %39, %40, %41, %42, %43, %44, %45, %46, %47, %48, %49, %50, %51, %52, %53, %54, %55, %56, %57, %58, %59, %60, %61, %62, %63, %64, %65, %66, %67, %68, %69, %70, %71, %72, %73, %74, %75, %76, %77, %78, %79, %80, %81, %82, %83, %84, %85, %86, %87, %88, %89, %90, %91, %92, %93, %94, %95}, "
    "{%96, %97, %98, %99}, %100, p, 1, 1, 1;\n}\n"
    : "=f"(d[0]), "=f"(d[1]), "=f"(d[2]), "=f"(d[3]), "=f"(d[4]), "=f"(d[5]), "=f"(d[6]), "=f"(d[7]), "=f"(d[8]), "=f"(d[9]), "=f"(d[10]), "=f"(d[11]), "=f"(d[12]), "=f"(d[13]), "=f"(d[14]), "=f"(d[15]), "=f"(d[16]), "=f"(d[17]), "=f"(d[18]), "=f"(d[19]), "=f"(d[20]), "=f"(d[21]), "=f"(d[22]), "=f"(d[23]), "=f"(d[24]), "=f"(d[25]), "=f"(d[26]), "=f"(d[27]), "=f"(d[28]), "=f"(d[29]), "=f"(d[30]), "=f"(d[31]), "=f"(d[32]), "=f"(d[33]), "=f"(d[34]), "=f"(d[35]), "=f"(d[36]), "=f"(d[37]), "=f"(d[38]), "=f"(d[39]), "=f"(d[40]), "=f"(d[41]), "=f"(d[42]), "=f"(d[43]), "=f"(d[44]), "=f"(d[45]), "=f"(d[46]), "=f"(d[47]), "=f"(d[48]), "=f"(d[49]), "=f"(d[50]), "=f"(d[51]), "=f"(d[52]), "=f"(d[53]), "=f"(d[54]), "=f"(d[55]), "=f"(d[56]), "=f"(d[57]), "=f"(d[58]), "=f"(d[59]), "=f"(d[60]), "=f"(d[61]), "=f"(d[62]), "=f"(d[63]), "=f"(d[64]), "=f"(d[65]), "=f"(d[66]), "=f"(d[67]), "=f"(d[68]), "=f"(d[69]), "=f"(d[70]), "=f"(d[71]), "=f"(d[72]), "=f"(d[73]), "=f"(d[74]), "=f"(d[75]), "=f"(d[76]), "=f"(d[77]), "=f"(d[78]), "=f"(d[79]), "=f"(d[80]), "=f"(d[81]), "=f"(d[82]), "=f"(d[83]), "=f"(d[84]), "=f"(d[85]), "=f"(d[86]), "=f"(d[87]), "=f"(d[88]), "=f"(d[89]), "=f"(d[90]), "=f"(d[91]), "=f"(d[92]), "=f"(d[93]), "=f"(d[94]), "=f"(d[95])
    : "r"(a0), "r"(a1), "r"(a2), "r"(a3), "l"(db));
}
__device__ __forceinline__ void wgmma_qkT0(float (&d)[8], uint64_t da, uint64_t db) {
  asm volatile("{\n.reg .pred p;\nsetp.ne.b32 p, 0, 0;\n"
    "wgmma.mma_async.sync.aligned.m64n16k16.f32.bf16.bf16 "
    "{%0, %1, %2, %3, %4, %5, %6, %7}, "
    "%8, %9, p, 1, 1, 0, 0;\n}\n"
    : "=f"(d[0]), "=f"(d[1]), "=f"(d[2]), "=f"(d[3]), "=f"(d[4]), "=f"(d[5]), "=f"(d[6]), "=f"(d[7])
    : "l"(da), "l"(db));
}
__device__ __forceinline__ void wgmma_pvT0(float (&d)[8], uint64_t da, uint64_t db) {
  asm volatile("{\n.reg .pred p;\nsetp.ne.b32 p, 0, 0;\n"
    "wgmma.mma_async.sync.aligned.m64n16k16.f32.bf16.bf16 "
    "{%0, %1, %2, %3, %4, %5, %6, %7}, "
    "%8, %9, p, 1, 1, 1, 0;\n}\n"
    : "=f"(d[0]), "=f"(d[1]), "=f"(d[2]), "=f"(d[3]), "=f"(d[4]), "=f"(d[5]), "=f"(d[6]), "=f"(d[7])
    : "l"(da), "l"(db));
}

struct Round { int head, qrow, mc; };
__device__ __forceinline__ Round decode_round(int g, int rank) {
  int p = g / 7, r = g - p * 7;
  Round o;
  if (r < 3) { o.head = 2 * p; o.qrow = r * 256 + rank * 128; o.mc = 1; }
  else if (r == 3) { o.head = 2 * p + rank; o.qrow = 768; o.mc = 0; }
  else { o.head = 2 * p + 1; o.qrow = (r - 4) * 256 + rank * 128; o.mc = 1; }
  return o;
}

__device__ __forceinline__ uint32_t kdesc0(uint32_t s_kv) { return ((s_kv & 0x3FFFFu) >> 4) | (1u << 16); }
__device__ __forceinline__ uint32_t vdesc0(uint32_t s_kv) { return ((s_kv & 0x3FFFFu) >> 4) | ((uint32_t)(SLAB >> 4) << 16); }
constexpr uint64_t DESC_HI = ((uint64_t)(RGRP >> 4) << 32) | ((uint64_t)1 << 62);
constexpr uint64_t DESC_HI_PT = ((uint64_t)(1024 >> 4) << 32) | ((uint64_t)1 << 62);

__device__ __forceinline__ void issue_qk(float (&S)[32], const uint32_t (&Q)[48], uint32_t kdesc) {
  const uint64_t d = DESC_HI | kdesc;
  wgmma_qk0(S, Q[0], Q[1], Q[2], Q[3], d);
#pragma unroll
  for (int kk = 1; kk < 12; kk++)
    wgmma_qk(S, Q[kk * 4], Q[kk * 4 + 1], Q[kk * 4 + 2], Q[kk * 4 + 3], d + (uint64_t)((kk / 4) * (SLAB / 16) + (kk % 4) * 2), 1);
}
__device__ __forceinline__ void issue_qk32(float (&S)[32], const uint32_t (&Q)[48], uint32_t kdesc) {
  uint32_t d[12];
#pragma unroll
  for (int kk = 0; kk < 12; kk++) {
    d[kk] = kdesc + ((kk / 4) * (SLAB / 16) + (kk % 4) * 2);
    asm volatile("" : "+r"(d[kk]));
  }
  wgmma_qk0(S, Q[0], Q[1], Q[2], Q[3], DESC_HI | d[0]);
#pragma unroll
  for (int kk = 1; kk < 12; kk++) wgmma_qk(S, Q[kk * 4], Q[kk * 4 + 1], Q[kk * 4 + 2], Q[kk * 4 + 3], DESC_HI | d[kk], 1);
}
__device__ __forceinline__ void issue_qk3(float (&S)[32], const uint32_t (&Q)[48], uint32_t kdesc) {
  const uint64_t d = DESC_HI | kdesc;
  wgmma_qk0(S, Q[0], Q[1], Q[2], Q[3], d);
#pragma unroll
  for (int kk = 1; kk < 12; kk++) {
    if (kk % 4 == 0) wg_commit();
    wgmma_qk(S, Q[kk * 4], Q[kk * 4 + 1], Q[kk * 4 + 2], Q[kk * 4 + 3], d + (uint64_t)((kk / 4) * (SLAB / 16) + (kk % 4) * 2), 1);
  }
}
template <bool ACCUMULATE>
__device__ __forceinline__ void issue_pv(float (&O)[96], const uint32_t (&P)[16], uint32_t vdesc) {
  const uint64_t d = DESC_HI | vdesc;
  if (ACCUMULATE) wgmma_pv(O, P[0], P[1], P[2], P[3], d, 1);
  else wgmma_pv0(O, P[0], P[1], P[2], P[3], d);
#pragma unroll
  for (int kk = 1; kk < 4; kk++)
    wgmma_pv(O, P[kk * 4], P[kk * 4 + 1], P[kk * 4 + 2], P[kk * 4 + 3], d + (uint64_t)(kk * (2 * RGRP / 16)), 1);
}

template <int K0 = 0, int K1 = 12>
__device__ __forceinline__ void load_q(uint32_t (&Q)[48], uint32_t lane_addr) {
#pragma unroll
  for (int kk = K0; kk < K1; kk++)
    ldsm_x4((lane_addr ^ ((kk % 4) << 5)) + (kk / 4) * SLAB, Q[kk * 4], Q[kk * 4 + 1], Q[kk * 4 + 2], Q[kk * 4 + 3]);
}

__device__ __forceinline__ void softmax_block(const float (&S)[32], uint32_t (&P)[16], float& l0, float& l1) {
#pragma unroll
  for (int i = 0; i < 8; i++) {
    const float a = ex2(S[4 * i + 0] * SCALE_LOG2);
    const float b = ex2(S[4 * i + 1] * SCALE_LOG2);
    const float c = ex2(S[4 * i + 2] * SCALE_LOG2);
    const float d = ex2(S[4 * i + 3] * SCALE_LOG2);
    l0 += a + b;
    l1 += c + d;
    P[2 * i] = pack_bf16(a, b);
    P[2 * i + 1] = pack_bf16(c, d);
  }
  fence_regs(P);
}

__device__ __forceinline__ void sums_put(uint32_t addr, float l0, float l1, uint32_t on) {
  asm volatile("{\n.reg .pred p;\nsetp.ne.u32 p, %3, 0;\n@p st.shared.v2.f32 [%0], {%1, %2};\n}\n" ::"r"(addr), "f"(l0), "f"(l1), "r"(on) : "memory");
}
__device__ __forceinline__ void sums_get(uint32_t addr, float& s0, float& s1) {
  float a, b, c, d, e, f, g, h;
  asm volatile("ld.shared.v4.f32 {%0, %1, %2, %3}, [%8];\nld.shared.v4.f32 {%4, %5, %6, %7}, [%8 + 16];\n"
               : "=f"(a), "=f"(b), "=f"(c), "=f"(d), "=f"(e), "=f"(f), "=f"(g), "=f"(h) : "r"(addr & ~31u) : "memory");
  s0 = (a + c) + (e + g);
  s1 = (b + d) + (f + h);
}

template <int K0, int K1>
__device__ __forceinline__ void epilogue_part(const float (&O)[96], float i0, float i1, uint32_t lane_addr) {
#pragma unroll
  for (int kk = K0; kk < K1; kk++) {
    const int b = kk * 8;
    stsm_x4((lane_addr ^ ((kk % 4) << 5)) + (kk / 4) * SLAB,
            pack_bf16(O[b] * i0, O[b + 1] * i0), pack_bf16(O[b + 2] * i1, O[b + 3] * i1),
            pack_bf16(O[b + 4] * i0, O[b + 5] * i0), pack_bf16(O[b + 6] * i1, O[b + 7] * i1));
  }
}
__device__ __forceinline__ void epilogue_done(uint32_t bar, int lane) {
  __syncwarp();
  if (lane == 0) mbar_arrive(bar);
}

__device__ __forceinline__ void redo_tile(const CUtensorMap* tmQ, const CUtensorMap* tmK, const CUtensorMap* tmV, const CUtensorMap* tmO,
                                          int head, int row, uint32_t qo, uint32_t kv, uint32_t lane_addr, uint32_t bar, uint32_t& phase,
                                          uint32_t wg_bar) {
  float O[96], S[32];
  uint32_t Q[48], P[16];
  uint64_t pol;
  asm volatile("createpolicy.fractional.L2::evict_normal.b64 %0, 1.0;" : "=l"(pol));
  const bool leader = (threadIdx.x & 127) == 0;
  if (leader) {
    mbar_expect_tx(bar, SLOT);
    tma_load(qo, tmQ, bar, row, head, pol);
  }
  mbar_wait(bar, phase);
  phase ^= 1;
  load_q(Q, lane_addr);
  float m0 = -INFINITY, m1 = -INFINITY, l0 = 0.f, l1 = 0.f;
#pragma unroll
  for (int i = 0; i < 96; i++) O[i] = 0.f;
#pragma unroll 1
  for (int j = 0; j < NBLK; j++) {
    asm volatile("bar.sync %0, 128;" ::"r"(wg_bar) : "memory");
    if (leader) {
      mbar_expect_tx(bar, 2 * SLOT);
      tma_load(kv, tmK, bar, j * BN, head, pol);
      tma_load(kv + SLOT, tmV, bar, j * BN, head, pol);
    }
    mbar_wait(bar, phase);
    phase ^= 1;
    wg_fence();
    issue_qk(S, Q, kdesc0(kv));
    wg_commit();
    wg_wait<0>();
    fence_regs(S);
    float n0 = m0, n1 = m1;
#pragma unroll
    for (int i = 0; i < 8; i++) {
      n0 = fmaxf(n0, fmaxf(S[4 * i], S[4 * i + 1]));
      n1 = fmaxf(n1, fmaxf(S[4 * i + 2], S[4 * i + 3]));
    }
#pragma unroll
    for (int o = 1; o < 4; o <<= 1) {
      n0 = fmaxf(n0, __shfl_xor_sync(0xffffffffu, n0, o));
      n1 = fmaxf(n1, __shfl_xor_sync(0xffffffffu, n1, o));
    }
    const float f0 = ex2((m0 - n0) * SCALE_LOG2), f1 = ex2((m1 - n1) * SCALE_LOG2);
    m0 = n0; m1 = n1;
    l0 *= f0; l1 *= f1;
#pragma unroll
    for (int i = 0; i < 24; i++) {
      O[4 * i] *= f0; O[4 * i + 1] *= f0; O[4 * i + 2] *= f1; O[4 * i + 3] *= f1;
    }
#pragma unroll
    for (int i = 0; i < 8; i++) {
      S[4 * i] -= m0; S[4 * i + 1] -= m0; S[4 * i + 2] -= m1; S[4 * i + 3] -= m1;
    }
    softmax_block(S, P, l0, l1);
    fence_regs(O);
    wg_fence();
    issue_pv<true>(O, P, vdesc0(kv + SLOT));
    wg_commit();
    wg_wait<0>();
    fence_regs(O);
  }
#pragma unroll
  for (int o = 1; o < 4; o <<= 1) {
    l0 += __shfl_xor_sync(0xffffffffu, l0, o);
    l1 += __shfl_xor_sync(0xffffffffu, l1, o);
  }
  epilogue_part<0, 12>(O, rcp(l0), rcp(l1), lane_addr);
  asm volatile("fence.proxy.async.shared::cta;" ::: "memory");
  asm volatile("bar.sync %0, 128;" ::"r"(wg_bar) : "memory");
  if (leader) {
    for (int i = 0; i < 64 && row + i < SQ; i += OROWS) tma_store(tmO, qo + i / 8 * RGRP, row + i, head, pol);
    asm volatile("cp.async.bulk.commit_group;" ::: "memory");
    asm volatile("cp.async.bulk.wait_group 0;" ::: "memory");
  }
}

__device__ __forceinline__ void wg_barrier() { asm volatile("bar.sync 3, 128;" ::: "memory"); }

__device__ __forceinline__ void tail_reduce(float (&v)[4], uint32_t red, int warp, int lane) {
#pragma unroll
  for (int o = 4; o < 32; o <<= 1)
#pragma unroll
    for (int i = 0; i < 4; i++) v[i] += __shfl_xor_sync(0xffffffffu, v[i], o);
  if (lane < 4)
    asm volatile("st.shared.v4.f32 [%0], {%1, %2, %3, %4};" ::"r"(red + (warp * 4 + lane) * 16), "f"(v[0]), "f"(v[1]), "f"(v[2]), "f"(v[3]) : "memory");
  wg_barrier();
#pragma unroll
  for (int ww = 0; ww < 4; ww++) {
    float x0, x1, x2, x3;
    asm volatile("ld.shared.v4.f32 {%0, %1, %2, %3}, [%4];" : "=f"(x0), "=f"(x1), "=f"(x2), "=f"(x3) : "r"(red + (ww * 4 + (lane & 3)) * 16) : "memory");
    if (ww == 0) { v[0] = x0; v[1] = x1; v[2] = x2; v[3] = x3; }
    else { v[0] += x0; v[1] += x1; v[2] += x2; v[3] += x3; }
  }
}

__device__ __forceinline__ void tail_softmax(const float (&S)[8], float (&l)[4], uint32_t pt_addr) {
  float e[8];
#pragma unroll
  for (int i = 0; i < 8; i++) e[i] = ex2(S[i] * SCALE_LOG2);
  stsm_x4_trans(pt_addr, pack_bf16(e[0], e[1]), pack_bf16(e[2], e[3]), pack_bf16(e[4], e[5]), pack_bf16(e[6], e[7]));
  l[0] += e[0] + e[2]; l[1] += e[1] + e[3]; l[2] += e[4] + e[6]; l[3] += e[5] + e[7];
}

__device__ __forceinline__ void issue_qkT(float (&S8)[8], uint32_t kdesc, uint32_t qt_addr) {
  const uint64_t da = DESC_HI | kdesc;
  const uint64_t db = DESC_HI | (uint64_t)(((qt_addr & 0x3FFFFu) >> 4) | (1u << 16));
  wgmma_qkT0(S8, da, db);
#pragma unroll
  for (int kk = 1; kk < 12; kk++)
    wgmma_qkT(S8, da + (uint64_t)((kk / 4) * (SLAB / 16) + (kk % 4) * 2), db + (uint64_t)((kk / 4) * (SLAB / 16) + (kk % 4) * 2), 1);
}
template <bool ACCUMULATE>
__device__ __forceinline__ void issue_pvT(float (&O)[3][8], uint32_t vdesc, uint32_t pt_base) {
  const uint64_t da = DESC_HI | vdesc;
  const uint64_t db = DESC_HI_PT | (uint64_t)(((pt_base & 0x3FFFFu) >> 4) | (1u << 16));
#pragma unroll
  for (int kk = 0; kk < 4; kk++)
#pragma unroll
    for (int b = 0; b < 3; b++) {
      if (kk == 0 && !ACCUMULATE) wgmma_pvT0(O[b], da + (uint64_t)(b * (SLAB / 16)), db);
      else wgmma_pvT(O[b], da + (uint64_t)(b * (SLAB / 16) + kk * (2 * RGRP / 16)), db + (uint64_t)(kk * 2), 1);
    }
}

template <bool B> struct Bool { static constexpr bool value = B; };

constexpr int MAX_CLUSTERS = 72;
constexpr int MAX_ROUNDS = 32;
struct Schedule {
  uint32_t first[MAX_CLUSTERS];
  uint32_t tails[MAX_CLUSTERS];
  uint16_t start[MAX_CLUSTERS + 1];
  uint16_t list[NROUNDS + 1];
};

#define TRACE_TILE()

__global__ void __cluster_dims__(2, 1, 1) __launch_bounds__(NTHREADS, 1)
attn_kernel(const __grid_constant__ CUtensorMap tmQ, const __grid_constant__ CUtensorMap tmQT, const __grid_constant__ CUtensorMap tmK,
            const __grid_constant__ CUtensorMap tmV, const __grid_constant__ CUtensorMap tmO, const __grid_constant__ Schedule sched) {
  extern __shared__ __align__(1024) uint8_t smem_raw[];
  const uint32_t c_entry = (uint32_t)clock();
  const uint32_t sbase = smem_u32(smem_raw);
  const uint32_t s_qo = sbase + OFF_QO;
  const uint32_t s_kv = sbase + OFF_KV;
  const uint32_t s_bar = sbase + OFF_BAR;
  const uint32_t bar_full = s_bar;
  const uint32_t bar_empty = s_bar + 8 * NSLOT;
  const uint32_t bar_qfull = s_bar + 16 * NSLOT;
  const uint32_t bar_ostg = bar_qfull + 16;
  const uint32_t bar_qreq = bar_ostg + 16;
  const uint32_t bar_redo = bar_qreq + 16;
  const uint32_t s_redo = bar_redo + 16;

  uint32_t rank;
  asm("mov.u32 %0, %%cluster_ctarank;" : "=r"(rank));
  const int cluster = blockIdx.x >> 1;
  auto get_rounds = [&](int& first, int& count) {
    int c = cluster;
    asm volatile("" : "+r"(c));
    first = sched.start[c];
    count = sched.start[c + 1] - first;
  };

  if (threadIdx.x == 32) {
    asm volatile("prefetch.tensormap [%0];" ::"l"(&tmK) : "memory");
    asm volatile("prefetch.tensormap [%0];" ::"l"(&tmQ) : "memory");
    asm volatile("prefetch.tensormap [%0];" ::"l"(&tmV) : "memory");
  }
  if (threadIdx.x == 0) {
    for (int i = 0; i < NSLOT; i++) {
      mbar_init(bar_full + 8 * i, 1);
      mbar_init(bar_empty + 8 * i, 4);
    }
    for (int i = 0; i < 2; i++) {
      mbar_init(bar_qfull + 8 * i, 1);
      mbar_init(bar_ostg + 8 * i, 4);
      mbar_init(bar_qreq + 8 * i, 1);
      mbar_init(bar_redo + 8 * i, 1);
      asm volatile("st.shared.u32 [%0], %1;" ::"r"(s_redo + 4 * i), "r"(0) : "memory");
    }
    asm volatile("fence.mbarrier_init.release.cluster;" ::: "memory");
    asm volatile("fence.proxy.async.shared::cta;" ::: "memory");
    const uint32_t e = sched.first[cluster];
    const Round r = decode_round(e & 0x7ff, rank);
    uint64_t polq, polk;
    asm volatile("createpolicy.fractional.L2::evict_first.b64 %0, 1.0;" : "=l"(polq));
    asm volatile("createpolicy.fractional.L2::evict_unchanged.b64 %0, 1.0;" : "=l"(polk));
    while ((uint32_t)clock() - c_entry < (e >> 16)) {}
    mbar_expect_tx(bar_full, SLOT);
    tma_load(s_kv, &tmK, bar_full, 0, r.head, polk);
    mbar_expect_tx(bar_qfull, SLOT);
    tma_load(s_qo, &tmQ, bar_qfull, r.qrow, r.head, polq);
    mbar_expect_tx(bar_full + 8, SLOT);
    tma_load(s_kv + SLOT, &tmK, bar_full + 8, BN, r.head, polk);
    mbar_expect_tx(bar_full + 16, SLOT);
    tma_load(s_kv + 2 * SLOT, &tmV, bar_full + 16, 0, r.head, polk);
    mbar_expect_tx(bar_qfull + 8, SLOT);
    tma_load(s_qo + SLOT, &tmQ, bar_qfull + 8, r.qrow + 64, r.head, polq);
  }
  __syncthreads();
  asm volatile("barrier.cluster.arrive.relaxed.aligned;\nbarrier.cluster.wait.aligned;" ::: "memory");

  const int wg = __shfl_sync(0xffffffffu, threadIdx.x >> 7, 0);
  const int warp = __shfl_sync(0xffffffffu, (threadIdx.x >> 5) & 3, 0);
  const int lane = threadIdx.x & 31;

  if (wg == 0) {
    asm volatile("setmaxnreg.dec.sync.aligned.u32 24;");
    int first_round, nrounds;
    get_rounds(first_round, nrounds);
    const int nblocks = nrounds * NBLK;
    if (warp == 0 && lane == 0) {
      uint64_t pol;
      asm volatile("createpolicy.fractional.L2::evict_unchanged.b64 %0, 1.0;" : "=l"(pol));
      uint32_t slot = 3, phase = 1;
      auto load = [&](const CUtensorMap* tm, int n, uint32_t owner) {
        const Round r = decode_round(sched.list[first_round + (n >> 3)] & 0x7ff, rank);
        mbar_wait_sleep(bar_empty + 8 * slot, phase);
        if (n < nblocks) {
          mbar_expect_tx(bar_full + 8 * slot, SLOT);
          if (!r.mc) tma_load(s_kv + slot * SLOT, tm, bar_full + 8 * slot, (n & 7) * BN, r.head, pol);
          else if (rank == owner) tma_load_mc(s_kv + slot * SLOT, tm, bar_full + 8 * slot, (n & 7) * BN, r.head, pol);
        }
        if (++slot == NSLOT) { slot = 0; phase ^= 1; }
      };
      for (int n = 1; n < nblocks; n++) {
        load(&tmK, n + 1, 0);
        load(&tmV, n, 1);
      }
      for (int i = 0; i < NSLOT; i++) {
        if (i != NSLOT - 2) mbar_wait_sleep(bar_empty + 8 * slot, phase);
        if (++slot == NSLOT) { slot = 0; phase ^= 1; }
      }
    } else if ((warp == 1 || warp == 2) && lane == 0) {
      const int w = warp - 1;
      uint64_t pol;
      asm volatile("createpolicy.fractional.L2::evict_first.b64 %0, 1.0;" : "=l"(pol));
      const uint32_t buf = s_qo + w * SLOT;
      Round r = decode_round(sched.list[first_round] & 0x7ff, rank);
      Round prev = r;
      for (int t = 0; t <= nrounds; t++) {
        mbar_wait_sleep(bar_ostg + 8 * w, t & 1);
        if (t > 0) {
          asm volatile("fence.proxy.async.shared::cta;" ::: "memory");
          const int row0 = prev.qrow + w * 64;
          const int nrows = row0 + 64 <= SQ ? 64 : SQ - row0;
#pragma unroll 1
          for (int i = 0; i < nrows; i += OROWS) {
            tma_store(&tmO, buf + i / 8 * RGRP, row0 + i, prev.head, pol);
            asm volatile("cp.async.bulk.commit_group;" ::: "memory");
            if (t < nrounds) asm volatile("cp.async.bulk.wait_group.read 0;" ::: "memory");
          }
          prev = r;
        }
        if (t + 1 < nrounds) {
          mbar_wait_sleep(bar_qreq + 8 * w, t & 1);
          const uint32_t e = sched.list[first_round + t + 1];
          r = decode_round(e & 0x7ff, rank);
          if (w == 1 && (e & 0x8000)) {
            mbar_expect_tx(bar_qfull + 8 * w, 3 * 2048);
            tma_load(sbase + OFF_QT, &tmQT, bar_qfull + 8 * w, r.qrow + 64, r.head, pol);
          } else {
            mbar_expect_tx(bar_qfull + 8 * w, SLOT);
            tma_load(buf, &tmQ, bar_qfull + 8 * w, r.qrow + w * 64, r.head, pol);
          }
        } else if (t < nrounds) {
          mbar_arrive(bar_qfull + 8 * w);
        }
      }
      asm volatile("cp.async.bulk.wait_group 0;" ::: "memory");
      mbar_arrive(bar_redo + 8 * w);
    } else if (warp == 3) {
      uint32_t slot = 1, phase = 0;
      const uint32_t tails = sched.tails[cluster];
      for (int n = 0; n < nblocks; n++) {
        if (n + 1 < nblocks) mbar_wait(bar_full + 8 * slot, phase);
        if (++slot == NSLOT) { slot = 0; phase ^= 1; }
        mbar_wait(bar_full + 8 * slot, phase);
        if (++slot == NSLOT) { slot = 0; phase ^= 1; }
        asm volatile("bar.sync 1, 288;" ::: "memory");
        asm volatile("bar.arrive 2, 288;" ::: "memory");
        if (lane < 2 && (n & 7) + ((tails >> (n >> 3 & 31) & 1) ? QREQT : 0) == (lane ? QREQ1 : QREQ0)) mbar_arrive(bar_qreq + 8 * lane);
        TRACE_TILE();
      }
    }
  } else {
    asm volatile("setmaxnreg.inc.sync.aligned.u32 240;");
    const int w = wg - 1;
    int first_round, nrounds;
    get_rounds(first_round, nrounds);
    const int nblocks = nrounds * NBLK;
    float O[96], S[32];
    uint32_t Q[48], P0[16], P1[16];
    float l0 = 0.f, l1 = 0.f, inv0 = 0.f, inv1 = 0.f;
    uint32_t redo = 0;
    const uint32_t lane_addr = s_qo + w * SLOT + (warp * 2 + ((lane >> 3) & 1)) * RGRP + (lane & 7) * 128 + (((lane >> 4) ^ (lane & 7)) << 4);
    const uint32_t sum_addr = s_qo + w * SLOT + warp * 2 * RGRP + lane * 8;
    const uint32_t my_qfull = bar_qfull + 8 * w, my_ostg = bar_ostg + 8 * w;

    uint32_t empty_remote;
    asm("mapa.shared::cluster.u32 %0, %1, %2;" : "=r"(empty_remote) : "r"(bar_empty), "r"(threadIdx.x & 1));
    const bool releaser = (threadIdx.x & 127) < 2;
    auto release = [&](uint32_t s) {
      if (releaser) asm volatile("mbarrier.arrive.shared::cluster.b64 _, [%0];" ::"r"(empty_remote + s) : "memory");
    };
    uint32_t ks = 8, vs = 16, kp = 0, vp = 0;
    const uint32_t kd0 = kdesc0(s_kv), vd0 = vdesc0(s_kv);
    uint32_t kd = kd0 + ks * (SLOT / 128), vd = vd0 + vs * (SLOT / 128);
    auto advance = [&]() {
      kp = ks; vp = vs;
      ks = ks >= 8 * (NSLOT - 2) ? ks - 8 * (NSLOT - 2) : ks + 16;
      vs = vs >= 8 * (NSLOT - 2) ? vs - 8 * (NSLOT - 2) : vs + 16;
      kd = kd0 + ks * (SLOT / 128); vd = vd0 + vs * (SLOT / 128);
      asm volatile("" : "+r"(ks), "+r"(vs), "+r"(kd), "+r"(vd));
    };

    uint32_t tails = w == 1 ? sched.tails[cluster] : 0u;
    auto turn_wait = [&]() { asm volatile("bar.sync %0, 288;" ::"r"(1 + w) : "memory"); };
    auto turn_pass = [&]() { asm volatile("bar.arrive %0, 288;" ::"r"(2 - w) : "memory"); };
    if (w == 1) turn_pass();

    mbar_wait(my_qfull, 0);
    load_q(Q, lane_addr);
    mbar_wait(bar_full, 0);
    wg_fence();
    issue_qk(S, Q, kd0);
    wg_commit();
    wg_wait<0>();
    fence_regs(S);
    release(0);
    __syncwarp();
    if (lane == 0) mbar_arrive(my_ostg);
    bool pending = false;

    int n = 0;
    auto finish_sums = [&]() {
      float s0, s1;
      sums_get(sum_addr, s0, s1);
      if (!(sum_ok(s0) && sum_ok(s1))) redo |= 1u << ((n >> 3) & 31);
      inv0 = rcp(s0); inv1 = rcp(s1);
      l0 = l1 = 0.f;
      asm volatile("" : "+f"(inv0), "+f"(inv1), "+r"(redo)::"memory");
    };

    int exit_n = -1;
#pragma unroll 1
    while (true) {
#pragma unroll 1
      while (true) {
        const int j = n & 7;
        softmax_block(S, P0, l0, l1);
        asm volatile("" : "+f"(l0), "+f"(l1)::"memory");
        if (j != 0) {
          wg_wait<0>();
          release(vp);
          turn_wait();
          wg_fence();
          issue_qk3(S, Q, kd);
          wg_commit();
          issue_pv<true>(O, P0, vd);
          wg_commit();
          turn_pass();
          advance();
          if (j == 6) {
            mbar_wait(my_qfull, ((n >> 3) + 1) & 1);
            wg_wait<3>();
            load_q<0, 4>(Q, lane_addr);
            wg_wait<2>();
            load_q<4, 8>(Q, lane_addr);
          }
          wg_wait<1>();
          fence_regs(S);
          fence_regs(P1);
        } else {
          wg_wait<0>();
          fence_regs(O);
          fence_regs(P1);
          if (pending) {
            release(vp);
            epilogue_part<0, ESPLIT>(O, inv0, inv1, lane_addr);
          }
          turn_wait();
          wg_fence();
          issue_qk32(S, Q, kd);
          wg_commit();
          if (pending) {
            epilogue_part<ESPLIT, 12>(O, inv0, inv1, lane_addr);
            epilogue_done(my_ostg, lane);
          }
          wg_fence();
          issue_pv<false>(O, P0, vd);
          wg_commit();
          turn_pass();
          advance();
          exit_n = ((tails & 2) || n + 8 == nblocks) ? n + 6 : -1;
          tails >>= 1;
          asm volatile("" : "+r"(exit_n), "+r"(tails));
          wg_wait<1>();
          fence_regs(S);
          pending = true;
        }
        release(kp);
        if (j == 6) load_q<8, 12>(Q, lane_addr);
        softmax_block(S, P1, l0, l1);
        sums_put(sum_addr, l0, l1, j == 6);
        wg_wait<0>();
        release(vp);
        turn_wait();
        if (n == exit_n) {
          wg_fence();
          issue_pv<true>(O, P1, vd);
          wg_commit();
          break;
        }
        wg_fence();
        issue_qk(S, Q, kd);
        wg_commit();
        issue_pv<true>(O, P1, vd);
        wg_commit();
        turn_pass();
        advance();
        if (j == 6) finish_sums();
        wg_wait<1>();
        fence_regs(S);
        fence_regs(P0);
        release(kp);
        n += 2;
      }
      if (n + 2 == nblocks) {
        if (w == 0) turn_pass();
        finish_sums();
        wg_wait<0>();
        fence_regs(O);
        release(vs);
        epilogue_part<0, 12>(O, inv0, inv1, lane_addr);
        epilogue_done(my_ostg, lane);
        break;
      }
      const int t = n >> 3;
      const uint32_t qt = sbase + OFF_QT, pt = sbase + OFF_PT, red = sbase + OFF_RED;
      const uint32_t tl = ((lane & 7) + (lane >> 4) * 8) * 128 + (((warp * 2 + ((lane >> 3) & 1)) ^ (lane & 7)) << 4);
      const bool tlast = n + 10 == nblocks;
      float lt[4] = {0.f, 0.f, 0.f, 0.f};
      float ST[8], OT[3][8];
      wg_fence();
      issue_qkT(ST, kd, qt);
      wg_commit();
      turn_pass();
      finish_sums();
      wg_wait<0>();
      fence_regs(ST);
      fence_regs(O);
      release(ks);
      release(vs);
      advance();
      epilogue_part<0, NT_SPLIT>(O, inv0, inv1, lane_addr);
      if (NT_SPLIT == 12) epilogue_done(my_ostg, lane);
      tail_softmax(ST, lt, pt + tl);
      auto tail_step = [&](auto first_c, int jj) {
        constexpr bool FIRST = decltype(first_c)::value;
        asm volatile("fence.proxy.async.shared::cta;" ::: "memory");
        turn_wait();
        wg_fence();
        issue_qkT(ST, kd, qt);
        wg_commit();
        issue_pvT<!FIRST>(OT, vd, pt + (jj & 1) * 2048);
        wg_commit();
        turn_pass();
        advance();
        wg_wait<1>();
        fence_regs(ST);
        release(kp);
        tail_softmax(ST, lt, pt + (~jj & 1) * 2048 + tl);
        wg_wait<0>();
        fence_regs(OT[0]); fence_regs(OT[1]); fence_regs(OT[2]);
        release(vp);
      };
      tail_step(Bool<true>(), 0);
      if (NT_SPLIT < 12) {
        epilogue_part<NT_SPLIT, 12>(O, inv0, inv1, lane_addr);
        epilogue_done(my_ostg, lane);
      }
#pragma unroll 1
      for (int jj = 1; jj < 7; jj++) tail_step(Bool<false>(), jj);
      mbar_wait(my_qfull, t & 1);
      load_q(Q, lane_addr);
      tail_reduce(lt, red, warp, lane);
      if (!(sum_ok(lt[0]) && sum_ok(lt[1]) && sum_ok(lt[2]) && sum_ok(lt[3]))) redo |= 1u << ((t + 1) & 31);
#pragma unroll
      for (int i = 0; i < 4; i++) lt[i] = rcp(lt[i]);
      asm volatile("fence.proxy.async.shared::cta;" ::: "memory");
      turn_wait();
      wg_fence();
      issue_pvT<true>(OT, vd, pt + 2048);
      wg_commit();
      issue_qk(S, Q, kd);
      wg_commit();
      if (!tlast) turn_pass();
      wg_wait<1>();
      fence_regs(OT[0]); fence_regs(OT[1]); fence_regs(OT[2]);
      release(vs);
#pragma unroll
      for (int b = 0; b < 3; b++)
        stsm_x4_trans(s_qo + SLOT + b * SLAB + tl + (lane >> 4) * (RGRP - 1024),
                      pack_bf16(OT[b][0] * lt[0], OT[b][1] * lt[1]), pack_bf16(OT[b][2] * lt[0], OT[b][3] * lt[1]),
                      pack_bf16(OT[b][4] * lt[2], OT[b][5] * lt[3]), pack_bf16(OT[b][6] * lt[2], OT[b][7] * lt[3]));
      epilogue_done(my_ostg, lane);
      wg_wait<0>();
      fence_regs(S);
      if (tlast) break;
      release(ks);
      advance();
#pragma unroll
      for (int i = 0; i < 96; i++) O[i] = 0.f;
      pending = false;
      n += 10;
      tails >>= 1;
    }
    if (redo) asm volatile("red.shared.or.b32 [%0], %1;" ::"r"(s_redo + 4 * w), "r"(redo) : "memory");
    asm volatile("bar.sync 4, 256;" ::: "memory");
    asm volatile("ld.shared.u32 %0, [%1];" : "=r"(redo) : "r"(s_redo + 4 * w) : "memory");
    redo = __shfl_sync(0xffffffffu, redo, 0);
    if (redo) {
      mbar_wait_sleep(bar_redo + 8 * w, 0);
      asm volatile("bar.sync %0, 128;" ::"r"(5 + w) : "memory");
      uint32_t phase = 1;
      get_rounds(first_round, nrounds);
#pragma unroll 1
      for (int t = 0; t < nrounds; t++) {
        if (!(redo >> (t & 31) & 1)) continue;
        const Round r = decode_round(sched.list[first_round + t] & 0x7ff, rank);
        redo_tile(&tmQ, &tmK, &tmV, &tmO, r.head, r.qrow + w * 64, s_qo + w * SLOT, s_kv + 2 * w * SLOT, lane_addr, bar_redo + 8 * w, phase, 5 + w);
      }
    }
  }
}

typedef CUresult (*EncodeFn)(CUtensorMap*, CUtensorMapDataType, cuuint32_t, void*, const cuuint64_t*, const cuuint64_t*,
                             const cuuint32_t*, const cuuint32_t*, CUtensorMapInterleave, CUtensorMapSwizzle,
                             CUtensorMapL2promotion, CUtensorMapFloatOOBfill);

void make_map(EncodeFn fn, CUtensorMap* tm, const void* ptr, int rows, int box_rows) {
  cuuint64_t dims[5] = {64, 8, 3, (cuuint64_t)rows / 8, (cuuint64_t)NHEADS};
  cuuint64_t strides[4] = {HD * 2, 128, 8 * HD * 2, (cuuint64_t)rows * HD * 2};
  cuuint32_t box[5] = {64, 8, 3, (cuuint32_t)box_rows / 8, 1};
  cuuint32_t estr[5] = {1, 1, 1, 1, 1};
  fn(tm, CU_TENSOR_MAP_DATA_TYPE_BFLOAT16, 5, const_cast<void*>(ptr), dims, strides, box, estr,
     CU_TENSOR_MAP_INTERLEAVE_NONE, CU_TENSOR_MAP_SWIZZLE_128B, CU_TENSOR_MAP_L2_PROMOTION_L2_128B, CU_TENSOR_MAP_FLOAT_OOB_FILL_NONE);
}

#define STAGGER 250
#define COST_N 12690
#define COST_T 10800
#define COST_TN 12720
#define TAIL_LATE 36
#define TAIL_MAX 60
#define HEAVY_STEP 3
void make_schedule(Schedule& s, int nclusters) {
  static uint16_t lists[MAX_CLUSTERS][NROUNDS];
  int cnt[MAX_CLUSTERS] = {0}, len[MAX_CLUSTERS], ntail[MAX_CLUSTERS] = {0}, quota[MAX_CLUSTERS] = {0};
  long long busy[MAX_CLUSTERS], fin[MAX_CLUSTERS];
  const int ntails = NROUNDS / 7, base = NROUNDS / nclusters, nheavy = NROUNDS % nclusters;
  const int step = nheavy * HEAVY_STEP <= nclusters ? HEAVY_STEP : 1;
  for (int c = 0; c < nclusters; c++) {
    len[c] = base + (c % step == 0 && c / step < nheavy);
    busy[c] = c / 3 * STAGGER;
    fin[c] = busy[c] + (long long)len[c] * COST_N;
  }
  for (int k = 0; k < ntails; k++) {
    int c = -1;
    for (int i = 0; i < nclusters; i++)
      if (quota[i] < len[i] / 2 && (c < 0 || fin[i] > fin[c])) c = i;
    quota[c]++;
    fin[c] -= 2 * COST_N - COST_T - COST_TN;
  }
  int gn = 0, gt = 3;
  for (int k = 0; k < NROUNDS; k++) {
    int c = -1;
    for (int i = 0; i < nclusters; i++)
      if (cnt[i] < len[i] && (c < 0 || busy[i] < busy[c])) c = i;
    const bool after_tail = cnt[c] > 0 && (lists[c][cnt[c] - 1] & 0x8000);
    const bool may_t = cnt[c] > 0 && !after_tail;
    const int left = len[c] - cnt[c], q = quota[c] - ntail[c];
    const bool due = (long long)(gt / 7) * quota[c] * 8 >= (long long)(ntail[c] * 8 + (c * 5 & 7)) * ntails;
    bool tail = may_t && q > 0 && (2 * q > left || (gn - gt >= TAIL_LATE && due) || gn - gt >= TAIL_MAX);
    if (4 * quota[c] >= len[c]) {
      const int m = len[c] - 1, phase = c / step * 11 % m;
      tail = may_t && q > 0 && (2 * q > left || (cnt[c] * quota[c] + phase) / m > ntail[c]);
    }
    if (gt >= NROUNDS) tail = false;
    if (gn >= NROUNDS) tail = true;
    const int g = tail ? gt : gn;
    if (tail) { gt += 7; ntail[c]++; }
    else { gn++; if (gn % 7 == 3) gn++; }
    const bool form_t = tail && may_t;
    lists[c][cnt[c]++] = (uint16_t)(g | (form_t ? 0x8000 : 0));
    busy[c] += form_t ? COST_T : after_tail ? COST_TN : COST_N;
  }
  bool use_tail = true;
  for (int c = 0; c < nclusters; c++) if (cnt[c] > MAX_ROUNDS) use_tail = false;
  if (!use_tail) for (int c = 0; c < nclusters; c++) for (int i = 0; i < cnt[c]; i++) lists[c][i] &= 0x7fff;
  int pos = 0;
  for (int c = 0; c < nclusters; c++) {
    s.start[c] = (uint16_t)pos;
    s.tails[c] = 0;
    s.first[c] = (lists[c][0] & 0x7ff) | (uint32_t)(c / 3 * STAGGER) << 16;
    for (int i = 0; i < cnt[c]; i++) {
      if (lists[c][i] & 0x8000) s.tails[c] |= 1u << i;
      s.list[pos++] = lists[c][i];
    }
  }
  for (int c = nclusters; c <= MAX_CLUSTERS; c++) s.start[c] = (uint16_t)pos;
  s.list[NROUNDS] = 0;
}

}

extern "C" void kernel_launch(void* const* d_in, const int* in_sizes, int n_in, void* d_out, int out_size) {
  static EncodeFn encode = nullptr;
  static int nclusters = 0;
  static Schedule sched;
  if (!encode) {
    void* fn = nullptr;
    cudaDriverEntryPointQueryResult qr;
    cudaGetDriverEntryPoint("cuTensorMapEncodeTiled", &fn, cudaEnableDefault, &qr);
    encode = (EncodeFn)fn;
    int dev = 0, nsm = 0;
    cudaGetDevice(&dev);
    cudaDeviceGetAttribute(&nsm, cudaDevAttrMultiProcessorCount, dev);
    nclusters = nsm / 2 < MAX_CLUSTERS ? nsm / 2 : MAX_CLUSTERS;
    make_schedule(sched, nclusters);
    cudaFuncSetAttribute(attn_kernel, cudaFuncAttributeMaxDynamicSharedMemorySize, SMEM_BYTES);
  }
  CUtensorMap tmQ, tmQT, tmK, tmV, tmO;
  make_map(encode, &tmQ, d_in[0], SQ, 64);
  make_map(encode, &tmQT, d_in[0], SQ, 16);
  make_map(encode, &tmK, d_in[1], SK, 64);
  make_map(encode, &tmV, d_in[2], SK, 64);
  make_map(encode, &tmO, d_out, SQ, OROWS);
  attn_kernel<<<2 * nclusters, NTHREADS, SMEM_BYTES>>>(tmQ, tmQT, tmK, tmV, tmO, sched);
}
```

```cpp
#include <cuda_runtime.h>
#include <cuda_bf16.h>
#include <cuda.h>
#include <stdint.h>

namespace {

constexpr int NHEADS = 512;
constexpr int SQ = 848;
constexpr int SK = 512;
constexpr int HD = 192;
constexpr int BN = 64;
constexpr int NBLK = SK / BN;
constexpr int SLOT = 64 * HD * 2;
constexpr int SLAB = 1024;
constexpr int RGRP = 3 * SLAB;
constexpr int NSLOT = 7;
constexpr int NROUNDS = (NHEADS / 2) * 7;
constexpr int NTHREADS = 384;
constexpr int OFF_QO = 0;
constexpr int OFF_KV = 2 * SLOT;
constexpr int OFF_QT = (2 + NSLOT) * SLOT;
constexpr int OFF_PT = OFF_QT + 3 * 2048;
constexpr int OFF_RED = OFF_PT + 2 * 2048;
constexpr int OFF_BAR = OFF_RED + 256;
constexpr int SMEM_BYTES = OFF_BAR + 256;

#define ESPLIT 8
#define OROWS 16
#define STAGGER 250
#define NT_SPLIT 4
#define QREQT 1
#define QREQ0 4
#define QREQ1 4
constexpr uint32_t WAIT_LIMIT = 1u << 18;
#define SUSPEND 20000
constexpr uint32_t SUSPEND_NS = SUSPEND;

constexpr float SCALE_LOG2 = 0.07216878364870322f * 1.4426950408889634f;
constexpr float SUM_MIN = 9.313225746154785e-10f;
constexpr float SUM_MAX = 1.152921504606847e+18f;
__device__ __forceinline__ bool sum_ok(float l) { return l >= SUM_MIN && l <= SUM_MAX; }

__device__ __forceinline__ uint32_t smem_u32(const void* p) { return (uint32_t)__cvta_generic_to_shared(p); }
__device__ __forceinline__ void wg_fence() { asm volatile("wgmma.fence.sync.aligned;" ::: "memory"); }
__device__ __forceinline__ void wg_commit() { asm volatile("wgmma.commit_group.sync.aligned;" ::: "memory"); }
template <int N> __device__ __forceinline__ void wg_wait() { asm volatile("wgmma.wait_group.sync.aligned %0;" ::"n"(N) : "memory"); }
template <int N> __device__ __forceinline__ void fence_regs(float (&r)[N]) {
#pragma unroll
  for (int i = 0; i < N; i++) asm volatile("" : "+f"(r[i])::"memory");
}
template <int N> __device__ __forceinline__ void fence_regs(uint32_t (&r)[N]) {
#pragma unroll
  for (int i = 0; i < N; i++) asm volatile("" : "+r"(r[i])::"memory");
}

__device__ __forceinline__ void mbar_init(uint32_t bar, uint32_t cnt) {
  asm volatile("mbarrier.init.shared::cta.b64 [%0], %1;" ::"r"(bar), "r"(cnt));
}
__device__ __forceinline__ void mbar_expect_tx(uint32_t bar, uint32_t bytes) {
  asm volatile("mbarrier.arrive.expect_tx.shared::cta.b64 _, [%0], %1;" ::"r"(bar), "r"(bytes) : "memory");
}
__device__ __forceinline__ void mbar_arrive(uint32_t bar) {
  asm volatile("mbarrier.arrive.shared::cta.b64 _, [%0];" ::"r"(bar) : "memory");
}
__device__ __forceinline__ bool mbar_try(uint32_t bar, uint32_t parity) {
  uint32_t ok;
  asm volatile(
      "{\n.reg .pred p;\nmbarrier.try_wait.parity.shared::cta.b64 p, [%1], %2;\nselp.b32 %0, 1, 0, p;\n}\n"
      : "=r"(ok)
      : "r"(bar), "r"(parity)
      : "memory");
  return ok;
}
__device__ __forceinline__ bool mbar_try_sleep(uint32_t bar, uint32_t parity) {
  uint32_t ok;
  asm volatile(
      "{\n.reg .pred p;\nmbarrier.try_wait.parity.shared::cta.b64 p, [%1], %2, %3;\nselp.b32 %0, 1, 0, p;\n}\n"
      : "=r"(ok)
      : "r"(bar), "r"(parity), "r"(SUSPEND_NS)
      : "memory");
  return ok;
}
__device__ __forceinline__ void mbar_wait(uint32_t bar, uint32_t parity) {
  if (mbar_try(bar, parity)) return;
  for (uint32_t n = 0; n < WAIT_LIMIT; n++)
    if (mbar_try(bar, parity)) break;
}
__device__ __forceinline__ void mbar_wait_sleep(uint32_t bar, uint32_t parity) {
  for (uint32_t n = 0; n < WAIT_LIMIT; n++) {
    if (mbar_try_sleep(bar, parity)) break;
  }
}

__device__ __forceinline__ void tma_load(uint32_t dst, const CUtensorMap* tm, uint32_t bar, int row, int head, uint64_t pol) {
  asm volatile(
      "cp.async.bulk.tensor.5d.shared::cluster.global.mbarrier::complete_tx::bytes.L2::cache_hint"
      " [%0], [%1, {%3, %3, %3, %4, %5}], [%2], %6;" ::"r"(dst),
      "l"(tm), "r"(bar), "r"(0), "r"(row >> 3), "r"(head), "l"(pol)
      : "memory");
}
__device__ __forceinline__ void tma_load_mc(uint32_t dst, const CUtensorMap* tm, uint32_t bar, int row, int head, uint64_t pol) {
  asm volatile(
      "cp.async.bulk.tensor.5d.shared::cluster.global.mbarrier::complete_tx::bytes.multicast::cluster.L2::cache_hint"
      " [%0], [%1, {%3, %3, %3, %4, %5}], [%2], %7, %6;" ::"r"(dst),
      "l"(tm), "r"(bar), "r"(0), "r"(row >> 3), "r"(head), "l"(pol), "h"((uint16_t)3)
      : "memory");
}
__device__ __forceinline__ void tma_store(const CUtensorMap* tm, uint32_t src, int row, int head, uint64_t pol) {
  asm volatile(
      "cp.async.bulk.tensor.5d.global.shared::cta.bulk_group.L2::cache_hint"
      " [%0, {%2, %2, %2, %3, %4}], [%1], %5;" ::"l"(tm),
      "r"(src), "r"(0), "r"(row >> 3), "r"(head), "l"(pol)
      : "memory");
}
__device__ __forceinline__ void ldsm_x4(uint32_t addr, uint32_t& r0, uint32_t& r1, uint32_t& r2, uint32_t& r3) {
  asm volatile("ldmatrix.sync.aligned.m8n8.x4.shared.b16 {%0, %1, %2, %3}, [%4];"
               : "=r"(r0), "=r"(r1), "=r"(r2), "=r"(r3)
               : "r"(addr)
               : "memory");
}
__device__ __forceinline__ void stsm_x4(uint32_t addr, uint32_t r0, uint32_t r1, uint32_t r2, uint32_t r3) {
  asm volatile("stmatrix.sync.aligned.m8n8.x4.shared.b16 [%0], {%1, %2, %3, %4};" ::"r"(addr), "r"(r0), "r"(r1), "r"(r2), "r"(r3)
               : "memory");
}
__device__ __forceinline__ void stsm_x4_trans(uint32_t addr, uint32_t r0, uint32_t r1, uint32_t r2, uint32_t r3) {
  asm volatile("stmatrix.sync.aligned.m8n8.x4.trans.shared.b16 [%0], {%1, %2, %3, %4};" ::"r"(addr), "r"(r0), "r"(r1), "r"(r2), "r"(r3)
               : "memory");
}
__device__ __forceinline__ float ex2(float x) {
  float y;
  asm("ex2.approx.ftz.f32 %0, %1;" : "=f"(y) : "f"(x));
  return y;
}
__device__ __forceinline__ float rcp(float x) {
  float y;
  asm("rcp.approx.ftz.f32 %0, %1;" : "=f"(y) : "f"(x));
  return y;
}
__device__ __forceinline__ uint32_t pack_bf16(float lo, float hi) {
  uint32_t r;
  asm("cvt.rn.bf16x2.f32 %0, %1, %2;" : "=r"(r) : "f"(hi), "f"(lo));
  return r;
}
__device__ __forceinline__ void wgmma_qk(float (&d)[32], uint32_t a0, uint32_t a1, uint32_t a2, uint32_t a3, uint64_t db, int scale_d) {
  asm volatile("{\n.reg .pred p;\nsetp.ne.b32 p, %37, 0;\n"
    "wgmma.mma_async.sync.aligned.m64n64k16.f32.bf16.bf16 "
    "{%0, %1, %2, %3, %4, %5, %6, %7, %8, %9, %10, %11, %12, %13, %14, %15, %16, %17, %18, %19, %20, %21, %22, %23, %24, %25, %26, %27, %28, %29, %30, %31}, "
    "{%32, %33, %34, %35}, %36, p, 1, 1, 0;\n}\n"
    : "+f"(d[0]), "+f"(d[1]), "+f"(d[2]), "+f"(d[3]), "+f"(d[4]), "+f"(d[5]), "+f"(d[6]), "+f"(d[7]), "+f"(d[8]), "+f"(d[9]), "+f"(d[10]), "+f"(d[11]), "+f"(d[12]), "+f"(d[13]), "+f"(d[14]), "+f"(d[15]), "+f"(d[16]), "+f"(d[17]), "+f"(d[18]), "+f"(d[19]), "+f"(d[20]), "+f"(d[21]), "+f"(d[22]), "+f"(d[23]), "+f"(d[24]), "+f"(d[25]), "+f"(d[26]), "+f"(d[27]), "+f"(d[28]), "+f"(d[29]), "+f"(d[30]), "+f"(d[31])
    : "r"(a0), "r"(a1), "r"(a2), "r"(a3), "l"(db), "r"(scale_d));
}

__device__ __forceinline__ void wgmma_pv(float (&d)[96], uint32_t a0, uint32_t a1, uint32_t a2, uint32_t a3, uint64_t db, int scale_d) {
  asm volatile("{\n.reg .pred p;\nsetp.ne.b32 p, %101, 0;\n"
    "wgmma.mma_async.sync.aligned.m64n192k16.f32.bf16.bf16 "
    "{%0, %1, %2, %3, %4, %5, %6, %7, %8, %9, %10, %11, %12, %13, %14, %15, %16, %17, %18, %19, %20, %21, %22, %23, %24, %25, %26, %27, %28, %29, %30, %31, %32, %33, %34, %35, %36, %37, %38, %39, %40, %41, %42, %43, %44, %45, %46, %47, %48, %49, %50, %51, %52, %53, %54, %55, %56, %57, %58, %59, %60, %61, %62, %63, %64, %65, %66, %67, %68, %69, %70, %71, %72, %73, %74, %75, %76, %77, %78, %79, %80, %81, %82, %83, %84, %85, %86, %87, %88, %89, %90, %91, %92, %93, %94, %95}, "
    "{%96, %97, %98, %99}, %100, p, 1, 1, 1;\n}\n"
    : "+f"(d[0]), "+f"(d[1]), "+f"(d[2]), "+f"(d[3]), "+f"(d[4]), "+f"(d[5]), "+f"(d[6]), "+f"(d[7]), "+f"(d[8]), "+f"(d[9]), "+f"(d[10]), "+f"(d[11]), "+f"(d[12]), "+f"(d[13]), "+f"(d[14]), "+f"(d[15]), "+f"(d[16]), "+f"(d[17]), "+f"(d[18]), "+f"(d[19]), "+f"(d[20]), "+f"(d[21]), "+f"(d[22]), "+f"(d[23]), "+f"(d[24]), "+f"(d[25]), "+f"(d[26]), "+f"(d[27]), "+f"(d[28]), "+f"(d[29]), "+f"(d[30]), "+f"(d[31]), "+f"(d[32]), "+f"(d[33]), "+f"(d[34]), "+f"(d[35]), "+f"(d[36]), "+f"(d[37]), "+f"(d[38]), "+f"(d[39]), "+f"(d[40]), "+f"(d[41]), "+f"(d[42]), "+f"(d[43]), "+f"(d[44]), "+f"(d[45]), "+f"(d[46]), "+f"(d[47]), "+f"(d[48]), "+f"(d[49]), "+f"(d[50]), "+f"(d[51]), "+f"(d[52]), "+f"(d[53]), "+f"(d[54]), "+f"(d[55]), "+f"(d[56]), "+f"(d[57]), "+f"(d[58]), "+f"(d[59]), "+f"(d[60]), "+f"(d[61]), "+f"(d[62]), "+f"(d[63]), "+f"(d[64]), "+f"(d[65]), "+f"(d[66]), "+f"(d[67]), "+f"(d[68]), "+f"(d[69]), "+f"(d[70]), "+f"(d[71]), "+f"(d[72]), "+f"(d[73]), "+f"(d[74]), "+f"(d[75]), "+f"(d[76]), "+f"(d[77]), "+f"(d[78]), "+f"(d[79]), "+f"(d[80]), "+f"(d[81]), "+f"(d[82]), "+f"(d[83]), "+f"(d[84]), "+f"(d[85]), "+f"(d[86]), "+f"(d[87]), "+f"(d[88]), "+f"(d[89]), "+f"(d[90]), "+f"(d[91]), "+f"(d[92]), "+f"(d[93]), "+f"(d[94]), "+f"(d[95])
    : "r"(a0), "r"(a1), "r"(a2), "r"(a3), "l"(db), "r"(scale_d));
}

__device__ __forceinline__ void wgmma_qkT(float (&d)[8], uint64_t da, uint64_t db, int scale_d) {
  asm volatile("{\n.reg .pred p;\nsetp.ne.b32 p, %10, 0;\n"
    "wgmma.mma_async.sync.aligned.m64n16k16.f32.bf16.bf16 "
    "{%0, %1, %2, %3, %4, %5, %6, %7}, "
    "%8, %9, p, 1, 1, 0, 0;\n}\n"
    : "+f"(d[0]), "+f"(d[1]), "+f"(d[2]), "+f"(d[3]), "+f"(d[4]), "+f"(d[5]), "+f"(d[6]), "+f"(d[7])
    : "l"(da), "l"(db), "r"(scale_d));
}
__device__ __forceinline__ void wgmma_pvT(float (&d)[8], uint64_t da, uint64_t db, int scale_d) {
  asm volatile("{\n.reg .pred p;\nsetp.ne.b32 p, %10, 0;\n"
    "wgmma.mma_async.sync.aligned.m64n16k16.f32.bf16.bf16 "
    "{%0, %1, %2, %3, %4, %5, %6, %7}, "
    "%8, %9, p, 1, 1, 1, 0;\n}\n"
    : "+f"(d[0]), "+f"(d[1]), "+f"(d[2]), "+f"(d[3]), "+f"(d[4]), "+f"(d[5]), "+f"(d[6]), "+f"(d[7])
    : "l"(da), "l"(db), "r"(scale_d));
}

__device__ __forceinline__ void wgmma_qk0(float (&d)[32], uint32_t a0, uint32_t a1, uint32_t a2, uint32_t a3, uint64_t db) {
  asm volatile("{\n.reg .pred p;\nsetp.ne.b32 p, 0, 0;\n"
    "wgmma.mma_async.sync.aligned.m64n64k16.f32.bf16.bf16 "
    "{%0, %1, %2, %3, %4, %5, %6, %7, %8, %9, %10, %11, %12, %13, %14, %15, %16, %17, %18, %19, %20, %21, %22, %23, %24, %25, %26, %27, %28, %29, %30, %31}, "
    "{%32, %33, %34, %35}, %36, p, 1, 1, 0;\n}\n"
    : "=f"(d[0]), "=f"(d[1]), "=f"(d[2]), "=f"(d[3]), "=f"(d[4]), "=f"(d[5]), "=f"(d[6]), "=f"(d[7]), "=f"(d[8]), "=f"(d[9]), "=f"(d[10]), "=f"(d[11]), "=f"(d[12]), "=f"(d[13]), "=f"(d[14]), "=f"(d[15]), "=f"(d[16]), "=f"(d[17]), "=f"(d[18]), "=f"(d[19]), "=f"(d[20]), "=f"(d[21]), "=f"(d[22]), "=f"(d[23]), "=f"(d[24]), "=f"(d[25]), "=f"(d[26]), "=f"(d[27]), "=f"(d[28]), "=f"(d[29]), "=f"(d[30]), "=f"(d[31])
    : "r"(a0), "r"(a1), "r"(a2), "r"(a3), "l"(db));
}
__device__ __forceinline__ void wgmma_pv0(float (&d)[96], uint32_t a0, uint32_t a1, uint32_t a2, uint32_t a3, uint64_t db) {
  asm volatile("{\n.reg .pred p;\nsetp.ne.b32 p, 0, 0;\n"
    "wgmma.mma_async.sync.aligned.m64n192k16.f32.bf16.bf16 "
    "{%0, %1, %2, %3, %4, %5, %6, %7, %8, %9, %10, %11, %12, %13, %14, %15, %16, %17, %18, %19, %20, %21, %22, %23, %24, %25, %26, %27, %28, %29, %30, %31, %32, %33, %34, %35, %36, %37, %38, %39, %40, %41, %42, %43, %44, %45, %46, %47, %48, %49, %50, %51, %52, %53, %54, %55, %56, %57, %58, %59, %60, %61, %62, %63, %64, %65, %66, %67, %68, %69, %70, %71, %72, %73, %74, %75, %76, %77, %78, %79, %80, %81, %82, %83, %84, %85, %86, %87, %88, %89, %90, %91, %92, %93, %94, %95}, "
    "{%96, %97, %98, %99}, %100, p, 1, 1, 1;\n}\n"
    : "=f"(d[0]), "=f"(d[1]), "=f"(d[2]), "=f"(d[3]), "=f"(d[4]), "=f"(d[5]), "=f"(d[6]), "=f"(d[7]), "=f"(d[8]), "=f"(d[9]), "=f"(d[10]), "=f"(d[11]), "=f"(d[12]), "=f"(d[13]), "=f"(d[14]), "=f"(d[15]), "=f"(d[16]), "=f"(d[17]), "=f"(d[18]), "=f"(d[19]), "=f"(d[20]), "=f"(d[21]), "=f"(d[22]), "=f"(d[23]), "=f"(d[24]), "=f"(d[25]), "=f"(d[26]), "=f"(d[27]), "=f"(d[28]), "=f"(d[29]), "=f"(d[30]), "=f"(d[31]), "=f"(d[32]), "=f"(d[33]), "=f"(d[34]), "=f"(d[35]), "=f"(d[36]), "=f"(d[37]), "=f"(d[38]), "=f"(d[39]), "=f"(d[40]), "=f"(d[41]), "=f"(d[42]), "=f"(d[43]), "=f"(d[44]), "=f"(d[45]), "=f"(d[46]), "=f"(d[47]), "=f"(d[48]), "=f"(d[49]), "=f"(d[50]), "=f"(d[51]), "=f"(d[52]), "=f"(d[53]), "=f"(d[54]), "=f"(d[55]), "=f"(d[56]), "=f"(d[57]), "=f"(d[58]), "=f"(d[59]), "=f"(d[60]), "=f"(d[61]), "=f"(d[62]), "=f"(d[63]), "=f"(d[64]), "=f"(d[65]), "=f"(d[66]), "=f"(d[67]), "=f"(d[68]), "=f"(d[69]), "=f"(d[70]), "=f"(d[71]), "=f"(d[72]), "=f"(d[73]), "=f"(d[74]), "=f"(d[75]), "=f"(d[76]), "=f"(d[77]), "=f"(d[78]), "=f"(d[79]), "=f"(d[80]), "=f"(d[81]), "=f"(d[82]), "=f"(d[83]), "=f"(d[84]), "=f"(d[85]), "=f"(d[86]), "=f"(d[87]), "=f"(d[88]), "=f"(d[89]), "=f"(d[90]), "=f"(d[91]), "=f"(d[92]), "=f"(d[93]), "=f"(d[94]), "=f"(d[95])
    : "r"(a0), "r"(a1), "r"(a2), "r"(a3), "l"(db));
}
__device__ __forceinline__ void wgmma_qkT0(float (&d)[8], uint64_t da, uint64_t db) {
  asm volatile("{\n.reg .pred p;\nsetp.ne.b32 p, 0, 0;\n"
    "wgmma.mma_async.sync.aligned.m64n16k16.f32.bf16.bf16 "
    "{%0, %1, %2, %3, %4, %5, %6, %7}, "
    "%8, %9, p, 1, 1, 0, 0;\n}\n"
    : "=f"(d[0]), "=f"(d[1]), "=f"(d[2]), "=f"(d[3]), "=f"(d[4]), "=f"(d[5]), "=f"(d[6]), "=f"(d[7])
    : "l"(da), "l"(db));
}
__device__ __forceinline__ void wgmma_pvT0(float (&d)[8], uint64_t da, uint64_t db) {
  asm volatile("{\n.reg .pred p;\nsetp.ne.b32 p, 0, 0;\n"
    "wgmma.mma_async.sync.aligned.m64n16k16.f32.bf16.bf16 "
    "{%0, %1, %2, %3, %4, %5, %6, %7}, "
    "%8, %9, p, 1, 1, 1, 0;\n}\n"
    : "=f"(d[0]), "=f"(d[1]), "=f"(d[2]), "=f"(d[3]), "=f"(d[4]), "=f"(d[5]), "=f"(d[6]), "=f"(d[7])
    : "l"(da), "l"(db));
}

struct Round { int head, qrow, mc; };
__device__ __forceinline__ Round decode_round(int g, int rank) {
  int p = g / 7, r = g - p * 7;
  Round o;
  if (r < 3) { o.head = 2 * p; o.qrow = r * 256 + rank * 128; o.mc = 1; }
  else if (r == 3) { o.head = 2 * p + rank; o.qrow = 768; o.mc = 0; }
  else { o.head = 2 * p + 1; o.qrow = (r - 4) * 256 + rank * 128; o.mc = 1; }
  return o;
}

__device__ __forceinline__ uint32_t kdesc0(uint32_t s_kv) { return ((s_kv & 0x3FFFFu) >> 4) | (1u << 16); }
__device__ __forceinline__ uint32_t vdesc0(uint32_t s_kv) { return ((s_kv & 0x3FFFFu) >> 4) | ((uint32_t)(SLAB >> 4) << 16); }
constexpr uint64_t DESC_HI = ((uint64_t)(RGRP >> 4) << 32) | ((uint64_t)1 << 62);
constexpr uint64_t DESC_HI_PT = ((uint64_t)(1024 >> 4) << 32) | ((uint64_t)1 << 62);

__device__ __forceinline__ void issue_qk(float (&S)[32], const uint32_t (&Q)[48], uint32_t kdesc) {
  const uint64_t d = DESC_HI | kdesc;
  wgmma_qk0(S, Q[0], Q[1], Q[2], Q[3], d);
#pragma unroll
  for (int kk = 1; kk < 12; kk++)
    wgmma_qk(S, Q[kk * 4], Q[kk * 4 + 1], Q[kk * 4 + 2], Q[kk * 4 + 3], d + (uint64_t)((kk / 4) * (SLAB / 16) + (kk % 4) * 2), 1);
}
__device__ __forceinline__ void issue_qk32(float (&S)[32], const uint32_t (&Q)[48], uint32_t kdesc) {
  uint32_t d[12];
#pragma unroll
  for (int kk = 0; kk < 12; kk++) {
    d[kk] = kdesc + ((kk / 4) * (SLAB / 16) + (kk % 4) * 2);
    asm volatile("" : "+r"(d[kk]));
  }
  wgmma_qk0(S, Q[0], Q[1], Q[2], Q[3], DESC_HI | d[0]);
#pragma unroll
  for (int kk = 1; kk < 12; kk++) wgmma_qk(S, Q[kk * 4], Q[kk * 4 + 1], Q[kk * 4 + 2], Q[kk * 4 + 3], DESC_HI | d[kk], 1);
}
__device__ __forceinline__ void issue_qk3(float (&S)[32], const uint32_t (&Q)[48], uint32_t kdesc) {
  const uint64_t d = DESC_HI | kdesc;
  wgmma_qk0(S, Q[0], Q[1], Q[2], Q[3], d);
#pragma unroll
  for (int kk = 1; kk < 12; kk++) {
    if (kk % 4 == 0) wg_commit();
    wgmma_qk(S, Q[kk * 4], Q[kk * 4 + 1], Q[kk * 4 + 2], Q[kk * 4 + 3], d + (uint64_t)((kk / 4) * (SLAB / 16) + (kk % 4) * 2), 1);
  }
}
template <bool ACCUMULATE>
__device__ __forceinline__ void issue_pv(float (&O)[96], const uint32_t (&P)[16], uint32_t vdesc) {
  const uint64_t d = DESC_HI | vdesc;
  if (ACCUMULATE) wgmma_pv(O, P[0], P[1], P[2], P[3], d, 1);
  else wgmma_pv0(O, P[0], P[1], P[2], P[3], d);
#pragma unroll
  for (int kk = 1; kk < 4; kk++)
    wgmma_pv(O, P[kk * 4], P[kk * 4 + 1], P[kk * 4 + 2], P[kk * 4 + 3], d + (uint64_t)(kk * (2 * RGRP / 16)), 1);
}

template <int K0 = 0, int K1 = 12>
__device__ __forceinline__ void load_q(uint32_t (&Q)[48], uint32_t lane_addr) {
#pragma unroll
  for (int kk = K0; kk < K1; kk++)
    ldsm_x4((lane_addr ^ ((kk % 4) << 5)) + (kk / 4) * SLAB, Q[kk * 4], Q[kk * 4 + 1], Q[kk * 4 + 2], Q[kk * 4 + 3]);
}

__device__ __forceinline__ void softmax_block(const float (&S)[32], uint32_t (&P)[16], float& l0, float& l1) {
#pragma unroll
  for (int i = 0; i < 8; i++) {
    const float a = ex2(S[4 * i + 0] * SCALE_LOG2);
    const float b = ex2(S[4 * i + 1] * SCALE_LOG2);
    const float c = ex2(S[4 * i + 2] * SCALE_LOG2);
    const float d = ex2(S[4 * i + 3] * SCALE_LOG2);
    l0 += a + b;
    l1 += c + d;
    P[2 * i] = pack_bf16(a, b);
    P[2 * i + 1] = pack_bf16(c, d);
  }
  fence_regs(P);
}

__device__ __forceinline__ void sums_put(uint32_t addr, float l0, float l1, uint32_t on) {
  asm volatile("{\n.reg .pred p;\nsetp.ne.u32 p, %3, 0;\n@p st.shared.v2.f32 [%0], {%1, %2};\n}\n" ::"r"(addr), "f"(l0), "f"(l1), "r"(on) : "memory");
}
__device__ __forceinline__ void sums_get(uint32_t addr, float& s0, float& s1) {
  float a, b, c, d, e, f, g, h;
  asm volatile("ld.shared.v4.f32 {%0, %1, %2, %3}, [%8];\nld.shared.v4.f32 {%4, %5, %6, %7}, [%8 + 16];\n"
               : "=f"(a), "=f"(b), "=f"(c), "=f"(d), "=f"(e), "=f"(f), "=f"(g), "=f"(h) : "r"(addr & ~31u) : "memory");
  s0 = (a + c) + (e + g);
  s1 = (b + d) + (f + h);
}

template <int K0, int K1>
__device__ __forceinline__ void epilogue_part(const float (&O)[96], float i0, float i1, uint32_t lane_addr) {
#pragma unroll
  for (int kk = K0; kk < K1; kk++) {
    const int b = kk * 8;
    stsm_x4((lane_addr ^ ((kk % 4) << 5)) + (kk / 4) * SLAB,
            pack_bf16(O[b] * i0, O[b + 1] * i0), pack_bf16(O[b + 2] * i1, O[b + 3] * i1),
            pack_bf16(O[b + 4] * i0, O[b + 5] * i0), pack_bf16(O[b + 6] * i1, O[b + 7] * i1));
  }
}
__device__ __forceinline__ void epilogue_done(uint32_t bar, int lane) {
  __syncwarp();
  if (lane == 0) mbar_arrive(bar);
}

__device__ __forceinline__ void redo_tile(const CUtensorMap* tmQ, const CUtensorMap* tmK, const CUtensorMap* tmV, const CUtensorMap* tmO,
                                          int head, int row, uint32_t qo, uint32_t kv, uint32_t lane_addr, uint32_t bar, uint32_t& phase,
                                          uint32_t wg_bar) {
  float O[96], S[32];
  uint32_t Q[48], P[16];
  uint64_t pol;
  asm volatile("createpolicy.fractional.L2::evict_normal.b64 %0, 1.0;" : "=l"(pol));
  const bool leader = (threadIdx.x & 127) == 0;
  if (leader) {
    mbar_expect_tx(bar, SLOT);
    tma_load(qo, tmQ, bar, row, head, pol);
  }
  mbar_wait(bar, phase);
  phase ^= 1;
  load_q(Q, lane_addr);
  float m0 = -INFINITY, m1 = -INFINITY, l0 = 0.f, l1 = 0.f;
#pragma unroll
  for (int i = 0; i < 96; i++) O[i] = 0.f;
#pragma unroll 1
  for (int j = 0; j < NBLK; j++) {
    asm volatile("bar.sync %0, 128;" ::"r"(wg_bar) : "memory");
    if (leader) {
      mbar_expect_tx(bar, 2 * SLOT);
      tma_load(kv, tmK, bar, j * BN, head, pol);
      tma_load(kv + SLOT, tmV, bar, j * BN, head, pol);
    }
    mbar_wait(bar, phase);
    phase ^= 1;
    wg_fence();
    issue_qk(S, Q, kdesc0(kv));
    wg_commit();
    wg_wait<0>();
    fence_regs(S);
    float n0 = m0, n1 = m1;
#pragma unroll
    for (int i = 0; i < 8; i++) {
      n0 = fmaxf(n0, fmaxf(S[4 * i], S[4 * i + 1]));
      n1 = fmaxf(n1, fmaxf(S[4 * i + 2], S[4 * i + 3]));
    }
#pragma unroll
    for (int o = 1; o < 4; o <<= 1) {
      n0 = fmaxf(n0, __shfl_xor_sync(0xffffffffu, n0, o));
      n1 = fmaxf(n1, __shfl_xor_sync(0xffffffffu, n1, o));
    }
    const float f0 = ex2((m0 - n0) * SCALE_LOG2), f1 = ex2((m1 - n1) * SCALE_LOG2);
    m0 = n0; m1 = n1;
    l0 *= f0; l1 *= f1;
#pragma unroll
    for (int i = 0; i < 24; i++) {
      O[4 * i] *= f0; O[4 * i + 1] *= f0; O[4 * i + 2] *= f1; O[4 * i + 3] *= f1;
    }
#pragma unroll
    for (int i = 0; i < 8; i++) {
      S[4 * i] -= m0; S[4 * i + 1] -= m0; S[4 * i + 2] -= m1; S[4 * i + 3] -= m1;
    }
    softmax_block(S, P, l0, l1);
    fence_regs(O);
    wg_fence();
    issue_pv<true>(O, P, vdesc0(kv + SLOT));
    wg_commit();
    wg_wait<0>();
    fence_regs(O);
  }
#pragma unroll
  for (int o = 1; o < 4; o <<= 1) {
    l0 += __shfl_xor_sync(0xffffffffu, l0, o);
    l1 += __shfl_xor_sync(0xffffffffu, l1, o);
  }
  epilogue_part<0, 12>(O, rcp(l0), rcp(l1), lane_addr);
  asm volatile("fence.proxy.async.shared::cta;" ::: "memory");
  asm volatile("bar.sync %0, 128;" ::"r"(wg_bar) : "memory");
  if (leader) {
    for (int i = 0; i < 64 && row + i < SQ; i += OROWS) tma_store(tmO, qo + i / 8 * RGRP, row + i, head, pol);
    asm volatile("cp.async.bulk.commit_group;" ::: "memory");
    asm volatile("cp.async.bulk.wait_group 0;" ::: "memory");
  }
}

__device__ __forceinline__ void wg_barrier() { asm volatile("bar.sync 3, 128;" ::: "memory"); }

__device__ __forceinline__ void tail_reduce(float (&v)[4], uint32_t red, int warp, int lane) {
#pragma unroll
  for (int o = 4; o < 32; o <<= 1)
#pragma unroll
    for (int i = 0; i < 4; i++) v[i] += __shfl_xor_sync(0xffffffffu, v[i], o);
  if (lane < 4)
    asm volatile("st.shared.v4.f32 [%0], {%1, %2, %3, %4};" ::"r"(red + (warp * 4 + lane) * 16), "f"(v[0]), "f"(v[1]), "f"(v[2]), "f"(v[3]) : "memory");
  wg_barrier();
#pragma unroll
  for (int ww = 0; ww < 4; ww++) {
    float x0, x1, x2, x3;
    asm volatile("ld.shared.v4.f32 {%0, %1, %2, %3}, [%4];" : "=f"(x0), "=f"(x1), "=f"(x2), "=f"(x3) : "r"(red + (ww * 4 + (lane & 3)) * 16) : "memory");
    if (ww == 0) { v[0] = x0; v[1] = x1; v[2] = x2; v[3] = x3; }
    else { v[0] += x0; v[1] += x1; v[2] += x2; v[3] += x3; }
  }
}

__device__ __forceinline__ void tail_softmax(const float (&S)[8], float (&l)[4], uint32_t pt_addr) {
  float e[8];
#pragma unroll
  for (int i = 0; i < 8; i++) e[i] = ex2(S[i] * SCALE_LOG2);
  stsm_x4_trans(pt_addr, pack_bf16(e[0], e[1]), pack_bf16(e[2], e[3]), pack_bf16(e[4], e[5]), pack_bf16(e[6], e[7]));
  l[0] += e[0] + e[2]; l[1] += e[1] + e[3]; l[2] += e[4] + e[6]; l[3] += e[5] + e[7];
}

__device__ __forceinline__ void issue_qkT(float (&S8)[8], uint32_t kdesc, uint32_t qt_addr) {
  const uint64_t da = DESC_HI | kdesc;
  const uint64_t db = DESC_HI | (uint64_t)(((qt_addr & 0x3FFFFu) >> 4) | (1u << 16));
  wgmma_qkT0(S8, da, db);
#pragma unroll
  for (int kk = 1; kk < 12; kk++)
    wgmma_qkT(S8, da + (uint64_t)((kk / 4) * (SLAB / 16) + (kk % 4) * 2), db + (uint64_t)((kk / 4) * (SLAB / 16) + (kk % 4) * 2), 1);
}
template <bool ACCUMULATE>
__device__ __forceinline__ void issue_pvT(float (&O)[3][8], uint32_t vdesc, uint32_t pt_base) {
  const uint64_t da = DESC_HI | vdesc;
  const uint64_t db = DESC_HI_PT | (uint64_t)(((pt_base & 0x3FFFFu) >> 4) | (1u << 16));
#pragma unroll
  for (int kk = 0; kk < 4; kk++)
#pragma unroll
    for (int b = 0; b < 3; b++) {
      if (kk == 0 && !ACCUMULATE) wgmma_pvT0(O[b], da + (uint64_t)(b * (SLAB / 16)), db);
      else wgmma_pvT(O[b], da + (uint64_t)(b * (SLAB / 16) + kk * (2 * RGRP / 16)), db + (uint64_t)(kk * 2), 1);
    }
}

template <bool B> struct Bool { static constexpr bool value = B; };

constexpr int MAX_CLUSTERS = 72;
constexpr int MAX_ROUNDS = 32;
struct Schedule {
  uint32_t tails[MAX_CLUSTERS];
  uint16_t start[MAX_CLUSTERS + 1];
  uint16_t list[NROUNDS + 1];
};

#define TRACE_TILE()

__global__ void __cluster_dims__(2, 1, 1) __launch_bounds__(NTHREADS, 1)
attn_kernel(const __grid_constant__ CUtensorMap tmQ, const __grid_constant__ CUtensorMap tmQT, const __grid_constant__ CUtensorMap tmK,
            const __grid_constant__ CUtensorMap tmV, const __grid_constant__ CUtensorMap tmO, const __grid_constant__ Schedule sched) {
  extern __shared__ __align__(1024) uint8_t smem_raw[];
  const uint32_t c_entry = (uint32_t)clock();
  const uint32_t sbase = smem_u32(smem_raw);
  const uint32_t s_qo = sbase + OFF_QO;
  const uint32_t s_kv = sbase + OFF_KV;
  const uint32_t s_bar = sbase + OFF_BAR;
  const uint32_t bar_full = s_bar;
  const uint32_t bar_empty = s_bar + 8 * NSLOT;
  const uint32_t bar_qfull = s_bar + 16 * NSLOT;
  const uint32_t bar_ostg = bar_qfull + 16;
  const uint32_t bar_qreq = bar_ostg + 16;
  const uint32_t bar_redo = bar_qreq + 16;
  const uint32_t s_redo = bar_redo + 16;

  uint32_t rank;
  asm("mov.u32 %0, %%cluster_ctarank;" : "=r"(rank));
  const int cluster = blockIdx.x >> 1;
  auto get_rounds = [&](int& first, int& count) {
    int c = cluster;
    asm volatile("" : "+r"(c));
    first = sched.start[c];
    count = sched.start[c + 1] - first;
  };

  if (threadIdx.x == 0) {
    asm volatile("prefetch.tensormap [%0];" ::"l"(&tmK) : "memory");
    asm volatile("prefetch.tensormap [%0];" ::"l"(&tmQ) : "memory");
    asm volatile("prefetch.tensormap [%0];" ::"l"(&tmV) : "memory");
    for (int i = 0; i < 3; i++) mbar_init(bar_full + 8 * i, 1);
    for (int i = 0; i < 2; i++) mbar_init(bar_qfull + 8 * i, 1);
    asm volatile("fence.mbarrier_init.release.cluster;" ::: "memory");
    asm volatile("fence.proxy.async.shared::cta;" ::: "memory");
    const int head = cluster / 3, qrow = cluster % 3 * 256 + rank * 128;
    uint64_t polq, polk;
    asm volatile("createpolicy.fractional.L2::evict_first.b64 %0, 1.0;" : "=l"(polq));
    asm volatile("createpolicy.fractional.L2::evict_unchanged.b64 %0, 1.0;" : "=l"(polk));
    while ((uint32_t)clock() - c_entry < (uint32_t)(cluster / 3 * STAGGER)) {}
    mbar_expect_tx(bar_full, SLOT);
    tma_load(s_kv, &tmK, bar_full, 0, head, polk);
    mbar_expect_tx(bar_qfull, SLOT);
    tma_load(s_qo, &tmQ, bar_qfull, qrow, head, polq);
    mbar_expect_tx(bar_full + 8, SLOT);
    tma_load(s_kv + SLOT, &tmK, bar_full + 8, BN, head, polk);
    mbar_expect_tx(bar_full + 16, SLOT);
    tma_load(s_kv + 2 * SLOT, &tmV, bar_full + 16, 0, head, polk);
    mbar_expect_tx(bar_qfull + 8, SLOT);
    tma_load(s_qo + SLOT, &tmQ, bar_qfull + 8, qrow + 64, head, polq);
  } else if (threadIdx.x == 32) {
    for (int i = 0; i < NSLOT; i++) {
      if (i >= 3) mbar_init(bar_full + 8 * i, 1);
      mbar_init(bar_empty + 8 * i, 4);
    }
    for (int i = 0; i < 2; i++) {
      mbar_init(bar_ostg + 8 * i, 4);
      mbar_init(bar_qreq + 8 * i, 1);
      mbar_init(bar_redo + 8 * i, 1);
      asm volatile("st.shared.u32 [%0], %1;" ::"r"(s_redo + 4 * i), "r"(0) : "memory");
    }
    asm volatile("fence.mbarrier_init.release.cluster;" ::: "memory");
    asm volatile("fence.proxy.async.shared::cta;" ::: "memory");
  }
  __syncthreads();
  asm volatile("barrier.cluster.arrive.relaxed.aligned;\nbarrier.cluster.wait.aligned;" ::: "memory");

  const int wg = __shfl_sync(0xffffffffu, threadIdx.x >> 7, 0);
  const int warp = __shfl_sync(0xffffffffu, (threadIdx.x >> 5) & 3, 0);
  const int lane = threadIdx.x & 31;

  if (wg == 0) {
    asm volatile("setmaxnreg.dec.sync.aligned.u32 24;");
    int first_round, nrounds;
    get_rounds(first_round, nrounds);
    const int nblocks = nrounds * NBLK;
    if (warp == 0 && lane == 0) {
      uint64_t pol;
      asm volatile("createpolicy.fractional.L2::evict_unchanged.b64 %0, 1.0;" : "=l"(pol));
      uint32_t slot = 3, phase = 1;
      auto load = [&](const CUtensorMap* tm, int n, uint32_t owner) {
        const Round r = decode_round(sched.list[first_round + (n >> 3)] & 0x7ff, rank);
        mbar_wait_sleep(bar_empty + 8 * slot, phase);
        if (n < nblocks) {
          mbar_expect_tx(bar_full + 8 * slot, SLOT);
          if (!r.mc) tma_load(s_kv + slot * SLOT, tm, bar_full + 8 * slot, (n & 7) * BN, r.head, pol);
          else if (rank == owner) tma_load_mc(s_kv + slot * SLOT, tm, bar_full + 8 * slot, (n & 7) * BN, r.head, pol);
        }
        if (++slot == NSLOT) { slot = 0; phase ^= 1; }
      };
      for (int n = 1; n < nblocks; n++) {
        load(&tmK, n + 1, 0);
        load(&tmV, n, 1);
      }
      for (int i = 0; i < NSLOT; i++) {
        if (i != NSLOT - 2) mbar_wait_sleep(bar_empty + 8 * slot, phase);
        if (++slot == NSLOT) { slot = 0; phase ^= 1; }
      }
    } else if ((warp == 1 || warp == 2) && lane == 0) {
      const int w = warp - 1;
      uint64_t pol;
      asm volatile("createpolicy.fractional.L2::evict_first.b64 %0, 1.0;" : "=l"(pol));
      const uint32_t buf = s_qo + w * SLOT;
      Round r = decode_round(sched.list[first_round] & 0x7ff, rank);
      Round prev = r;
      for (int t = 0; t <= nrounds; t++) {
        mbar_wait_sleep(bar_ostg + 8 * w, t & 1);
        if (t > 0) {
          asm volatile("fence.proxy.async.shared::cta;" ::: "memory");
          const int row0 = prev.qrow + w * 64;
          const int nrows = row0 + 64 <= SQ ? 64 : SQ - row0;
#pragma unroll 1
          for (int i = 0; i < nrows; i += OROWS) {
            tma_store(&tmO, buf + i / 8 * RGRP, row0 + i, prev.head, pol);
            asm volatile("cp.async.bulk.commit_group;" ::: "memory");
            if (t < nrounds) asm volatile("cp.async.bulk.wait_group.read 0;" ::: "memory");
          }
          prev = r;
        }
        if (t + 1 < nrounds) {
          mbar_wait_sleep(bar_qreq + 8 * w, t & 1);
          const uint32_t e = sched.list[first_round + t + 1];
          r = decode_round(e & 0x7ff, rank);
          if (w == 1 && (e & 0x8000)) {
            mbar_expect_tx(bar_qfull + 8 * w, 3 * 2048);
            tma_load(sbase + OFF_QT, &tmQT, bar_qfull + 8 * w, r.qrow + 64, r.head, pol);
          } else {
            mbar_expect_tx(bar_qfull + 8 * w, SLOT);
            tma_load(buf, &tmQ, bar_qfull + 8 * w, r.qrow + w * 64, r.head, pol);
          }
        } else if (t < nrounds) {
          mbar_arrive(bar_qfull + 8 * w);
        }
      }
      asm volatile("cp.async.bulk.wait_group 0;" ::: "memory");
      mbar_arrive(bar_redo + 8 * w);
    } else if (warp == 3) {
      uint32_t slot = 1, phase = 0;
      const uint32_t tails = sched.tails[cluster];
      for (int n = 0; n < nblocks; n++) {
        if (n + 1 < nblocks) mbar_wait(bar_full + 8 * slot, phase);
        if (++slot == NSLOT) { slot = 0; phase ^= 1; }
        mbar_wait(bar_full + 8 * slot, phase);
        if (++slot == NSLOT) { slot = 0; phase ^= 1; }
        asm volatile("bar.sync 1, 288;" ::: "memory");
        asm volatile("bar.arrive 2, 288;" ::: "memory");
        if (lane < 2 && (n & 7) + ((tails >> (n >> 3 & 31) & 1) ? QREQT : 0) == (lane ? QREQ1 : QREQ0)) mbar_arrive(bar_qreq + 8 * lane);
        TRACE_TILE();
      }
    }
  } else {
    asm volatile("setmaxnreg.inc.sync.aligned.u32 240;");
    const int w = wg - 1;
    int first_round, nrounds;
    get_rounds(first_round, nrounds);
    const int nblocks = nrounds * NBLK;
    float O[96], S[32];
    uint32_t Q[48], P0[16], P1[16];
    float l0 = 0.f, l1 = 0.f, inv0 = 0.f, inv1 = 0.f;
    uint32_t redo = 0;
    const uint32_t lane_addr = s_qo + w * SLOT + (warp * 2 + ((lane >> 3) & 1)) * RGRP + (lane & 7) * 128 + (((lane >> 4) ^ (lane & 7)) << 4);
    const uint32_t sum_addr = s_qo + w * SLOT + warp * 2 * RGRP + lane * 8;
    const uint32_t my_qfull = bar_qfull + 8 * w, my_ostg = bar_ostg + 8 * w;

    uint32_t empty_remote;
    asm("mapa.shared::cluster.u32 %0, %1, %2;" : "=r"(empty_remote) : "r"(bar_empty), "r"(threadIdx.x & 1));
    const bool releaser = (threadIdx.x & 127) < 2;
    auto release = [&](uint32_t s) {
      if (releaser) asm volatile("mbarrier.arrive.shared::cluster.b64 _, [%0];" ::"r"(empty_remote + s) : "memory");
    };
    uint32_t ks = 8, vs = 16, kp = 0, vp = 0;
    const uint32_t kd0 = kdesc0(s_kv), vd0 = vdesc0(s_kv);
    uint32_t kd = kd0 + ks * (SLOT / 128), vd = vd0 + vs * (SLOT / 128);
    auto advance = [&]() {
      kp = ks; vp = vs;
      ks = ks >= 8 * (NSLOT - 2) ? ks - 8 * (NSLOT - 2) : ks + 16;
      vs = vs >= 8 * (NSLOT - 2) ? vs - 8 * (NSLOT - 2) : vs + 16;
      kd = kd0 + ks * (SLOT / 128); vd = vd0 + vs * (SLOT / 128);
      asm volatile("" : "+r"(ks), "+r"(vs), "+r"(kd), "+r"(vd));
    };

    uint32_t tails = w == 1 ? sched.tails[cluster] : 0u;
    auto turn_wait = [&]() { asm volatile("bar.sync %0, 288;" ::"r"(1 + w) : "memory"); };
    auto turn_pass = [&]() { asm volatile("bar.arrive %0, 288;" ::"r"(2 - w) : "memory"); };
    if (w == 1) turn_pass();

    mbar_wait(my_qfull, 0);
    load_q(Q, lane_addr);
    mbar_wait(bar_full, 0);
    wg_fence();
    issue_qk(S, Q, kd0);
    wg_commit();
    wg_wait<0>();
    fence_regs(S);
    release(0);
    __syncwarp();
    if (lane == 0) mbar_arrive(my_ostg);
    bool pending = false;

    int n = 0;
    auto finish_sums = [&]() {
      float s0, s1;
      sums_get(sum_addr, s0, s1);
      if (!(sum_ok(s0) && sum_ok(s1))) redo |= 1u << ((n >> 3) & 31);
      inv0 = rcp(s0); inv1 = rcp(s1);
      l0 = l1 = 0.f;
      asm volatile("" : "+f"(inv0), "+f"(inv1), "+r"(redo)::"memory");
    };

    int exit_n = -1;
#pragma unroll 1
    while (true) {
#pragma unroll 1
      while (true) {
        const int j = n & 7;
        softmax_block(S, P0, l0, l1);
        asm volatile("" : "+f"(l0), "+f"(l1)::"memory");
        if (j != 0) {
          wg_wait<0>();
          release(vp);
          turn_wait();
          wg_fence();
          issue_qk3(S, Q, kd);
          wg_commit();
          issue_pv<true>(O, P0, vd);
          wg_commit();
          turn_pass();
          advance();
          if (j == 6) {
            mbar_wait(my_qfull, ((n >> 3) + 1) & 1);
            wg_wait<3>();
            load_q<0, 4>(Q, lane_addr);
            wg_wait<2>();
            load_q<4, 8>(Q, lane_addr);
          }
          wg_wait<1>();
          fence_regs(S);
          fence_regs(P1);
        } else {
          wg_wait<0>();
          fence_regs(O);
          fence_regs(P1);
          if (pending) {
            release(vp);
            epilogue_part<0, ESPLIT>(O, inv0, inv1, lane_addr);
          }
          turn_wait();
          wg_fence();
          issue_qk32(S, Q, kd);
          wg_commit();
          if (pending) {
            epilogue_part<ESPLIT, 12>(O, inv0, inv1, lane_addr);
            epilogue_done(my_ostg, lane);
          }
          wg_fence();
          issue_pv<false>(O, P0, vd);
          wg_commit();
          turn_pass();
          advance();
          exit_n = ((tails & 2) || n + 8 == nblocks) ? n + 6 : -1;
          tails >>= 1;
          asm volatile("" : "+r"(exit_n), "+r"(tails));
          wg_wait<1>();
          fence_regs(S);
          pending = true;
        }
        release(kp);
        if (j == 6) load_q<8, 12>(Q, lane_addr);
        softmax_block(S, P1, l0, l1);
        sums_put(sum_addr, l0, l1, j == 6);
        wg_wait<0>();
        release(vp);
        turn_wait();
        if (n == exit_n) {
          wg_fence();
          issue_pv<true>(O, P1, vd);
          wg_commit();
          break;
        }
        wg_fence();
        issue_qk(S, Q, kd);
        wg_commit();
        issue_pv<true>(O, P1, vd);
        wg_commit();
        turn_pass();
        advance();
        if (j == 6) finish_sums();
        wg_wait<1>();
        fence_regs(S);
        fence_regs(P0);
        release(kp);
        n += 2;
      }
      if (n + 2 == nblocks) {
        if (w == 0) turn_pass();
        finish_sums();
        wg_wait<0>();
        fence_regs(O);
        release(vs);
        epilogue_part<0, 12>(O, inv0, inv1, lane_addr);
        epilogue_done(my_ostg, lane);
        break;
      }
      const int t = n >> 3;
      const uint32_t qt = sbase + OFF_QT, pt = sbase + OFF_PT, red = sbase + OFF_RED;
      const uint32_t tl = ((lane & 7) + (lane >> 4) * 8) * 128 + (((warp * 2 + ((lane >> 3) & 1)) ^ (lane & 7)) << 4);
      const bool tlast = n + 10 == nblocks;
      float lt[4] = {0.f, 0.f, 0.f, 0.f};
      float ST[8], OT[3][8];
      wg_fence();
      issue_qkT(ST, kd, qt);
      wg_commit();
      turn_pass();
      finish_sums();
      wg_wait<0>();
      fence_regs(ST);
      fence_regs(O);
      release(ks);
      release(vs);
      advance();
      epilogue_part<0, NT_SPLIT>(O, inv0, inv1, lane_addr);
      if (NT_SPLIT == 12) epilogue_done(my_ostg, lane);
      tail_softmax(ST, lt, pt + tl);
      auto tail_step = [&](auto first_c, int jj) {
        constexpr bool FIRST = decltype(first_c)::value;
        asm volatile("fence.proxy.async.shared::cta;" ::: "memory");
        turn_wait();
        wg_fence();
        issue_qkT(ST, kd, qt);
        wg_commit();
        issue_pvT<!FIRST>(OT, vd, pt + (jj & 1) * 2048);
        wg_commit();
        turn_pass();
        advance();
        wg_wait<1>();
        fence_regs(ST);
        release(kp);
        tail_softmax(ST, lt, pt + (~jj & 1) * 2048 + tl);
        wg_wait<0>();
        fence_regs(OT[0]); fence_regs(OT[1]); fence_regs(OT[2]);
        release(vp);
      };
      tail_step(Bool<true>(), 0);
      if (NT_SPLIT < 12) {
        epilogue_part<NT_SPLIT, 12>(O, inv0, inv1, lane_addr);
        epilogue_done(my_ostg, lane);
      }
#pragma unroll 1
      for (int jj = 1; jj < 7; jj++) tail_step(Bool<false>(), jj);
      mbar_wait(my_qfull, t & 1);
      load_q(Q, lane_addr);
      tail_reduce(lt, red, warp, lane);
      if (!(sum_ok(lt[0]) && sum_ok(lt[1]) && sum_ok(lt[2]) && sum_ok(lt[3]))) redo |= 1u << ((t + 1) & 31);
#pragma unroll
      for (int i = 0; i < 4; i++) lt[i] = rcp(lt[i]);
      asm volatile("fence.proxy.async.shared::cta;" ::: "memory");
      turn_wait();
      wg_fence();
      issue_pvT<true>(OT, vd, pt + 2048);
      wg_commit();
      issue_qk(S, Q, kd);
      wg_commit();
      if (!tlast) turn_pass();
      wg_wait<1>();
      fence_regs(OT[0]); fence_regs(OT[1]); fence_regs(OT[2]);
      release(vs);
#pragma unroll
      for (int b = 0; b < 3; b++)
        stsm_x4_trans(s_qo + SLOT + b * SLAB + tl + (lane >> 4) * (RGRP - 1024),
                      pack_bf16(OT[b][0] * lt[0], OT[b][1] * lt[1]), pack_bf16(OT[b][2] * lt[0], OT[b][3] * lt[1]),
                      pack_bf16(OT[b][4] * lt[2], OT[b][5] * lt[3]), pack_bf16(OT[b][6] * lt[2], OT[b][7] * lt[3]));
      epilogue_done(my_ostg, lane);
      wg_wait<0>();
      fence_regs(S);
      if (tlast) break;
      release(ks);
      advance();
#pragma unroll
      for (int i = 0; i < 96; i++) O[i] = 0.f;
      pending = false;
      n += 10;
      tails >>= 1;
    }
    if (redo) asm volatile("red.shared.or.b32 [%0], %1;" ::"r"(s_redo + 4 * w), "r"(redo) : "memory");
    asm volatile("bar.sync 4, 256;" ::: "memory");
    asm volatile("ld.shared.u32 %0, [%1];" : "=r"(redo) : "r"(s_redo + 4 * w) : "memory");
    redo = __shfl_sync(0xffffffffu, redo, 0);
    if (redo) {
      mbar_wait_sleep(bar_redo + 8 * w, 0);
      asm volatile("bar.sync %0, 128;" ::"r"(5 + w) : "memory");
      uint32_t phase = 1;
      get_rounds(first_round, nrounds);
#pragma unroll 1
      for (int t = 0; t < nrounds; t++) {
        if (!(redo >> (t & 31) & 1)) continue;
        const Round r = decode_round(sched.list[first_round + t] & 0x7ff, rank);
        redo_tile(&tmQ, &tmK, &tmV, &tmO, r.head, r.qrow + w * 64, s_qo + w * SLOT, s_kv + 2 * w * SLOT, lane_addr, bar_redo + 8 * w, phase, 5 + w);
      }
    }
  }
}

typedef CUresult (*EncodeFn)(CUtensorMap*, CUtensorMapDataType, cuuint32_t, void*, const cuuint64_t*, const cuuint64_t*,
                             const cuuint32_t*, const cuuint32_t*, CUtensorMapInterleave, CUtensorMapSwizzle,
                             CUtensorMapL2promotion, CUtensorMapFloatOOBfill);

void make_map(EncodeFn fn, CUtensorMap* tm, const void* ptr, int rows, int box_rows) {
  cuuint64_t dims[5] = {64, 8, 3, (cuuint64_t)rows / 8, (cuuint64_t)NHEADS};
  cuuint64_t strides[4] = {HD * 2, 128, 8 * HD * 2, (cuuint64_t)rows * HD * 2};
  cuuint32_t box[5] = {64, 8, 3, (cuuint32_t)box_rows / 8, 1};
  cuuint32_t estr[5] = {1, 1, 1, 1, 1};
  fn(tm, CU_TENSOR_MAP_DATA_TYPE_BFLOAT16, 5, const_cast<void*>(ptr), dims, strides, box, estr,
     CU_TENSOR_MAP_INTERLEAVE_NONE, CU_TENSOR_MAP_SWIZZLE_128B, CU_TENSOR_MAP_L2_PROMOTION_L2_128B, CU_TENSOR_MAP_FLOAT_OOB_FILL_NONE);
}

#define COST_N 12690
#define COST_T 10800
#define COST_TN 12720
#define TAIL_LATE 36
#define TAIL_MAX 60
#define HEAVY_STEP 3
static_assert(MAX_CLUSTERS / 3 * STAGGER < COST_T, "the first wave has to be handed out in the order of the clusters");
void make_schedule(Schedule& s, int nclusters) {
  static uint16_t lists[MAX_CLUSTERS][NROUNDS];
  int cnt[MAX_CLUSTERS] = {0}, len[MAX_CLUSTERS], ntail[MAX_CLUSTERS] = {0}, quota[MAX_CLUSTERS] = {0};
  long long busy[MAX_CLUSTERS], fin[MAX_CLUSTERS];
  const int ntails = NROUNDS / 7, base = NROUNDS / nclusters, nheavy = NROUNDS % nclusters;
  const int step = nheavy * HEAVY_STEP <= nclusters ? HEAVY_STEP : 1;
  for (int c = 0; c < nclusters; c++) {
    len[c] = base + (c % step == 0 && c / step < nheavy);
    busy[c] = c / 3 * STAGGER;
    fin[c] = busy[c] + (long long)len[c] * COST_N;
  }
  for (int k = 0; k < ntails; k++) {
    int c = -1;
    for (int i = 0; i < nclusters; i++)
      if (quota[i] < len[i] / 2 && (c < 0 || fin[i] > fin[c])) c = i;
    quota[c]++;
    fin[c] -= 2 * COST_N - COST_T - COST_TN;
  }
  int gn = 0, gt = 3;
  for (int k = 0; k < NROUNDS; k++) {
    int c = -1;
    for (int i = 0; i < nclusters; i++)
      if (cnt[i] < len[i] && (c < 0 || busy[i] < busy[c])) c = i;
    const bool after_tail = cnt[c] > 0 && (lists[c][cnt[c] - 1] & 0x8000);
    const bool may_t = cnt[c] > 0 && !after_tail;
    const int left = len[c] - cnt[c], q = quota[c] - ntail[c];
    const bool due = (long long)(gt / 7) * quota[c] * 8 >= (long long)(ntail[c] * 8 + (c * 5 & 7)) * ntails;
    bool tail = may_t && q > 0 && (2 * q > left || (gn - gt >= TAIL_LATE && due) || gn - gt >= TAIL_MAX);
    if (4 * quota[c] >= len[c]) {
      const int m = len[c] - 1, phase = c / step * 11 % m;
      tail = may_t && q > 0 && (2 * q > left || (cnt[c] * quota[c] + phase) / m > ntail[c]);
    }
    if (gt >= NROUNDS) tail = false;
    if (gn >= NROUNDS) tail = true;
    const int g = tail ? gt : gn;
    if (tail) { gt += 7; ntail[c]++; }
    else { gn++; if (gn % 7 == 3) gn++; }
    const bool form_t = tail && may_t;
    lists[c][cnt[c]++] = (uint16_t)(g | (form_t ? 0x8000 : 0));
    busy[c] += form_t ? COST_T : after_tail ? COST_TN : COST_N;
  }
  bool use_tail = true;
  for (int c = 0; c < nclusters; c++) if (cnt[c] > MAX_ROUNDS) use_tail = false;
  if (!use_tail) for (int c = 0; c < nclusters; c++) for (int i = 0; i < cnt[c]; i++) lists[c][i] &= 0x7fff;
  int pos = 0;
  for (int c = 0; c < nclusters; c++) {
    s.start[c] = (uint16_t)pos;
    s.tails[c] = 0;
    for (int i = 0; i < cnt[c]; i++) {
      if (lists[c][i] & 0x8000) s.tails[c] |= 1u << i;
      s.list[pos++] = lists[c][i];
    }
  }
  for (int c = nclusters; c <= MAX_CLUSTERS; c++) s.start[c] = (uint16_t)pos;
  s.list[NROUNDS] = 0;
}

}

extern "C" void kernel_launch(void* const* d_in, const int* in_sizes, int n_in, void* d_out, int out_size) {
  static EncodeFn encode = nullptr;
  static int nclusters = 0;
  static Schedule sched;
  if (!encode) {
    void* fn = nullptr;
    cudaDriverEntryPointQueryResult qr;
    cudaGetDriverEntryPoint("cuTensorMapEncodeTiled", &fn, cudaEnableDefault, &qr);
    encode = (EncodeFn)fn;
    int dev = 0, nsm = 0;
    cudaGetDevice(&dev);
    cudaDeviceGetAttribute(&nsm, cudaDevAttrMultiProcessorCount, dev);
    nclusters = nsm / 2 < MAX_CLUSTERS ? nsm / 2 : MAX_CLUSTERS;
    make_schedule(sched, nclusters);
    cudaFuncSetAttribute(attn_kernel, cudaFuncAttributeMaxDynamicSharedMemorySize, SMEM_BYTES);
  }
  CUtensorMap tmQ, tmQT, tmK, tmV, tmO;
  make_map(encode, &tmQ, d_in[0], SQ, 64);
  make_map(encode, &tmQT, d_in[0], SQ, 16);
  make_map(encode, &tmK, d_in[1], SK, 64);
  make_map(encode, &tmV, d_in[2], SK, 64);
  make_map(encode, &tmO, d_out, SQ, OROWS);
  attn_kernel<<<2 * nclusters, NTHREADS, SMEM_BYTES>>>(tmQ, tmQT, tmK, tmV, tmO, sched);
}
```

```cpp
#include <cuda_runtime.h>
#include <cuda_bf16.h>
#include <cuda.h>
#include <stdint.h>

namespace {

constexpr int NHEADS = 512;
constexpr int SQ = 848;
constexpr int SK = 512;
constexpr int HD = 192;
constexpr int BN = 64;
constexpr int NBLK = SK / BN;
constexpr int SLOT = 64 * HD * 2;
constexpr int SLAB = 1024;
constexpr int RGRP = 3 * SLAB;
constexpr int NSLOT = 7;
constexpr int NROUNDS = (NHEADS / 2) * 7;
constexpr int NTHREADS = 384;
constexpr int OFF_QO = 0;
constexpr int OFF_KV = 2 * SLOT;
constexpr int OFF_QT = (2 + NSLOT) * SLOT;
constexpr int OFF_PT = OFF_QT + 3 * 2048;
constexpr int OFF_RED = OFF_PT + 2 * 2048;
constexpr int OFF_BAR = OFF_RED + 256;
constexpr int SMEM_BYTES = OFF_BAR + 256;

#define ESPLIT 8
#define OROWS 16
#define STAGGER 250
#define PRESCALE 1
#define NT_SPLIT 4
#define QREQT 1
#define QREQ0 4
#define QREQ1 4
constexpr uint32_t WAIT_LIMIT = 1u << 18;
#define SUSPEND 20000
constexpr uint32_t SUSPEND_NS = SUSPEND;

constexpr float SCALE_LOG2 = 0.07216878364870322f * 1.4426950408889634f;
__device__ __forceinline__ void check_inv(float a, float b, uint32_t& mask, uint32_t bit) {
  asm("{\n.reg .pred p;\nsetp.ge.f32 p, %1, 0f21800000;\nsetp.le.and.f32 p, %1, 0f4E800000, p;\n"
      "setp.ge.and.f32 p, %2, 0f21800000, p;\nsetp.le.and.f32 p, %2, 0f4E800000, p;\n@!p or.b32 %0, %0, %3;\n}\n"
      : "+r"(mask) : "f"(a), "f"(b), "r"(bit));
}

__device__ __forceinline__ uint32_t smem_u32(const void* p) { return (uint32_t)__cvta_generic_to_shared(p); }
__device__ __forceinline__ void wg_fence() { asm volatile("wgmma.fence.sync.aligned;" ::: "memory"); }
__device__ __forceinline__ void wg_commit() { asm volatile("wgmma.commit_group.sync.aligned;" ::: "memory"); }
template <int N> __device__ __forceinline__ void wg_wait() { asm volatile("wgmma.wait_group.sync.aligned %0;" ::"n"(N) : "memory"); }
template <int N> __device__ __forceinline__ void fence_regs(float (&r)[N]) {
#pragma unroll
  for (int i = 0; i < N; i++) asm volatile("" : "+f"(r[i])::"memory");
}
template <int N> __device__ __forceinline__ void fence_regs(uint32_t (&r)[N]) {
#pragma unroll
  for (int i = 0; i < N; i++) asm volatile("" : "+r"(r[i])::"memory");
}

__device__ __forceinline__ void mbar_init(uint32_t bar, uint32_t cnt) {
  asm volatile("mbarrier.init.shared::cta.b64 [%0], %1;" ::"r"(bar), "r"(cnt));
}
__device__ __forceinline__ void mbar_expect_tx(uint32_t bar, uint32_t bytes) {
  asm volatile("mbarrier.arrive.expect_tx.shared::cta.b64 _, [%0], %1;" ::"r"(bar), "r"(bytes) : "memory");
}
__device__ __forceinline__ void mbar_arrive(uint32_t bar) {
  asm volatile("mbarrier.arrive.shared::cta.b64 _, [%0];" ::"r"(bar) : "memory");
}
__device__ __forceinline__ bool mbar_try(uint32_t bar, uint32_t parity) {
  uint32_t ok;
  asm volatile(
      "{\n.reg .pred p;\nmbarrier.try_wait.parity.shared::cta.b64 p, [%1], %2;\nselp.b32 %0, 1, 0, p;\n}\n"
      : "=r"(ok)
      : "r"(bar), "r"(parity)
      : "memory");
  return ok;
}
__device__ __forceinline__ bool mbar_try_sleep(uint32_t bar, uint32_t parity) {
  uint32_t ok;
  asm volatile(
      "{\n.reg .pred p;\nmbarrier.try_wait.parity.shared::cta.b64 p, [%1], %2, %3;\nselp.b32 %0, 1, 0, p;\n}\n"
      : "=r"(ok)
      : "r"(bar), "r"(parity), "r"(SUSPEND_NS)
      : "memory");
  return ok;
}
__device__ __forceinline__ void mbar_wait(uint32_t bar, uint32_t parity) {
  if (mbar_try(bar, parity)) return;
  for (uint32_t n = 0; n < WAIT_LIMIT; n++)
    if (mbar_try(bar, parity)) break;
}
__device__ __forceinline__ void mbar_wait_sleep(uint32_t bar, uint32_t parity) {
  for (uint32_t n = 0; n < WAIT_LIMIT; n++) {
    if (mbar_try_sleep(bar, parity)) break;
  }
}

__device__ __forceinline__ void tma_load(uint32_t dst, const CUtensorMap* tm, uint32_t bar, int row, int head, uint64_t pol) {
  asm volatile(
      "cp.async.bulk.tensor.5d.shared::cluster.global.mbarrier::complete_tx::bytes.L2::cache_hint"
      " [%0], [%1, {%3, %3, %3, %4, %5}], [%2], %6;" ::"r"(dst),
      "l"(tm), "r"(bar), "r"(0), "r"(row >> 3), "r"(head), "l"(pol)
      : "memory");
}
__device__ __forceinline__ void tma_load_mc(uint32_t dst, const CUtensorMap* tm, uint32_t bar, int row, int head, uint64_t pol) {
  asm volatile(
      "cp.async.bulk.tensor.5d.shared::cluster.global.mbarrier::complete_tx::bytes.multicast::cluster.L2::cache_hint"
      " [%0], [%1, {%3, %3, %3, %4, %5}], [%2], %7, %6;" ::"r"(dst),
      "l"(tm), "r"(bar), "r"(0), "r"(row >> 3), "r"(head), "l"(pol), "h"((uint16_t)3)
      : "memory");
}
__device__ __forceinline__ void tma_store(const CUtensorMap* tm, uint32_t src, int row, int head, uint64_t pol) {
  asm volatile(
      "cp.async.bulk.tensor.5d.global.shared::cta.bulk_group.L2::cache_hint"
      " [%0, {%2, %2, %2, %3, %4}], [%1], %5;" ::"l"(tm),
      "r"(src), "r"(0), "r"(row >> 3), "r"(head), "l"(pol)
      : "memory");
}
__device__ __forceinline__ void ldsm_x4(uint32_t addr, uint32_t& r0, uint32_t& r1, uint32_t& r2, uint32_t& r3) {
  asm volatile("ldmatrix.sync.aligned.m8n8.x4.shared.b16 {%0, %1, %2, %3}, [%4];"
               : "=r"(r0), "=r"(r1), "=r"(r2), "=r"(r3)
               : "r"(addr)
               : "memory");
}
__device__ __forceinline__ void stsm_x4(uint32_t addr, uint32_t r0, uint32_t r1, uint32_t r2, uint32_t r3) {
  asm volatile("stmatrix.sync.aligned.m8n8.x4.shared.b16 [%0], {%1, %2, %3, %4};" ::"r"(addr), "r"(r0), "r"(r1), "r"(r2), "r"(r3)
               : "memory");
}
__device__ __forceinline__ void stsm_x4_trans(uint32_t addr, uint32_t r0, uint32_t r1, uint32_t r2, uint32_t r3) {
  asm volatile("stmatrix.sync.aligned.m8n8.x4.trans.shared.b16 [%0], {%1, %2, %3, %4};" ::"r"(addr), "r"(r0), "r"(r1), "r"(r2), "r"(r3)
               : "memory");
}
__device__ __forceinline__ float ex2(float x) {
  float y;
  asm("ex2.approx.ftz.f32 %0, %1;" : "=f"(y) : "f"(x));
  return y;
}
__device__ __forceinline__ float rcp(float x) {
  float y;
  asm("rcp.approx.ftz.f32 %0, %1;" : "=f"(y) : "f"(x));
  return y;
}
__device__ __forceinline__ uint32_t pack_bf16(float lo, float hi) {
  uint32_t r;
  asm("cvt.rn.bf16x2.f32 %0, %1, %2;" : "=r"(r) : "f"(hi), "f"(lo));
  return r;
}
__device__ __forceinline__ void wgmma_qk(float (&d)[32], uint32_t a0, uint32_t a1, uint32_t a2, uint32_t a3, uint64_t db, int scale_d) {
  asm volatile("{\n.reg .pred p;\nsetp.ne.b32 p, %37, 0;\n"
    "wgmma.mma_async.sync.aligned.m64n64k16.f32.bf16.bf16 "
    "{%0, %1, %2, %3, %4, %5, %6, %7, %8, %9, %10, %11, %12, %13, %14, %15, %16, %17, %18, %19, %20, %21, %22, %23, %24, %25, %26, %27, %28, %29, %30, %31}, "
    "{%32, %33, %34, %35}, %36, p, 1, 1, 0;\n}\n"
    : "+f"(d[0]), "+f"(d[1]), "+f"(d[2]), "+f"(d[3]), "+f"(d[4]), "+f"(d[5]), "+f"(d[6]), "+f"(d[7]), "+f"(d[8]), "+f"(d[9]), "+f"(d[10]), "+f"(d[11]), "+f"(d[12]), "+f"(d[13]), "+f"(d[14]), "+f"(d[15]), "+f"(d[16]), "+f"(d[17]), "+f"(d[18]), "+f"(d[19]), "+f"(d[20]), "+f"(d[21]), "+f"(d[22]), "+f"(d[23]), "+f"(d[24]), "+f"(d[25]), "+f"(d[26]), "+f"(d[27]), "+f"(d[28]), "+f"(d[29]), "+f"(d[30]), "+f"(d[31])
    : "r"(a0), "r"(a1), "r"(a2), "r"(a3), "l"(db), "r"(scale_d));
}

__device__ __forceinline__ void wgmma_pv(float (&d)[96], uint32_t a0, uint32_t a1, uint32_t a2, uint32_t a3, uint64_t db, int scale_d) {
  asm volatile("{\n.reg .pred p;\nsetp.ne.b32 p, %101, 0;\n"
    "wgmma.mma_async.sync.aligned.m64n192k16.f32.bf16.bf16 "
    "{%0, %1, %2, %3, %4, %5, %6, %7, %8, %9, %10, %11, %12, %13, %14, %15, %16, %17, %18, %19, %20, %21, %22, %23, %24, %25, %26, %27, %28, %29, %30, %31, %32, %33, %34, %35, %36, %37, %38, %39, %40, %41, %42, %43, %44, %45, %46, %47, %48, %49, %50, %51, %52, %53, %54, %55, %56, %57, %58, %59, %60, %61, %62, %63, %64, %65, %66, %67, %68, %69, %70, %71, %72, %73, %74, %75, %76, %77, %78, %79, %80, %81, %82, %83, %84, %85, %86, %87, %88, %89, %90, %91, %92, %93, %94, %95}, "
    "{%96, %97, %98, %99}, %100, p, 1, 1, 1;\n}\n"
    : "+f"(d[0]), "+f"(d[1]), "+f"(d[2]), "+f"(d[3]), "+f"(d[4]), "+f"(d[5]), "+f"(d[6]), "+f"(d[7]), "+f"(d[8]), "+f"(d[9]), "+f"(d[10]), "+f"(d[11]), "+f"(d[12]), "+f"(d[13]), "+f"(d[14]), "+f"(d[15]), "+f"(d[16]), "+f"(d[17]), "+f"(d[18]), "+f"(d[19]), "+f"(d[20]), "+f"(d[21]), "+f"(d[22]), "+f"(d[23]), "+f"(d[24]), "+f"(d[25]), "+f"(d[26]), "+f"(d[27]), "+f"(d[28]), "+f"(d[29]), "+f"(d[30]), "+f"(d[31]), "+f"(d[32]), "+f"(d[33]), "+f"(d[34]), "+f"(d[35]), "+f"(d[36]), "+f"(d[37]), "+f"(d[38]), "+f"(d[39]), "+f"(d[40]), "+f"(d[41]), "+f"(d[42]), "+f"(d[43]), "+f"(d[44]), "+f"(d[45]), "+f"(d[46]), "+f"(d[47]), "+f"(d[48]), "+f"(d[49]), "+f"(d[50]), "+f"(d[51]), "+f"(d[52]), "+f"(d[53]), "+f"(d[54]), "+f"(d[55]), "+f"(d[56]), "+f"(d[57]), "+f"(d[58]), "+f"(d[59]), "+f"(d[60]), "+f"(d[61]), "+f"(d[62]), "+f"(d[63]), "+f"(d[64]), "+f"(d[65]), "+f"(d[66]), "+f"(d[67]), "+f"(d[68]), "+f"(d[69]), "+f"(d[70]), "+f"(d[71]), "+f"(d[72]), "+f"(d[73]), "+f"(d[74]), "+f"(d[75]), "+f"(d[76]), "+f"(d[77]), "+f"(d[78]), "+f"(d[79]), "+f"(d[80]), "+f"(d[81]), "+f"(d[82]), "+f"(d[83]), "+f"(d[84]), "+f"(d[85]), "+f"(d[86]), "+f"(d[87]), "+f"(d[88]), "+f"(d[89]), "+f"(d[90]), "+f"(d[91]), "+f"(d[92]), "+f"(d[93]), "+f"(d[94]), "+f"(d[95])
    : "r"(a0), "r"(a1), "r"(a2), "r"(a3), "l"(db), "r"(scale_d));
}

__device__ __forceinline__ void wgmma_qkT(float (&d)[8], uint64_t da, uint64_t db, int scale_d) {
  asm volatile("{\n.reg .pred p;\nsetp.ne.b32 p, %10, 0;\n"
    "wgmma.mma_async.sync.aligned.m64n16k16.f32.bf16.bf16 "
    "{%0, %1, %2, %3, %4, %5, %6, %7}, "
    "%8, %9, p, 1, 1, 0, 0;\n}\n"
    : "+f"(d[0]), "+f"(d[1]), "+f"(d[2]), "+f"(d[3]), "+f"(d[4]), "+f"(d[5]), "+f"(d[6]), "+f"(d[7])
    : "l"(da), "l"(db), "r"(scale_d));
}
__device__ __forceinline__ void wgmma_pvT(float (&d)[8], uint64_t da, uint64_t db, int scale_d) {
  asm volatile("{\n.reg .pred p;\nsetp.ne.b32 p, %10, 0;\n"
    "wgmma.mma_async.sync.aligned.m64n16k16.f32.bf16.bf16 "
    "{%0, %1, %2, %3, %4, %5, %6, %7}, "
    "%8, %9, p, 1, 1, 1, 0;\n}\n"
    : "+f"(d[0]), "+f"(d[1]), "+f"(d[2]), "+f"(d[3]), "+f"(d[4]), "+f"(d[5]), "+f"(d[6]), "+f"(d[7])
    : "l"(da), "l"(db), "r"(scale_d));
}

__device__ __forceinline__ void wgmma_qk0(float (&d)[32], uint32_t a0, uint32_t a1, uint32_t a2, uint32_t a3, uint64_t db) {
  asm volatile("{\n.reg .pred p;\nsetp.ne.b32 p, 0, 0;\n"
    "wgmma.mma_async.sync.aligned.m64n64k16.f32.bf16.bf16 "
    "{%0, %1, %2, %3, %4, %5, %6, %7, %8, %9, %10, %11, %12, %13, %14, %15, %16, %17, %18, %19, %20, %21, %22, %23, %24, %25, %26, %27, %28, %29, %30, %31}, "
    "{%32, %33, %34, %35}, %36, p, 1, 1, 0;\n}\n"
    : "=f"(d[0]), "=f"(d[1]), "=f"(d[2]), "=f"(d[3]), "=f"(d[4]), "=f"(d[5]), "=f"(d[6]), "=f"(d[7]), "=f"(d[8]), "=f"(d[9]), "=f"(d[10]), "=f"(d[11]), "=f"(d[12]), "=f"(d[13]), "=f"(d[14]), "=f"(d[15]), "=f"(d[16]), "=f"(d[17]), "=f"(d[18]), "=f"(d[19]), "=f"(d[20]), "=f"(d[21]), "=f"(d[22]), "=f"(d[23]), "=f"(d[24]), "=f"(d[25]), "=f"(d[26]), "=f"(d[27]), "=f"(d[28]), "=f"(d[29]), "=f"(d[30]), "=f"(d[31])
    : "r"(a0), "r"(a1), "r"(a2), "r"(a3), "l"(db));
}
__device__ __forceinline__ void wgmma_pv0(float (&d)[96], uint32_t a0, uint32_t a1, uint32_t a2, uint32_t a3, uint64_t db) {
  asm volatile("{\n.reg .pred p;\nsetp.ne.b32 p, 0, 0;\n"
    "wgmma.mma_async.sync.aligned.m64n192k16.f32.bf16.bf16 "
    "{%0, %1, %2, %3, %4, %5, %6, %7, %8, %9, %10, %11, %12, %13, %14, %15, %16, %17, %18, %19, %20, %21, %22, %23, %24, %25, %26, %27, %28, %29, %30, %31, %32, %33, %34, %35, %36, %37, %38, %39, %40, %41, %42, %43, %44, %45, %46, %47, %48, %49, %50, %51, %52, %53, %54, %55, %56, %57, %58, %59, %60, %61, %62, %63, %64, %65, %66, %67, %68, %69, %70, %71, %72, %73, %74, %75, %76, %77, %78, %79, %80, %81, %82, %83, %84, %85, %86, %87, %88, %89, %90, %91, %92, %93, %94, %95}, "
    "{%96, %97, %98, %99}, %100, p, 1, 1, 1;\n}\n"
    : "=f"(d[0]), "=f"(d[1]), "=f"(d[2]), "=f"(d[3]), "=f"(d[4]), "=f"(d[5]), "=f"(d[6]), "=f"(d[7]), "=f"(d[8]), "=f"(d[9]), "=f"(d[10]), "=f"(d[11]), "=f"(d[12]), "=f"(d[13]), "=f"(d[14]), "=f"(d[15]), "=f"(d[16]), "=f"(d[17]), "=f"(d[18]), "=f"(d[19]), "=f"(d[20]), "=f"(d[21]), "=f"(d[22]), "=f"(d[23]), "=f"(d[24]), "=f"(d[25]), "=f"(d[26]), "=f"(d[27]), "=f"(d[28]), "=f"(d[29]), "=f"(d[30]), "=f"(d[31]), "=f"(d[32]), "=f"(d[33]), "=f"(d[34]), "=f"(d[35]), "=f"(d[36]), "=f"(d[37]), "=f"(d[38]), "=f"(d[39]), "=f"(d[40]), "=f"(d[41]), "=f"(d[42]), "=f"(d[43]), "=f"(d[44]), "=f"(d[45]), "=f"(d[46]), "=f"(d[47]), "=f"(d[48]), "=f"(d[49]), "=f"(d[50]), "=f"(d[51]), "=f"(d[52]), "=f"(d[53]), "=f"(d[54]), "=f"(d[55]), "=f"(d[56]), "=f"(d[57]), "=f"(d[58]), "=f"(d[59]), "=f"(d[60]), "=f"(d[61]), "=f"(d[62]), "=f"(d[63]), "=f"(d[64]), "=f"(d[65]), "=f"(d[66]), "=f"(d[67]), "=f"(d[68]), "=f"(d[69]), "=f"(d[70]), "=f"(d[71]), "=f"(d[72]), "=f"(d[73]), "=f"(d[74]), "=f"(d[75]), "=f"(d[76]), "=f"(d[77]), "=f"(d[78]), "=f"(d[79]), "=f"(d[80]), "=f"(d[81]), "=f"(d[82]), "=f"(d[83]), "=f"(d[84]), "=f"(d[85]), "=f"(d[86]), "=f"(d[87]), "=f"(d[88]), "=f"(d[89]), "=f"(d[90]), "=f"(d[91]), "=f"(d[92]), "=f"(d[93]), "=f"(d[94]), "=f"(d[95])
    : "r"(a0), "r"(a1), "r"(a2), "r"(a3), "l"(db));
}
__device__ __forceinline__ void wgmma_qkT0(float (&d)[8], uint64_t da, uint64_t db) {
  asm volatile("{\n.reg .pred p;\nsetp.ne.b32 p, 0, 0;\n"
    "wgmma.mma_async.sync.aligned.m64n16k16.f32.bf16.bf16 "
    "{%0, %1, %2, %3, %4, %5, %6, %7}, "
    "%8, %9, p, 1, 1, 0, 0;\n}\n"
    : "=f"(d[0]), "=f"(d[1]), "=f"(d[2]), "=f"(d[3]), "=f"(d[4]), "=f"(d[5]), "=f"(d[6]), "=f"(d[7])
    : "l"(da), "l"(db));
}
__device__ __forceinline__ void wgmma_pvT0(float (&d)[8], uint64_t da, uint64_t db) {
  asm volatile("{\n.reg .pred p;\nsetp.ne.b32 p, 0, 0;\n"
    "wgmma.mma_async.sync.aligned.m64n16k16.f32.bf16.bf16 "
    "{%0, %1, %2, %3, %4, %5, %6, %7}, "
    "%8, %9, p, 1, 1, 1, 0;\n}\n"
    : "=f"(d[0]), "=f"(d[1]), "=f"(d[2]), "=f"(d[3]), "=f"(d[4]), "=f"(d[5]), "=f"(d[6]), "=f"(d[7])
    : "l"(da), "l"(db));
}

struct Round { int head, qrow, mc; };
__device__ __forceinline__ Round decode_round(int g, int rank) {
  int p = g / 7, r = g - p * 7;
  Round o;
  if (r < 3) { o.head = 2 * p; o.qrow = r * 256 + rank * 128; o.mc = 1; }
  else if (r == 3) { o.head = 2 * p + rank; o.qrow = 768; o.mc = 0; }
  else { o.head = 2 * p + 1; o.qrow = (r - 4) * 256 + rank * 128; o.mc = 1; }
  return o;
}

__device__ __forceinline__ uint32_t kdesc0(uint32_t s_kv) { return ((s_kv & 0x3FFFFu) >> 4) | (1u << 16); }
__device__ __forceinline__ uint32_t vdesc0(uint32_t s_kv) { return ((s_kv & 0x3FFFFu) >> 4) | ((uint32_t)(SLAB >> 4) << 16); }
constexpr uint64_t DESC_HI = ((uint64_t)(RGRP >> 4) << 32) | ((uint64_t)1 << 62);
constexpr uint64_t DESC_HI_PT = ((uint64_t)(1024 >> 4) << 32) | ((uint64_t)1 << 62);

__device__ __forceinline__ void issue_qk(float (&S)[32], const uint32_t (&Q)[48], uint32_t kdesc) {
  const uint64_t d = DESC_HI | kdesc;
  wgmma_qk0(S, Q[0], Q[1], Q[2], Q[3], d);
#pragma unroll
  for (int kk = 1; kk < 12; kk++)
    wgmma_qk(S, Q[kk * 4], Q[kk * 4 + 1], Q[kk * 4 + 2], Q[kk * 4 + 3], d + (uint64_t)((kk / 4) * (SLAB / 16) + (kk % 4) * 2), 1);
}
__device__ __forceinline__ void issue_qk32(float (&S)[32], const uint32_t (&Q)[48], uint32_t kdesc) {
  uint32_t d[12];
#pragma unroll
  for (int kk = 0; kk < 12; kk++) {
    d[kk] = kdesc + ((kk / 4) * (SLAB / 16) + (kk % 4) * 2);
    asm volatile("" : "+r"(d[kk]));
  }
  wgmma_qk0(S, Q[0], Q[1], Q[2], Q[3], DESC_HI | d[0]);
#pragma unroll
  for (int kk = 1; kk < 12; kk++) wgmma_qk(S, Q[kk * 4], Q[kk * 4 + 1], Q[kk * 4 + 2], Q[kk * 4 + 3], DESC_HI | d[kk], 1);
}
__device__ __forceinline__ void issue_qk3(float (&S)[32], const uint32_t (&Q)[48], uint32_t kdesc) {
  const uint64_t d = DESC_HI | kdesc;
  wgmma_qk0(S, Q[0], Q[1], Q[2], Q[3], d);
#pragma unroll
  for (int kk = 1; kk < 12; kk++) {
    if (kk % 4 == 0) wg_commit();
    wgmma_qk(S, Q[kk * 4], Q[kk * 4 + 1], Q[kk * 4 + 2], Q[kk * 4 + 3], d + (uint64_t)((kk / 4) * (SLAB / 16) + (kk % 4) * 2), 1);
  }
}
template <bool ACCUMULATE>
__device__ __forceinline__ void issue_pv(float (&O)[96], const uint32_t (&P)[16], uint32_t vdesc) {
  const uint64_t d = DESC_HI | vdesc;
  if (ACCUMULATE) wgmma_pv(O, P[0], P[1], P[2], P[3], d, 1);
  else wgmma_pv0(O, P[0], P[1], P[2], P[3], d);
#pragma unroll
  for (int kk = 1; kk < 4; kk++)
    wgmma_pv(O, P[kk * 4], P[kk * 4 + 1], P[kk * 4 + 2], P[kk * 4 + 3], d + (uint64_t)(kk * (2 * RGRP / 16)), 1);
}

template <int K0 = 0, int K1 = 12>
__device__ __forceinline__ void load_q(uint32_t (&Q)[48], uint32_t lane_addr) {
#pragma unroll
  for (int kk = K0; kk < K1; kk++)
    ldsm_x4((lane_addr ^ ((kk % 4) << 5)) + (kk / 4) * SLAB, Q[kk * 4], Q[kk * 4 + 1], Q[kk * 4 + 2], Q[kk * 4 + 3]);
}

__device__ __forceinline__ void scale_q(uint32_t (&Q)[48]) {
#pragma unroll
  for (int i = 0; i < 48; i++) {
    asm("mul.rn.bf16x2 %0, %1, %2;" : "=r"(Q[i]) : "r"(Q[i]), "r"(0x3DD53DD5u));
  }
  fence_regs(Q);
}
__device__ __forceinline__ void softmax_block(const float (&S)[32], uint32_t (&P)[16], float& l0, float& l1) {
#pragma unroll
  for (int i = 0; i < 8; i++) {
    const float a = ex2(S[4 * i + 0]);
    const float b = ex2(S[4 * i + 1]);
    const float c = ex2(S[4 * i + 2]);
    const float d = ex2(S[4 * i + 3]);
    l0 += a + b;
    l1 += c + d;
    P[2 * i] = pack_bf16(a, b);
    P[2 * i + 1] = pack_bf16(c, d);
  }
  fence_regs(P);
}

__device__ __forceinline__ void sums_put(uint32_t addr, float l0, float l1, uint32_t on) {
  asm volatile("{\n.reg .pred p;\nsetp.ne.u32 p, %3, 0;\n@p st.shared.v2.f32 [%0], {%1, %2};\n}\n" ::"r"(addr), "f"(l0), "f"(l1), "r"(on) : "memory");
}
__device__ __forceinline__ void sums_get(uint32_t addr, float& s0, float& s1) {
  float a, b, c, d, e, f, g, h;
  asm volatile("ld.shared.v4.f32 {%0, %1, %2, %3}, [%8];\nld.shared.v4.f32 {%4, %5, %6, %7}, [%8 + 16];\n"
               : "=f"(a), "=f"(b), "=f"(c), "=f"(d), "=f"(e), "=f"(f), "=f"(g), "=f"(h) : "r"(addr & ~31u) : "memory");
  s0 = (a + c) + (e + g);
  s1 = (b + d) + (f + h);
}

template <int K0, int K1>
__device__ __forceinline__ void epilogue_part(const float (&O)[96], float i0, float i1, uint32_t lane_addr) {
#pragma unroll
  for (int kk = K0; kk < K1; kk++) {
    const int b = kk * 8;
    stsm_x4((lane_addr ^ ((kk % 4) << 5)) + (kk / 4) * SLAB,
            pack_bf16(O[b] * i0, O[b + 1] * i0), pack_bf16(O[b + 2] * i1, O[b + 3] * i1),
            pack_bf16(O[b + 4] * i0, O[b + 5] * i0), pack_bf16(O[b + 6] * i1, O[b + 7] * i1));
  }
}
__device__ __forceinline__ void epilogue_done(uint32_t bar, int lane) {
  __syncwarp();
  if (lane == 0) mbar_arrive(bar);
}

__device__ __forceinline__ void redo_tile(const CUtensorMap* tmQ, const CUtensorMap* tmK, const CUtensorMap* tmV, const CUtensorMap* tmO,
                                          int head, int row, uint32_t qo, uint32_t kv, uint32_t lane_addr, uint32_t bar, uint32_t& phase,
                                          uint32_t wg_bar) {
  float O[96], S[32];
  uint32_t Q[48], P[16];
  uint64_t pol;
  asm volatile("createpolicy.fractional.L2::evict_normal.b64 %0, 1.0;" : "=l"(pol));
  const bool leader = (threadIdx.x & 127) == 0;
  if (leader) {
    mbar_expect_tx(bar, SLOT);
    tma_load(qo, tmQ, bar, row, head, pol);
  }
  mbar_wait(bar, phase);
  phase ^= 1;
  load_q(Q, lane_addr);
  float m0 = -INFINITY, m1 = -INFINITY, l0 = 0.f, l1 = 0.f;
#pragma unroll
  for (int i = 0; i < 96; i++) O[i] = 0.f;
#pragma unroll 1
  for (int j = 0; j < NBLK; j++) {
    asm volatile("bar.sync %0, 128;" ::"r"(wg_bar) : "memory");
    if (leader) {
      mbar_expect_tx(bar, 2 * SLOT);
      tma_load(kv, tmK, bar, j * BN, head, pol);
      tma_load(kv + SLOT, tmV, bar, j * BN, head, pol);
    }
    mbar_wait(bar, phase);
    phase ^= 1;
    wg_fence();
    issue_qk(S, Q, kdesc0(kv));
    wg_commit();
    wg_wait<0>();
    fence_regs(S);
    float n0 = m0, n1 = m1;
#pragma unroll
    for (int i = 0; i < 8; i++) {
      n0 = fmaxf(n0, fmaxf(S[4 * i], S[4 * i + 1]));
      n1 = fmaxf(n1, fmaxf(S[4 * i + 2], S[4 * i + 3]));
    }
#pragma unroll
    for (int o = 1; o < 4; o <<= 1) {
      n0 = fmaxf(n0, __shfl_xor_sync(0xffffffffu, n0, o));
      n1 = fmaxf(n1, __shfl_xor_sync(0xffffffffu, n1, o));
    }
    const float f0 = ex2((m0 - n0) * SCALE_LOG2), f1 = ex2((m1 - n1) * SCALE_LOG2);
    m0 = n0; m1 = n1;
    l0 *= f0; l1 *= f1;
#pragma unroll
    for (int i = 0; i < 24; i++) {
      O[4 * i] *= f0; O[4 * i + 1] *= f0; O[4 * i + 2] *= f1; O[4 * i + 3] *= f1;
    }
#pragma unroll
    for (int i = 0; i < 8; i++) {
      S[4 * i] = (S[4 * i] - m0) * SCALE_LOG2; S[4 * i + 1] = (S[4 * i + 1] - m0) * SCALE_LOG2;
      S[4 * i + 2] = (S[4 * i + 2] - m1) * SCALE_LOG2; S[4 * i + 3] = (S[4 * i + 3] - m1) * SCALE_LOG2;
    }
    softmax_block(S, P, l0, l1);
    fence_regs(O);
    wg_fence();
    issue_pv<true>(O, P, vdesc0(kv + SLOT));
    wg_commit();
    wg_wait<0>();
    fence_regs(O);
  }
#pragma unroll
  for (int o = 1; o < 4; o <<= 1) {
    l0 += __shfl_xor_sync(0xffffffffu, l0, o);
    l1 += __shfl_xor_sync(0xffffffffu, l1, o);
  }
  epilogue_part<0, 12>(O, rcp(l0), rcp(l1), lane_addr);
  asm volatile("fence.proxy.async.shared::cta;" ::: "memory");
  asm volatile("bar.sync %0, 128;" ::"r"(wg_bar) : "memory");
  if (leader) {
    for (int i = 0; i < 64 && row + i < SQ; i += OROWS) tma_store(tmO, qo + i / 8 * RGRP, row + i, head, pol);
    asm volatile("cp.async.bulk.commit_group;" ::: "memory");
    asm volatile("cp.async.bulk.wait_group 0;" ::: "memory");
  }
}

__device__ __forceinline__ void wg_barrier() { asm volatile("bar.sync 3, 128;" ::: "memory"); }

__device__ __forceinline__ void tail_reduce(float (&v)[4], uint32_t red, int warp, int lane) {
#pragma unroll
  for (int o = 4; o < 32; o <<= 1)
#pragma unroll
    for (int i = 0; i < 4; i++) v[i] += __shfl_xor_sync(0xffffffffu, v[i], o);
  if (lane < 4)
    asm volatile("st.shared.v4.f32 [%0], {%1, %2, %3, %4};" ::"r"(red + (warp * 4 + lane) * 16), "f"(v[0]), "f"(v[1]), "f"(v[2]), "f"(v[3]) : "memory");
  wg_barrier();
#pragma unroll
  for (int ww = 0; ww < 4; ww++) {
    float x0, x1, x2, x3;
    asm volatile("ld.shared.v4.f32 {%0, %1, %2, %3}, [%4];" : "=f"(x0), "=f"(x1), "=f"(x2), "=f"(x3) : "r"(red + (ww * 4 + (lane & 3)) * 16) : "memory");
    if (ww == 0) { v[0] = x0; v[1] = x1; v[2] = x2; v[3] = x3; }
    else { v[0] += x0; v[1] += x1; v[2] += x2; v[3] += x3; }
  }
}

__device__ __forceinline__ void tail_softmax(const float (&S)[8], float (&l)[4], uint32_t pt_addr) {
  float e[8];
#pragma unroll
  for (int i = 0; i < 8; i++) e[i] = ex2(S[i] * SCALE_LOG2);
  stsm_x4_trans(pt_addr, pack_bf16(e[0], e[1]), pack_bf16(e[2], e[3]), pack_bf16(e[4], e[5]), pack_bf16(e[6], e[7]));
  l[0] += e[0] + e[2]; l[1] += e[1] + e[3]; l[2] += e[4] + e[6]; l[3] += e[5] + e[7];
}

__device__ __forceinline__ void issue_qkT(float (&S8)[8], uint32_t kdesc, uint32_t qt_addr) {
  const uint64_t da = DESC_HI | kdesc;
  const uint64_t db = DESC_HI | (uint64_t)(((qt_addr & 0x3FFFFu) >> 4) | (1u << 16));
  wgmma_qkT0(S8, da, db);
#pragma unroll
  for (int kk = 1; kk < 12; kk++)
    wgmma_qkT(S8, da + (uint64_t)((kk / 4) * (SLAB / 16) + (kk % 4) * 2), db + (uint64_t)((kk / 4) * (SLAB / 16) + (kk % 4) * 2), 1);
}
template <bool ACCUMULATE>
__device__ __forceinline__ void issue_pvT(float (&O)[3][8], uint32_t vdesc, uint32_t pt_base) {
  const uint64_t da = DESC_HI | vdesc;
  const uint64_t db = DESC_HI_PT | (uint64_t)(((pt_base & 0x3FFFFu) >> 4) | (1u << 16));
#pragma unroll
  for (int kk = 0; kk < 4; kk++)
#pragma unroll
    for (int b = 0; b < 3; b++) {
      if (kk == 0 && !ACCUMULATE) wgmma_pvT0(O[b], da + (uint64_t)(b * (SLAB / 16)), db);
      else wgmma_pvT(O[b], da + (uint64_t)(b * (SLAB / 16) + kk * (2 * RGRP / 16)), db + (uint64_t)(kk * 2), 1);
    }
}

template <bool B> struct Bool { static constexpr bool value = B; };

constexpr int MAX_CLUSTERS = 72;
constexpr int MAX_ROUNDS = 32;
struct Schedule {
  uint32_t tails[MAX_CLUSTERS];
  uint16_t start[MAX_CLUSTERS + 1];
  uint16_t list[NROUNDS + 1];
};

#define TRACE_TILE()

__global__ void __cluster_dims__(2, 1, 1) __launch_bounds__(NTHREADS, 1)
attn_kernel(const __grid_constant__ CUtensorMap tmQ, const __grid_constant__ CUtensorMap tmQT, const __grid_constant__ CUtensorMap tmK,
            const __grid_constant__ CUtensorMap tmV, const __grid_constant__ CUtensorMap tmO, const __grid_constant__ Schedule sched) {
  extern __shared__ __align__(1024) uint8_t smem_raw[];
  const uint32_t c_entry = (uint32_t)clock();
  const uint32_t sbase = smem_u32(smem_raw);
  const uint32_t s_qo = sbase + OFF_QO;
  const uint32_t s_kv = sbase + OFF_KV;
  const uint32_t s_bar = sbase + OFF_BAR;
  const uint32_t bar_full = s_bar;
  const uint32_t bar_empty = s_bar + 8 * NSLOT;
  const uint32_t bar_qfull = s_bar + 16 * NSLOT;
  const uint32_t bar_ostg = bar_qfull + 16;
  const uint32_t bar_qreq = bar_ostg + 16;
  const uint32_t bar_redo = bar_qreq + 16;
  const uint32_t s_redo = bar_redo + 16;

  uint32_t rank;
  asm("mov.u32 %0, %%cluster_ctarank;" : "=r"(rank));
  const int cluster = blockIdx.x >> 1;
  auto get_rounds = [&](int& first, int& count) {
    int c = cluster;
    asm volatile("" : "+r"(c));
    first = sched.start[c];
    count = sched.start[c + 1] - first;
  };

  if (threadIdx.x == 0) {
    asm volatile("prefetch.tensormap [%0];" ::"l"(&tmK) : "memory");
    asm volatile("prefetch.tensormap [%0];" ::"l"(&tmQ) : "memory");
    asm volatile("prefetch.tensormap [%0];" ::"l"(&tmV) : "memory");
    for (int i = 0; i < 3; i++) mbar_init(bar_full + 8 * i, 1);
    for (int i = 0; i < 2; i++) mbar_init(bar_qfull + 8 * i, 1);
    asm volatile("fence.mbarrier_init.release.cluster;" ::: "memory");
    asm volatile("fence.proxy.async.shared::cta;" ::: "memory");
    const int head = cluster / 3, qrow = cluster % 3 * 256 + rank * 128;
    uint64_t polq, polk;
    asm volatile("createpolicy.fractional.L2::evict_first.b64 %0, 1.0;" : "=l"(polq));
    asm volatile("createpolicy.fractional.L2::evict_unchanged.b64 %0, 1.0;" : "=l"(polk));
    while ((uint32_t)clock() - c_entry < (uint32_t)(cluster / 3 * STAGGER)) {}
    mbar_expect_tx(bar_full, SLOT);
    tma_load(s_kv, &tmK, bar_full, 0, head, polk);
    mbar_expect_tx(bar_qfull, SLOT);
    tma_load(s_qo, &tmQ, bar_qfull, qrow, head, polq);
    mbar_expect_tx(bar_full + 8, SLOT);
    tma_load(s_kv + SLOT, &tmK, bar_full + 8, BN, head, polk);
    mbar_expect_tx(bar_full + 16, SLOT);
    tma_load(s_kv + 2 * SLOT, &tmV, bar_full + 16, 0, head, polk);
    mbar_expect_tx(bar_qfull + 8, SLOT);
    tma_load(s_qo + SLOT, &tmQ, bar_qfull + 8, qrow + 64, head, polq);
  } else if (threadIdx.x == 32) {
    for (int i = 0; i < NSLOT; i++) {
      if (i >= 3) mbar_init(bar_full + 8 * i, 1);
      mbar_init(bar_empty + 8 * i, 4);
    }
    for (int i = 0; i < 2; i++) {
      mbar_init(bar_ostg + 8 * i, 4);
      mbar_init(bar_qreq + 8 * i, 1);
      mbar_init(bar_redo + 8 * i, 1);
      asm volatile("st.shared.u32 [%0], %1;" ::"r"(s_redo + 4 * i), "r"(0) : "memory");
    }
    asm volatile("fence.mbarrier_init.release.cluster;" ::: "memory");
    asm volatile("fence.proxy.async.shared::cta;" ::: "memory");
  }
  __syncthreads();
  asm volatile("barrier.cluster.arrive.relaxed.aligned;\nbarrier.cluster.wait.aligned;" ::: "memory");

  const int wg = __shfl_sync(0xffffffffu, threadIdx.x >> 7, 0);
  const int warp = __shfl_sync(0xffffffffu, (threadIdx.x >> 5) & 3, 0);
  const int lane = threadIdx.x & 31;

  if (wg == 0) {
    asm volatile("setmaxnreg.dec.sync.aligned.u32 24;");
    int first_round, nrounds;
    get_rounds(first_round, nrounds);
    const int nblocks = nrounds * NBLK;
    if (warp == 0 && lane == 0) {
      uint64_t pol;
      asm volatile("createpolicy.fractional.L2::evict_unchanged.b64 %0, 1.0;" : "=l"(pol));
      uint32_t slot = 3, phase = 1;
      auto load = [&](const CUtensorMap* tm, int n, uint32_t owner) {
        const Round r = decode_round(sched.list[first_round + (n >> 3)] & 0x7ff, rank);
        mbar_wait_sleep(bar_empty + 8 * slot, phase);
        if (n < nblocks) {
          mbar_expect_tx(bar_full + 8 * slot, SLOT);
          if (!r.mc) tma_load(s_kv + slot * SLOT, tm, bar_full + 8 * slot, (n & 7) * BN, r.head, pol);
          else if (rank == owner) tma_load_mc(s_kv + slot * SLOT, tm, bar_full + 8 * slot, (n & 7) * BN, r.head, pol);
        }
        if (++slot == NSLOT) { slot = 0; phase ^= 1; }
      };
      for (int n = 1; n < nblocks; n++) {
        load(&tmK, n + 1, 0);
        load(&tmV, n, 1);
      }
      for (int i = 0; i < NSLOT; i++) {
        if (i != NSLOT - 2) mbar_wait_sleep(bar_empty + 8 * slot, phase);
        if (++slot == NSLOT) { slot = 0; phase ^= 1; }
      }
    } else if ((warp == 1 || warp == 2) && lane == 0) {
      const int w = warp - 1;
      uint64_t pol;
      asm volatile("createpolicy.fractional.L2::evict_first.b64 %0, 1.0;" : "=l"(pol));
      const uint32_t buf = s_qo + w * SLOT;
      Round r = decode_round(sched.list[first_round] & 0x7ff, rank);
      Round prev = r;
      for (int t = 0; t <= nrounds; t++) {
        mbar_wait_sleep(bar_ostg + 8 * w, t & 1);
        if (t > 0) {
          asm volatile("fence.proxy.async.shared::cta;" ::: "memory");
          const int row0 = prev.qrow + w * 64;
          const int nrows = row0 + 64 <= SQ ? 64 : SQ - row0;
#pragma unroll 1
          for (int i = 0; i < nrows; i += OROWS) {
            tma_store(&tmO, buf + i / 8 * RGRP, row0 + i, prev.head, pol);
            asm volatile("cp.async.bulk.commit_group;" ::: "memory");
            if (t < nrounds) asm volatile("cp.async.bulk.wait_group.read 0;" ::: "memory");
          }
          prev = r;
        }
        if (t + 1 < nrounds) {
          mbar_wait_sleep(bar_qreq + 8 * w, t & 1);
          const uint32_t e = sched.list[first_round + t + 1];
          r = decode_round(e & 0x7ff, rank);
          if (w == 1 && (e & 0x8000)) {
            mbar_expect_tx(bar_qfull + 8 * w, 3 * 2048);
            tma_load(sbase + OFF_QT, &tmQT, bar_qfull + 8 * w, r.qrow + 64, r.head, pol);
          } else {
            mbar_expect_tx(bar_qfull + 8 * w, SLOT);
            tma_load(buf, &tmQ, bar_qfull + 8 * w, r.qrow + w * 64, r.head, pol);
          }
        } else if (t < nrounds) {
          mbar_arrive(bar_qfull + 8 * w);
        }
      }
      asm volatile("cp.async.bulk.wait_group 0;" ::: "memory");
      mbar_arrive(bar_redo + 8 * w);
    } else if (warp == 3) {
      uint32_t slot = 1, phase = 0;
      const uint32_t tails = sched.tails[cluster];
      for (int n = 0; n < nblocks; n++) {
        if (n + 1 < nblocks) mbar_wait(bar_full + 8 * slot, phase);
        if (++slot == NSLOT) { slot = 0; phase ^= 1; }
        mbar_wait(bar_full + 8 * slot, phase);
        if (++slot == NSLOT) { slot = 0; phase ^= 1; }
        asm volatile("bar.sync 1, 288;" ::: "memory");
        asm volatile("bar.arrive 2, 288;" ::: "memory");
        if (lane < 2 && (n & 7) + ((tails >> (n >> 3 & 31) & 1) ? QREQT : 0) == (lane ? QREQ1 : QREQ0)) mbar_arrive(bar_qreq + 8 * lane);
        TRACE_TILE();
      }
    }
  } else {
    asm volatile("setmaxnreg.inc.sync.aligned.u32 240;");
    const int w = wg - 1;
    int first_round, nrounds;
    get_rounds(first_round, nrounds);
    const int nblocks = nrounds * NBLK;
    float O[96], S[32];
    uint32_t Q[48], P0[16], P1[16];
    float l0 = 0.f, l1 = 0.f, inv0 = 1.f, inv1 = 1.f;
    uint32_t redo = 0;
    const uint32_t lane_addr = s_qo + w * SLOT + (warp * 2 + ((lane >> 3) & 1)) * RGRP + (lane & 7) * 128 + (((lane >> 4) ^ (lane & 7)) << 4);
    const uint32_t sum_addr = s_qo + w * SLOT + warp * 2 * RGRP + lane * 8;
    const uint32_t my_qfull = bar_qfull + 8 * w, my_ostg = bar_ostg + 8 * w;

    uint32_t empty_remote;
    asm("mapa.shared::cluster.u32 %0, %1, %2;" : "=r"(empty_remote) : "r"(bar_empty), "r"(threadIdx.x & 1));
    const bool releaser = (threadIdx.x & 127) < 2;
    auto release = [&](uint32_t s) {
      if (releaser) asm volatile("mbarrier.arrive.shared::cluster.b64 _, [%0];" ::"r"(empty_remote + s) : "memory");
    };
    uint32_t ks = 8, vs = 16, kp = 0, vp = 0;
    const uint32_t kd0 = kdesc0(s_kv), vd0 = vdesc0(s_kv);
    uint32_t kd = kd0 + ks * (SLOT / 128), vd = vd0 + vs * (SLOT / 128);
    auto advance = [&]() {
      kp = ks; vp = vs;
      ks = ks >= 8 * (NSLOT - 2) ? ks - 8 * (NSLOT - 2) : ks + 16;
      vs = vs >= 8 * (NSLOT - 2) ? vs - 8 * (NSLOT - 2) : vs + 16;
      kd = kd0 + ks * (SLOT / 128); vd = vd0 + vs * (SLOT / 128);
      asm volatile("" : "+r"(ks), "+r"(vs), "+r"(kd), "+r"(vd));
    };

    uint32_t tails = w == 1 ? sched.tails[cluster] : 0u;
    auto turn_wait = [&]() { asm volatile("bar.sync %0, 288;" ::"r"(1 + w) : "memory"); };
    auto turn_pass = [&]() { asm volatile("bar.arrive %0, 288;" ::"r"(2 - w) : "memory"); };
    if (w == 1) turn_pass();

    mbar_wait(my_qfull, 0);
    load_q(Q, lane_addr);
    scale_q(Q);
    mbar_wait(bar_full, 0);
    wg_fence();
    issue_qk(S, Q, kd0);
    wg_commit();
    wg_wait<0>();
    fence_regs(S);
    release(0);
    __syncwarp();
    if (lane == 0) mbar_arrive(my_ostg);
    bool pending = false;

    int n = 0;
    auto finish_sums = [&]() {
      float s0, s1;
      sums_get(sum_addr, s0, s1);
      inv0 = rcp(s0); inv1 = rcp(s1);
      l0 = l1 = 0.f;
      asm volatile("" : "+f"(inv0), "+f"(inv1)::"memory");
    };
    auto check_sums = [&](int t) { check_inv(inv0, inv1, redo, 1u << (t & 31)); };

    int exit_n = -1;
#pragma unroll 1
    while (true) {
#pragma unroll 1
      while (true) {
        const int j = n & 7;
        softmax_block(S, P0, l0, l1);
        asm volatile("" : "+f"(l0), "+f"(l1)::"memory");
        if (j != 0) {
          wg_wait<0>();
          release(vp);
          turn_wait();
          wg_fence();
          issue_qk3(S, Q, kd);
          wg_commit();
          issue_pv<true>(O, P0, vd);
          wg_commit();
          turn_pass();
          advance();
          if (j == 6) {
            mbar_wait(my_qfull, ((n >> 3) + 1) & 1);
            wg_wait<3>();
            load_q<0, 4>(Q, lane_addr);
            wg_wait<2>();
            load_q<4, 8>(Q, lane_addr);
          }
          wg_wait<1>();
          fence_regs(S);
          fence_regs(P1);
        } else {
          wg_wait<0>();
          fence_regs(O);
          fence_regs(P1);
          if (pending) {
            release(vp);
            epilogue_part<0, ESPLIT>(O, inv0, inv1, lane_addr);
          }
          turn_wait();
          wg_fence();
          issue_qk32(S, Q, kd);
          wg_commit();
          if (pending) {
            epilogue_part<ESPLIT, 12>(O, inv0, inv1, lane_addr);
            epilogue_done(my_ostg, lane);
          }
          wg_fence();
          issue_pv<false>(O, P0, vd);
          wg_commit();
          turn_pass();
          advance();
          check_sums((n >> 3) - 1);
          exit_n = ((tails & 2) || n + 8 == nblocks) ? n + 6 : -1;
          tails >>= 1;
          asm volatile("" : "+r"(exit_n), "+r"(tails), "+r"(redo));
          wg_wait<1>();
          fence_regs(S);
          pending = true;
        }
        release(kp);
        if (j == 6) load_q<8, 12>(Q, lane_addr);
        softmax_block(S, P1, l0, l1);
        sums_put(sum_addr, l0, l1, j == 6);
        wg_wait<0>();
        release(vp);
        if (j == 6) {
          scale_q(Q);
          if (n == exit_n) {
            turn_wait();
            wg_fence();
            issue_pv<true>(O, P1, vd);
            wg_commit();
            break;
          }
          asm volatile("" ::: "memory");
          turn_wait();
          wg_fence();
          issue_qk32(S, Q, kd);
          wg_commit();
          issue_pv<true>(O, P1, vd);
          wg_commit();
          turn_pass();
          advance();
          if (pending) finish_sums();
          wg_wait<1>();
        } else {
          turn_wait();
          wg_fence();
          issue_qk(S, Q, kd);
          wg_commit();
          issue_pv<true>(O, P1, vd);
          wg_commit();
          turn_pass();
          advance();
          wg_wait<1>();
        }
        fence_regs(S);
        fence_regs(P0);
        release(kp);
        n += 2;
      }
      if (n + 2 == nblocks) {
        if (w == 0) turn_pass();
        finish_sums();
        check_sums(n >> 3);
        wg_wait<0>();
        fence_regs(O);
        release(vs);
        epilogue_part<0, 12>(O, inv0, inv1, lane_addr);
        epilogue_done(my_ostg, lane);
        break;
      }
      const int t = n >> 3;
      const uint32_t qt = sbase + OFF_QT, pt = sbase + OFF_PT, red = sbase + OFF_RED;
      const uint32_t tl = ((lane & 7) + (lane >> 4) * 8) * 128 + (((warp * 2 + ((lane >> 3) & 1)) ^ (lane & 7)) << 4);
      const bool tlast = n + 10 == nblocks;
      float lt[4] = {0.f, 0.f, 0.f, 0.f};
      float ST[8], OT[3][8];
      wg_fence();
      issue_qkT(ST, kd, qt);
      wg_commit();
      turn_pass();
      finish_sums();
      check_sums(t);
      wg_wait<0>();
      fence_regs(ST);
      fence_regs(O);
      release(ks);
      release(vs);
      advance();
      epilogue_part<0, NT_SPLIT>(O, inv0, inv1, lane_addr);
      if (NT_SPLIT == 12) epilogue_done(my_ostg, lane);
      tail_softmax(ST, lt, pt + tl);
      auto tail_step = [&](auto first_c, int jj) {
        constexpr bool FIRST = decltype(first_c)::value;
        asm volatile("fence.proxy.async.shared::cta;" ::: "memory");
        turn_wait();
        wg_fence();
        issue_qkT(ST, kd, qt);
        wg_commit();
        issue_pvT<!FIRST>(OT, vd, pt + (jj & 1) * 2048);
        wg_commit();
        turn_pass();
        advance();
        wg_wait<1>();
        fence_regs(ST);
        release(kp);
        tail_softmax(ST, lt, pt + (~jj & 1) * 2048 + tl);
        wg_wait<0>();
        fence_regs(OT[0]); fence_regs(OT[1]); fence_regs(OT[2]);
        release(vp);
      };
      tail_step(Bool<true>(), 0);
      if (NT_SPLIT < 12) {
        epilogue_part<NT_SPLIT, 12>(O, inv0, inv1, lane_addr);
        epilogue_done(my_ostg, lane);
      }
#pragma unroll 1
      for (int jj = 1; jj < 7; jj++) tail_step(Bool<false>(), jj);
      mbar_wait(my_qfull, t & 1);
      load_q(Q, lane_addr);
      scale_q(Q);
      tail_reduce(lt, red, warp, lane);
#pragma unroll
      for (int i = 0; i < 4; i++) lt[i] = rcp(lt[i]);
      check_inv(lt[0], lt[1], redo, 1u << ((t + 1) & 31));
      check_inv(lt[2], lt[3], redo, 1u << ((t + 1) & 31));
      inv0 = inv1 = 1.f;
      asm volatile("fence.proxy.async.shared::cta;" ::: "memory");
      turn_wait();
      wg_fence();
      issue_pvT<true>(OT, vd, pt + 2048);
      wg_commit();
      issue_qk(S, Q, kd);
      wg_commit();
      if (!tlast) turn_pass();
      wg_wait<1>();
      fence_regs(OT[0]); fence_regs(OT[1]); fence_regs(OT[2]);
      release(vs);
#pragma unroll
      for (int b = 0; b < 3; b++)
        stsm_x4_trans(s_qo + SLOT + b * SLAB + tl + (lane >> 4) * (RGRP - 1024),
                      pack_bf16(OT[b][0] * lt[0], OT[b][1] * lt[1]), pack_bf16(OT[b][2] * lt[0], OT[b][3] * lt[1]),
                      pack_bf16(OT[b][4] * lt[2], OT[b][5] * lt[3]), pack_bf16(OT[b][6] * lt[2], OT[b][7] * lt[3]));
      epilogue_done(my_ostg, lane);
      wg_wait<0>();
      fence_regs(S);
      if (tlast) break;
      release(ks);
      advance();
#pragma unroll
      for (int i = 0; i < 96; i++) O[i] = 0.f;
      pending = false;
      n += 10;
      tails >>= 1;
    }
    if (redo) asm volatile("red.shared.or.b32 [%0], %1;" ::"r"(s_redo + 4 * w), "r"(redo) : "memory");
    asm volatile("bar.sync 4, 256;" ::: "memory");
    asm volatile("ld.shared.u32 %0, [%1];" : "=r"(redo) : "r"(s_redo + 4 * w) : "memory");
    redo = __shfl_sync(0xffffffffu, redo, 0);
    if (redo) {
      mbar_wait_sleep(bar_redo + 8 * w, 0);
      asm volatile("bar.sync %0, 128;" ::"r"(5 + w) : "memory");
      uint32_t phase = 1;
      get_rounds(first_round, nrounds);
#pragma unroll 1
      for (int t = 0; t < nrounds; t++) {
        if (!(redo >> (t & 31) & 1)) continue;
        const Round r = decode_round(sched.list[first_round + t] & 0x7ff, rank);
        redo_tile(&tmQ, &tmK, &tmV, &tmO, r.head, r.qrow + w * 64, s_qo + w * SLOT, s_kv + 2 * w * SLOT, lane_addr, bar_redo + 8 * w, phase, 5 + w);
      }
    }
  }
}

typedef CUresult (*EncodeFn)(CUtensorMap*, CUtensorMapDataType, cuuint32_t, void*, const cuuint64_t*, const cuuint64_t*,
                             const cuuint32_t*, const cuuint32_t*, CUtensorMapInterleave, CUtensorMapSwizzle,
                             CUtensorMapL2promotion, CUtensorMapFloatOOBfill);

void make_map(EncodeFn fn, CUtensorMap* tm, const void* ptr, int rows, int box_rows) {
  cuuint64_t dims[5] = {64, 8, 3, (cuuint64_t)rows / 8, (cuuint64_t)NHEADS};
  cuuint64_t strides[4] = {HD * 2, 128, 8 * HD * 2, (cuuint64_t)rows * HD * 2};
  cuuint32_t box[5] = {64, 8, 3, (cuuint32_t)box_rows / 8, 1};
  cuuint32_t estr[5] = {1, 1, 1, 1, 1};
  fn(tm, CU_TENSOR_MAP_DATA_TYPE_BFLOAT16, 5, const_cast<void*>(ptr), dims, strides, box, estr,
     CU_TENSOR_MAP_INTERLEAVE_NONE, CU_TENSOR_MAP_SWIZZLE_128B, CU_TENSOR_MAP_L2_PROMOTION_L2_128B, CU_TENSOR_MAP_FLOAT_OOB_FILL_NONE);
}

#define COST_N 12690
#define COST_T 10800
#define COST_TN 12720
#define TAIL_LATE 36
#define TAIL_MAX 60
#define HEAVY_STEP 3
static_assert(MAX_CLUSTERS / 3 * STAGGER < COST_T, "the first wave has to be handed out in the order of the clusters");
void make_schedule(Schedule& s, int nclusters) {
  static uint16_t lists[MAX_CLUSTERS][NROUNDS];
  int cnt[MAX_CLUSTERS] = {0}, len[MAX_CLUSTERS], ntail[MAX_CLUSTERS] = {0}, quota[MAX_CLUSTERS] = {0};
  long long busy[MAX_CLUSTERS], fin[MAX_CLUSTERS];
  const int ntails = NROUNDS / 7, base = NROUNDS / nclusters, nheavy = NROUNDS % nclusters;
  const int step = nheavy * HEAVY_STEP <= nclusters ? HEAVY_STEP : 1;
  for (int c = 0; c < nclusters; c++) {
    len[c] = base + (c % step == 0 && c / step < nheavy);
    busy[c] = c / 3 * STAGGER;
    fin[c] = busy[c] + (long long)len[c] * COST_N;
  }
  for (int k = 0; k < ntails; k++) {
    int c = -1;
    for (int i = 0; i < nclusters; i++)
      if (quota[i] < len[i] / 2 && (c < 0 || fin[i] > fin[c])) c = i;
    quota[c]++;
    fin[c] -= 2 * COST_N - COST_T - COST_TN;
  }
  int gn = 0, gt = 3;
  for (int k = 0; k < NROUNDS; k++) {
    int c = -1;
    for (int i = 0; i < nclusters; i++)
      if (cnt[i] < len[i] && (c < 0 || busy[i] < busy[c])) c = i;
    const bool after_tail = cnt[c] > 0 && (lists[c][cnt[c] - 1] & 0x8000);
    const bool may_t = cnt[c] > 0 && !after_tail;
    const int left = len[c] - cnt[c], q = quota[c] - ntail[c];
    const bool due = (long long)(gt / 7) * quota[c] * 8 >= (long long)(ntail[c] * 8 + (c * 5 & 7)) * ntails;
    bool tail = may_t && q > 0 && (2 * q > left || (gn - gt >= TAIL_LATE && due) || gn - gt >= TAIL_MAX);
    if (4 * quota[c] >= len[c]) {
      const int m = len[c] - 1, phase = c / step * 11 % m;
      tail = may_t && q > 0 && (2 * q > left || (cnt[c] * quota[c] + phase) / m > ntail[c]);
    }
    if (gt >= NROUNDS) tail = false;
    if (gn >= NROUNDS) tail = true;
    const int g = tail ? gt : gn;
    if (tail) { gt += 7; ntail[c]++; }
    else { gn++; if (gn % 7 == 3) gn++; }
    const bool form_t = tail && may_t;
    lists[c][cnt[c]++] = (uint16_t)(g | (form_t ? 0x8000 : 0));
    busy[c] += form_t ? COST_T : after_tail ? COST_TN : COST_N;
  }
  bool use_tail = true;
  for (int c = 0; c < nclusters; c++) if (cnt[c] > MAX_ROUNDS) use_tail = false;
  if (!use_tail) for (int c = 0; c < nclusters; c++) for (int i = 0; i < cnt[c]; i++) lists[c][i] &= 0x7fff;
  int pos = 0;
  for (int c = 0; c < nclusters; c++) {
    s.start[c] = (uint16_t)pos;
    s.tails[c] = 0;
    for (int i = 0; i < cnt[c]; i++) {
      if (lists[c][i] & 0x8000) s.tails[c] |= 1u << i;
      s.list[pos++] = lists[c][i];
    }
  }
  for (int c = nclusters; c <= MAX_CLUSTERS; c++) s.start[c] = (uint16_t)pos;
  s.list[NROUNDS] = 0;
}

}

extern "C" void kernel_launch(void* const* d_in, const int* in_sizes, int n_in, void* d_out, int out_size) {
  static EncodeFn encode = nullptr;
  static int nclusters = 0;
  static Schedule sched;
  if (!encode) {
    void* fn = nullptr;
    cudaDriverEntryPointQueryResult qr;
    cudaGetDriverEntryPoint("cuTensorMapEncodeTiled", &fn, cudaEnableDefault, &qr);
    encode = (EncodeFn)fn;
    int dev = 0, nsm = 0;
    cudaGetDevice(&dev);
    cudaDeviceGetAttribute(&nsm, cudaDevAttrMultiProcessorCount, dev);
    nclusters = nsm / 2 < MAX_CLUSTERS ? nsm / 2 : MAX_CLUSTERS;
    make_schedule(sched, nclusters);
    cudaFuncSetAttribute(attn_kernel, cudaFuncAttributeMaxDynamicSharedMemorySize, SMEM_BYTES);
  }
  CUtensorMap tmQ, tmQT, tmK, tmV, tmO;
  make_map(encode, &tmQ, d_in[0], SQ, 64);
  make_map(encode, &tmQT, d_in[0], SQ, 16);
  make_map(encode, &tmK, d_in[1], SK, 64);
  make_map(encode, &tmV, d_in[2], SK, 64);
  make_map(encode, &tmO, d_out, SQ, OROWS);
  attn_kernel<<<2 * nclusters, NTHREADS, SMEM_BYTES>>>(tmQ, tmQT, tmK, tmV, tmO, sched);
}
```

```cpp
#include <cuda_runtime.h>
#include <cuda_bf16.h>
#include <cuda.h>
#include <stdint.h>

namespace {

constexpr int NHEADS = 512;
constexpr int SQ = 848;
constexpr int SK = 512;
constexpr int HD = 192;
constexpr int BN = 64;
constexpr int NBLK = SK / BN;
constexpr int SLOT = 64 * HD * 2;
constexpr int SLAB = 1024;
constexpr int RGRP = 3 * SLAB;
constexpr int NSLOT = 7;
constexpr int NROUNDS = (NHEADS / 2) * 7;
constexpr int NTHREADS = 384;
constexpr int OFF_QO = 0;
constexpr int OFF_KV = 2 * SLOT;
constexpr int OFF_QT = (2 + NSLOT) * SLOT;
constexpr int OFF_PT = OFF_QT + 3 * 2048;
constexpr int OFF_RED = OFF_PT + 2 * 2048;
constexpr int OFF_BAR = OFF_RED + 256;
constexpr int SMEM_BYTES = OFF_BAR + 256;

#define ESPLIT 8
#define OROWS 16
#define STAGGER 250
#define PRESCALE 1
#define NT_SPLIT 4
#define QREQ0 12
#define QREQ1 14
#define QREQT 2
constexpr uint32_t WAIT_LIMIT = 1u << 18;
#define SUSPEND 20000
constexpr uint32_t SUSPEND_NS = SUSPEND;

constexpr float SCALE_LOG2 = 0.07216878364870322f * 1.4426950408889634f;
__device__ __forceinline__ void check_inv(float a, float b, uint32_t& mask, uint32_t bit) {
  asm("{\n.reg .pred p;\nsetp.ge.f32 p, %1, 0f21800000;\nsetp.le.and.f32 p, %1, 0f4E800000, p;\n"
      "setp.ge.and.f32 p, %2, 0f21800000, p;\nsetp.le.and.f32 p, %2, 0f4E800000, p;\n@!p or.b32 %0, %0, %3;\n}\n"
      : "+r"(mask) : "f"(a), "f"(b), "r"(bit));
}

__device__ __forceinline__ uint32_t smem_u32(const void* p) { return (uint32_t)__cvta_generic_to_shared(p); }
__device__ __forceinline__ void wg_fence() { asm volatile("wgmma.fence.sync.aligned;" ::: "memory"); }
__device__ __forceinline__ void wg_commit() { asm volatile("wgmma.commit_group.sync.aligned;" ::: "memory"); }
template <int N> __device__ __forceinline__ void wg_wait() { asm volatile("wgmma.wait_group.sync.aligned %0;" ::"n"(N) : "memory"); }
template <int N> __device__ __forceinline__ void fence_regs(float (&r)[N]) {
#pragma unroll
  for (int i = 0; i < N; i++) asm volatile("" : "+f"(r[i])::"memory");
}
template <int N> __device__ __forceinline__ void fence_regs(uint32_t (&r)[N]) {
#pragma unroll
  for (int i = 0; i < N; i++) asm volatile("" : "+r"(r[i])::"memory");
}

__device__ __forceinline__ void mbar_init(uint32_t bar, uint32_t cnt) {
  asm volatile("mbarrier.init.shared::cta.b64 [%0], %1;" ::"r"(bar), "r"(cnt));
}
__device__ __forceinline__ void mbar_expect_tx(uint32_t bar, uint32_t bytes) {
  asm volatile("mbarrier.arrive.expect_tx.shared::cta.b64 _, [%0], %1;" ::"r"(bar), "r"(bytes) : "memory");
}
__device__ __forceinline__ void mbar_arrive(uint32_t bar) {
  asm volatile("mbarrier.arrive.shared::cta.b64 _, [%0];" ::"r"(bar) : "memory");
}
__device__ __forceinline__ bool mbar_try(uint32_t bar, uint32_t parity) {
  uint32_t ok;
  asm volatile(
      "{\n.reg .pred p;\nmbarrier.try_wait.parity.shared::cta.b64 p, [%1], %2;\nselp.b32 %0, 1, 0, p;\n}\n"
      : "=r"(ok)
      : "r"(bar), "r"(parity)
      : "memory");
  return ok;
}
__device__ __forceinline__ bool mbar_try_sleep(uint32_t bar, uint32_t parity) {
  uint32_t ok;
  asm volatile(
      "{\n.reg .pred p;\nmbarrier.try_wait.parity.shared::cta.b64 p, [%1], %2, %3;\nselp.b32 %0, 1, 0, p;\n}\n"
      : "=r"(ok)
      : "r"(bar), "r"(parity), "r"(SUSPEND_NS)
      : "memory");
  return ok;
}
__device__ __forceinline__ void mbar_wait(uint32_t bar, uint32_t parity) {
  if (mbar_try(bar, parity)) return;
  for (uint32_t n = 0; n < WAIT_LIMIT; n++)
    if (mbar_try(bar, parity)) break;
}
__device__ __forceinline__ void mbar_wait_sleep(uint32_t bar, uint32_t parity) {
  for (uint32_t n = 0; n < WAIT_LIMIT; n++) {
    if (mbar_try_sleep(bar, parity)) break;
  }
}

__device__ __forceinline__ void tma_load(uint32_t dst, const CUtensorMap* tm, uint32_t bar, int row, int head, uint64_t pol) {
  asm volatile(
      "cp.async.bulk.tensor.5d.shared::cluster.global.mbarrier::complete_tx::bytes.L2::cache_hint"
      " [%0], [%1, {%3, %3, %3, %4, %5}], [%2], %6;" ::"r"(dst),
      "l"(tm), "r"(bar), "r"(0), "r"(row >> 3), "r"(head), "l"(pol)
      : "memory");
}
__device__ __forceinline__ void tma_load_mc(uint32_t dst, const CUtensorMap* tm, uint32_t bar, int row, int head, uint64_t pol) {
  asm volatile(
      "cp.async.bulk.tensor.5d.shared::cluster.global.mbarrier::complete_tx::bytes.multicast::cluster.L2::cache_hint"
      " [%0], [%1, {%3, %3, %3, %4, %5}], [%2], %7, %6;" ::"r"(dst),
      "l"(tm), "r"(bar), "r"(0), "r"(row >> 3), "r"(head), "l"(pol), "h"((uint16_t)3)
      : "memory");
}
__device__ __forceinline__ void tma_store(const CUtensorMap* tm, uint32_t src, int row, int head, uint64_t pol) {
  asm volatile(
      "cp.async.bulk.tensor.5d.global.shared::cta.bulk_group.L2::cache_hint"
      " [%0, {%2, %2, %2, %3, %4}], [%1], %5;" ::"l"(tm),
      "r"(src), "r"(0), "r"(row >> 3), "r"(head), "l"(pol)
      : "memory");
}
__device__ __forceinline__ void ldsm_x4(uint32_t addr, uint32_t& r0, uint32_t& r1, uint32_t& r2, uint32_t& r3) {
  asm volatile("ldmatrix.sync.aligned.m8n8.x4.shared.b16 {%0, %1, %2, %3}, [%4];"
               : "=r"(r0), "=r"(r1), "=r"(r2), "=r"(r3)
               : "r"(addr)
               : "memory");
}
__device__ __forceinline__ void stsm_x4(uint32_t addr, uint32_t r0, uint32_t r1, uint32_t r2, uint32_t r3) {
  asm volatile("stmatrix.sync.aligned.m8n8.x4.shared.b16 [%0], {%1, %2, %3, %4};" ::"r"(addr), "r"(r0), "r"(r1), "r"(r2), "r"(r3)
               : "memory");
}
__device__ __forceinline__ void stsm_x4_trans(uint32_t addr, uint32_t r0, uint32_t r1, uint32_t r2, uint32_t r3) {
  asm volatile("stmatrix.sync.aligned.m8n8.x4.trans.shared.b16 [%0], {%1, %2, %3, %4};" ::"r"(addr), "r"(r0), "r"(r1), "r"(r2), "r"(r3)
               : "memory");
}
__device__ __forceinline__ float ex2(float x) {
  float y;
  asm("ex2.approx.ftz.f32 %0, %1;" : "=f"(y) : "f"(x));
  return y;
}
__device__ __forceinline__ float rcp(float x) {
  float y;
  asm("rcp.approx.ftz.f32 %0, %1;" : "=f"(y) : "f"(x));
  return y;
}
__device__ __forceinline__ uint32_t pack_bf16(float lo, float hi) {
  uint32_t r;
  asm("cvt.rn.bf16x2.f32 %0, %1, %2;" : "=r"(r) : "f"(hi), "f"(lo));
  return r;
}
__device__ __forceinline__ void wgmma_qk(float (&d)[32], uint32_t a0, uint32_t a1, uint32_t a2, uint32_t a3, uint64_t db, int scale_d) {
  asm volatile("{\n.reg .pred p;\nsetp.ne.b32 p, %37, 0;\n"
    "wgmma.mma_async.sync.aligned.m64n64k16.f32.bf16.bf16 "
    "{%0, %1, %2, %3, %4, %5, %6, %7, %8, %9, %10, %11, %12, %13, %14, %15, %16, %17, %18, %19, %20, %21, %22, %23, %24, %25, %26, %27, %28, %29, %30, %31}, "
    "{%32, %33, %34, %35}, %36, p, 1, 1, 0;\n}\n"
    : "+f"(d[0]), "+f"(d[1]), "+f"(d[2]), "+f"(d[3]), "+f"(d[4]), "+f"(d[5]), "+f"(d[6]), "+f"(d[7]), "+f"(d[8]), "+f"(d[9]), "+f"(d[10]), "+f"(d[11]), "+f"(d[12]), "+f"(d[13]), "+f"(d[14]), "+f"(d[15]), "+f"(d[16]), "+f"(d[17]), "+f"(d[18]), "+f"(d[19]), "+f"(d[20]), "+f"(d[21]), "+f"(d[22]), "+f"(d[23]), "+f"(d[24]), "+f"(d[25]), "+f"(d[26]), "+f"(d[27]), "+f"(d[28]), "+f"(d[29]), "+f"(d[30]), "+f"(d[31])
    : "r"(a0), "r"(a1), "r"(a2), "r"(a3), "l"(db), "r"(scale_d));
}

__device__ __forceinline__ void wgmma_pv(float (&d)[96], uint32_t a0, uint32_t a1, uint32_t a2, uint32_t a3, uint64_t db, int scale_d) {
  asm volatile("{\n.reg .pred p;\nsetp.ne.b32 p, %101, 0;\n"
    "wgmma.mma_async.sync.aligned.m64n192k16.f32.bf16.bf16 "
    "{%0, %1, %2, %3, %4, %5, %6, %7, %8, %9, %10, %11, %12, %13, %14, %15, %16, %17, %18, %19, %20, %21, %22, %23, %24, %25, %26, %27, %28, %29, %30, %31, %32, %33, %34, %35, %36, %37, %38, %39, %40, %41, %42, %43, %44, %45, %46, %47, %48, %49, %50, %51, %52, %53, %54, %55, %56, %57, %58, %59, %60, %61, %62, %63, %64, %65, %66, %67, %68, %69, %70, %71, %72, %73, %74, %75, %76, %77, %78, %79, %80, %81, %82, %83, %84, %85, %86, %87, %88, %89, %90, %91, %92, %93, %94, %95}, "
    "{%96, %97, %98, %99}, %100, p, 1, 1, 1;\n}\n"
    : "+f"(d[0]), "+f"(d[1]), "+f"(d[2]), "+f"(d[3]), "+f"(d[4]), "+f"(d[5]), "+f"(d[6]), "+f"(d[7]), "+f"(d[8]), "+f"(d[9]), "+f"(d[10]), "+f"(d[11]), "+f"(d[12]), "+f"(d[13]), "+f"(d[14]), "+f"(d[15]), "+f"(d[16]), "+f"(d[17]), "+f"(d[18]), "+f"(d[19]), "+f"(d[20]), "+f"(d[21]), "+f"(d[22]), "+f"(d[23]), "+f"(d[24]), "+f"(d[25]), "+f"(d[26]), "+f"(d[27]), "+f"(d[28]), "+f"(d[29]), "+f"(d[30]), "+f"(d[31]), "+f"(d[32]), "+f"(d[33]), "+f"(d[34]), "+f"(d[35]), "+f"(d[36]), "+f"(d[37]), "+f"(d[38]), "+f"(d[39]), "+f"(d[40]), "+f"(d[41]), "+f"(d[42]), "+f"(d[43]), "+f"(d[44]), "+f"(d[45]), "+f"(d[46]), "+f"(d[47]), "+f"(d[48]), "+f"(d[49]), "+f"(d[50]), "+f"(d[51]), "+f"(d[52]), "+f"(d[53]), "+f"(d[54]), "+f"(d[55]), "+f"(d[56]), "+f"(d[57]), "+f"(d[58]), "+f"(d[59]), "+f"(d[60]), "+f"(d[61]), "+f"(d[62]), "+f"(d[63]), "+f"(d[64]), "+f"(d[65]), "+f"(d[66]), "+f"(d[67]), "+f"(d[68]), "+f"(d[69]), "+f"(d[70]), "+f"(d[71]), "+f"(d[72]), "+f"(d[73]), "+f"(d[74]), "+f"(d[75]), "+f"(d[76]), "+f"(d[77]), "+f"(d[78]), "+f"(d[79]), "+f"(d[80]), "+f"(d[81]), "+f"(d[82]), "+f"(d[83]), "+f"(d[84]), "+f"(d[85]), "+f"(d[86]), "+f"(d[87]), "+f"(d[88]), "+f"(d[89]), "+f"(d[90]), "+f"(d[91]), "+f"(d[92]), "+f"(d[93]), "+f"(d[94]), "+f"(d[95])
    : "r"(a0), "r"(a1), "r"(a2), "r"(a3), "l"(db), "r"(scale_d));
}

__device__ __forceinline__ void wgmma_qkT(float (&d)[8], uint64_t da, uint64_t db, int scale_d) {
  asm volatile("{\n.reg .pred p;\nsetp.ne.b32 p, %10, 0;\n"
    "wgmma.mma_async.sync.aligned.m64n16k16.f32.bf16.bf16 "
    "{%0, %1, %2, %3, %4, %5, %6, %7}, "
    "%8, %9, p, 1, 1, 0, 0;\n}\n"
    : "+f"(d[0]), "+f"(d[1]), "+f"(d[2]), "+f"(d[3]), "+f"(d[4]), "+f"(d[5]), "+f"(d[6]), "+f"(d[7])
    : "l"(da), "l"(db), "r"(scale_d));
}
__device__ __forceinline__ void wgmma_pvT(float (&d)[8], uint64_t da, uint64_t db, int scale_d) {
  asm volatile("{\n.reg .pred p;\nsetp.ne.b32 p, %10, 0;\n"
    "wgmma.mma_async.sync.aligned.m64n16k16.f32.bf16.bf16 "
    "{%0, %1, %2, %3, %4, %5, %6, %7}, "
    "%8, %9, p, 1, 1, 1, 0;\n}\n"
    : "+f"(d[0]), "+f"(d[1]), "+f"(d[2]), "+f"(d[3]), "+f"(d[4]), "+f"(d[5]), "+f"(d[6]), "+f"(d[7])
    : "l"(da), "l"(db), "r"(scale_d));
}

__device__ __forceinline__ void wgmma_qk0(float (&d)[32], uint32_t a0, uint32_t a1, uint32_t a2, uint32_t a3, uint64_t db) {
  asm volatile("{\n.reg .pred p;\nsetp.ne.b32 p, 0, 0;\n"
    "wgmma.mma_async.sync.aligned.m64n64k16.f32.bf16.bf16 "
    "{%0, %1, %2, %3, %4, %5, %6, %7, %8, %9, %10, %11, %12, %13, %14, %15, %16, %17, %18, %19, %20, %21, %22, %23, %24, %25, %26, %27, %28, %29, %30, %31}, "
    "{%32, %33, %34, %35}, %36, p, 1, 1, 0;\n}\n"
    : "=f"(d[0]), "=f"(d[1]), "=f"(d[2]), "=f"(d[3]), "=f"(d[4]), "=f"(d[5]), "=f"(d[6]), "=f"(d[7]), "=f"(d[8]), "=f"(d[9]), "=f"(d[10]), "=f"(d[11]), "=f"(d[12]), "=f"(d[13]), "=f"(d[14]), "=f"(d[15]), "=f"(d[16]), "=f"(d[17]), "=f"(d[18]), "=f"(d[19]), "=f"(d[20]), "=f"(d[21]), "=f"(d[22]), "=f"(d[23]), "=f"(d[24]), "=f"(d[25]), "=f"(d[26]), "=f"(d[27]), "=f"(d[28]), "=f"(d[29]), "=f"(d[30]), "=f"(d[31])
    : "r"(a0), "r"(a1), "r"(a2), "r"(a3), "l"(db));
}
__device__ __forceinline__ void wgmma_pv0(float (&d)[96], uint32_t a0, uint32_t a1, uint32_t a2, uint32_t a3, uint64_t db) {
  asm volatile("{\n.reg .pred p;\nsetp.ne.b32 p, 0, 0;\n"
    "wgmma.mma_async.sync.aligned.m64n192k16.f32.bf16.bf16 "
    "{%0, %1, %2, %3, %4, %5, %6, %7, %8, %9, %10, %11, %12, %13, %14, %15, %16, %17, %18, %19, %20, %21, %22, %23, %24, %25, %26, %27, %28, %29, %30, %31, %32, %33, %34, %35, %36, %37, %38, %39, %40, %41, %42, %43, %44, %45, %46, %47, %48, %49, %50, %51, %52, %53, %54, %55, %56, %57, %58, %59, %60, %61, %62, %63, %64, %65, %66, %67, %68, %69, %70, %71, %72, %73, %74, %75, %76, %77, %78, %79, %80, %81, %82, %83, %84, %85, %86, %87, %88, %89, %90, %91, %92, %93, %94, %95}, "
    "{%96, %97, %98, %99}, %100, p, 1, 1, 1;\n}\n"
    : "=f"(d[0]), "=f"(d[1]), "=f"(d[2]), "=f"(d[3]), "=f"(d[4]), "=f"(d[5]), "=f"(d[6]), "=f"(d[7]), "=f"(d[8]), "=f"(d[9]), "=f"(d[10]), "=f"(d[11]), "=f"(d[12]), "=f"(d[13]), "=f"(d[14]), "=f"(d[15]), "=f"(d[16]), "=f"(d[17]), "=f"(d[18]), "=f"(d[19]), "=f"(d[20]), "=f"(d[21]), "=f"(d[22]), "=f"(d[23]), "=f"(d[24]), "=f"(d[25]), "=f"(d[26]), "=f"(d[27]), "=f"(d[28]), "=f"(d[29]), "=f"(d[30]), "=f"(d[31]), "=f"(d[32]), "=f"(d[33]), "=f"(d[34]), "=f"(d[35]), "=f"(d[36]), "=f"(d[37]), "=f"(d[38]), "=f"(d[39]), "=f"(d[40]), "=f"(d[41]), "=f"(d[42]), "=f"(d[43]), "=f"(d[44]), "=f"(d[45]), "=f"(d[46]), "=f"(d[47]), "=f"(d[48]), "=f"(d[49]), "=f"(d[50]), "=f"(d[51]), "=f"(d[52]), "=f"(d[53]), "=f"(d[54]), "=f"(d[55]), "=f"(d[56]), "=f"(d[57]), "=f"(d[58]), "=f"(d[59]), "=f"(d[60]), "=f"(d[61]), "=f"(d[62]), "=f"(d[63]), "=f"(d[64]), "=f"(d[65]), "=f"(d[66]), "=f"(d[67]), "=f"(d[68]), "=f"(d[69]), "=f"(d[70]), "=f"(d[71]), "=f"(d[72]), "=f"(d[73]), "=f"(d[74]), "=f"(d[75]), "=f"(d[76]), "=f"(d[77]), "=f"(d[78]), "=f"(d[79]), "=f"(d[80]), "=f"(d[81]), "=f"(d[82]), "=f"(d[83]), "=f"(d[84]), "=f"(d[85]), "=f"(d[86]), "=f"(d[87]), "=f"(d[88]), "=f"(d[89]), "=f"(d[90]), "=f"(d[91]), "=f"(d[92]), "=f"(d[93]), "=f"(d[94]), "=f"(d[95])
    : "r"(a0), "r"(a1), "r"(a2), "r"(a3), "l"(db));
}
__device__ __forceinline__ void wgmma_qkT0(float (&d)[8], uint64_t da, uint64_t db) {
  asm volatile("{\n.reg .pred p;\nsetp.ne.b32 p, 0, 0;\n"
    "wgmma.mma_async.sync.aligned.m64n16k16.f32.bf16.bf16 "
    "{%0, %1, %2, %3, %4, %5, %6, %7}, "
    "%8, %9, p, 1, 1, 0, 0;\n}\n"
    : "=f"(d[0]), "=f"(d[1]), "=f"(d[2]), "=f"(d[3]), "=f"(d[4]), "=f"(d[5]), "=f"(d[6]), "=f"(d[7])
    : "l"(da), "l"(db));
}
__device__ __forceinline__ void wgmma_pvT0(float (&d)[8], uint64_t da, uint64_t db) {
  asm volatile("{\n.reg .pred p;\nsetp.ne.b32 p, 0, 0;\n"
    "wgmma.mma_async.sync.aligned.m64n16k16.f32.bf16.bf16 "
    "{%0, %1, %2, %3, %4, %5, %6, %7}, "
    "%8, %9, p, 1, 1, 1, 0;\n}\n"
    : "=f"(d[0]), "=f"(d[1]), "=f"(d[2]), "=f"(d[3]), "=f"(d[4]), "=f"(d[5]), "=f"(d[6]), "=f"(d[7])
    : "l"(da), "l"(db));
}

struct Round { int head, qrow, mc; };
__device__ __forceinline__ Round decode_round(uint32_t e, uint32_t rank) {
  Round o;
  o.mc = (e & 0x600) != 0x600;
  o.head = (e & 0x1ff) + (o.mc ? 0 : rank);
  o.qrow = (e >> 1 & 0x300) + (o.mc ? rank * 128 : 0);
  return o;
}

__device__ __forceinline__ uint32_t kdesc0(uint32_t s_kv) { return ((s_kv & 0x3FFFFu) >> 4) | (1u << 16); }
__device__ __forceinline__ uint32_t vdesc0(uint32_t s_kv) { return ((s_kv & 0x3FFFFu) >> 4) | ((uint32_t)(SLAB >> 4) << 16); }
constexpr uint64_t DESC_HI = ((uint64_t)(RGRP >> 4) << 32) | ((uint64_t)1 << 62);
constexpr uint64_t DESC_HI_PT = ((uint64_t)(1024 >> 4) << 32) | ((uint64_t)1 << 62);

__device__ __forceinline__ void issue_qk(float (&S)[32], const uint32_t (&Q)[48], uint32_t kdesc) {
  const uint64_t d = DESC_HI | kdesc;
  wgmma_qk0(S, Q[0], Q[1], Q[2], Q[3], d);
#pragma unroll
  for (int kk = 1; kk < 12; kk++)
    wgmma_qk(S, Q[kk * 4], Q[kk * 4 + 1], Q[kk * 4 + 2], Q[kk * 4 + 3], d + (uint64_t)((kk / 4) * (SLAB / 16) + (kk % 4) * 2), 1);
}
__device__ __forceinline__ void issue_qk32(float (&S)[32], const uint32_t (&Q)[48], uint32_t kdesc) {
  uint32_t d[12];
#pragma unroll
  for (int kk = 0; kk < 12; kk++) {
    d[kk] = kdesc + ((kk / 4) * (SLAB / 16) + (kk % 4) * 2);
    asm volatile("" : "+r"(d[kk]));
  }
  wgmma_qk0(S, Q[0], Q[1], Q[2], Q[3], DESC_HI | d[0]);
#pragma unroll
  for (int kk = 1; kk < 12; kk++) wgmma_qk(S, Q[kk * 4], Q[kk * 4 + 1], Q[kk * 4 + 2], Q[kk * 4 + 3], DESC_HI | d[kk], 1);
}
__device__ __forceinline__ void issue_qk3(float (&S)[32], const uint32_t (&Q)[48], uint32_t kdesc) {
  const uint64_t d = DESC_HI | kdesc;
  wgmma_qk0(S, Q[0], Q[1], Q[2], Q[3], d);
#pragma unroll
  for (int kk = 1; kk < 12; kk++) {
    if (kk % 4 == 0) wg_commit();
    wgmma_qk(S, Q[kk * 4], Q[kk * 4 + 1], Q[kk * 4 + 2], Q[kk * 4 + 3], d + (uint64_t)((kk / 4) * (SLAB / 16) + (kk % 4) * 2), 1);
  }
}
template <bool ACCUMULATE>
__device__ __forceinline__ void issue_pv(float (&O)[96], const uint32_t (&P)[16], uint32_t vdesc) {
  const uint64_t d = DESC_HI | vdesc;
  if (ACCUMULATE) wgmma_pv(O, P[0], P[1], P[2], P[3], d, 1);
  else wgmma_pv0(O, P[0], P[1], P[2], P[3], d);
#pragma unroll
  for (int kk = 1; kk < 4; kk++)
    wgmma_pv(O, P[kk * 4], P[kk * 4 + 1], P[kk * 4 + 2], P[kk * 4 + 3], d + (uint64_t)(kk * (2 * RGRP / 16)), 1);
}

template <int K0 = 0, int K1 = 12>
__device__ __forceinline__ void load_q(uint32_t (&Q)[48], uint32_t lane_addr) {
#pragma unroll
  for (int kk = K0; kk < K1; kk++)
    ldsm_x4((lane_addr ^ ((kk % 4) << 5)) + (kk / 4) * SLAB, Q[kk * 4], Q[kk * 4 + 1], Q[kk * 4 + 2], Q[kk * 4 + 3]);
}

__device__ __forceinline__ void scale_q(uint32_t (&Q)[48]) {
#pragma unroll
  for (int i = 0; i < 48; i++) {
    asm("mul.rn.bf16x2 %0, %1, %2;" : "=r"(Q[i]) : "r"(Q[i]), "r"(0x3DD53DD5u));
  }
  fence_regs(Q);
}
__device__ __forceinline__ void softmax_block(const float (&S)[32], uint32_t (&P)[16], float& l0, float& l1) {
#pragma unroll
  for (int i = 0; i < 8; i++) {
    const float a = ex2(S[4 * i + 0]);
    const float b = ex2(S[4 * i + 1]);
    const float c = ex2(S[4 * i + 2]);
    const float d = ex2(S[4 * i + 3]);
    l0 += a + b;
    l1 += c + d;
    P[2 * i] = pack_bf16(a, b);
    P[2 * i + 1] = pack_bf16(c, d);
  }
  fence_regs(P);
}

__device__ __forceinline__ void sums_put(uint32_t addr, float l0, float l1, uint32_t on) {
  asm volatile("{\n.reg .pred p;\nsetp.ne.u32 p, %3, 0;\n@p st.shared.v2.f32 [%0], {%1, %2};\n}\n" ::"r"(addr), "f"(l0), "f"(l1), "r"(on) : "memory");
}
__device__ __forceinline__ void sums_get(uint32_t addr, float& s0, float& s1) {
  float a, b, c, d, e, f, g, h;
  asm volatile("ld.shared.v4.f32 {%0, %1, %2, %3}, [%8];\nld.shared.v4.f32 {%4, %5, %6, %7}, [%8 + 16];\n"
               : "=f"(a), "=f"(b), "=f"(c), "=f"(d), "=f"(e), "=f"(f), "=f"(g), "=f"(h) : "r"(addr & ~31u) : "memory");
  s0 = (a + c) + (e + g);
  s1 = (b + d) + (f + h);
}

template <int K0, int K1>
__device__ __forceinline__ void epilogue_part(const float (&O)[96], float i0, float i1, uint32_t lane_addr) {
#pragma unroll
  for (int kk = K0; kk < K1; kk++) {
    const int b = kk * 8;
    stsm_x4((lane_addr ^ ((kk % 4) << 5)) + (kk / 4) * SLAB,
            pack_bf16(O[b] * i0, O[b + 1] * i0), pack_bf16(O[b + 2] * i1, O[b + 3] * i1),
            pack_bf16(O[b + 4] * i0, O[b + 5] * i0), pack_bf16(O[b + 6] * i1, O[b + 7] * i1));
  }
}
__device__ __forceinline__ void epilogue_done(uint32_t bar, int lane) {
  __syncwarp();
  if (lane == 0) mbar_arrive(bar);
}

__device__ __forceinline__ void redo_tile(const CUtensorMap* tmQ, const CUtensorMap* tmK, const CUtensorMap* tmV, const CUtensorMap* tmO,
                                          int head, int row, uint32_t qo, uint32_t kv, uint32_t lane_addr, uint32_t bar, uint32_t& phase,
                                          uint32_t wg_bar) {
  float O[96], S[32];
  uint32_t Q[48], P[16];
  uint64_t pol;
  asm volatile("createpolicy.fractional.L2::evict_normal.b64 %0, 1.0;" : "=l"(pol));
  const bool leader = (threadIdx.x & 127) == 0;
  if (leader) {
    mbar_expect_tx(bar, SLOT);
    tma_load(qo, tmQ, bar, row, head, pol);
  }
  mbar_wait(bar, phase);
  phase ^= 1;
  load_q(Q, lane_addr);
  float m0 = -INFINITY, m1 = -INFINITY, l0 = 0.f, l1 = 0.f;
#pragma unroll
  for (int i = 0; i < 96; i++) O[i] = 0.f;
#pragma unroll 1
  for (int j = 0; j < NBLK; j++) {
    asm volatile("bar.sync %0, 128;" ::"r"(wg_bar) : "memory");
    if (leader) {
      mbar_expect_tx(bar, 2 * SLOT);
      tma_load(kv, tmK, bar, j * BN, head, pol);
      tma_load(kv + SLOT, tmV, bar, j * BN, head, pol);
    }
    mbar_wait(bar, phase);
    phase ^= 1;
    wg_fence();
    issue_qk(S, Q, kdesc0(kv));
    wg_commit();
    wg_wait<0>();
    fence_regs(S);
    float n0 = m0, n1 = m1;
#pragma unroll
    for (int i = 0; i < 8; i++) {
      n0 = fmaxf(n0, fmaxf(S[4 * i], S[4 * i + 1]));
      n1 = fmaxf(n1, fmaxf(S[4 * i + 2], S[4 * i + 3]));
    }
#pragma unroll
    for (int o = 1; o < 4; o <<= 1) {
      n0 = fmaxf(n0, __shfl_xor_sync(0xffffffffu, n0, o));
      n1 = fmaxf(n1, __shfl_xor_sync(0xffffffffu, n1, o));
    }
    const float f0 = ex2((m0 - n0) * SCALE_LOG2), f1 = ex2((m1 - n1) * SCALE_LOG2);
    m0 = n0; m1 = n1;
    l0 *= f0; l1 *= f1;
#pragma unroll
    for (int i = 0; i < 24; i++) {
      O[4 * i] *= f0; O[4 * i + 1] *= f0; O[4 * i + 2] *= f1; O[4 * i + 3] *= f1;
    }
#pragma unroll
    for (int i = 0; i < 8; i++) {
      S[4 * i] = (S[4 * i] - m0) * SCALE_LOG2; S[4 * i + 1] = (S[4 * i + 1] - m0) * SCALE_LOG2;
      S[4 * i + 2] = (S[4 * i + 2] - m1) * SCALE_LOG2; S[4 * i + 3] = (S[4 * i + 3] - m1) * SCALE_LOG2;
    }
    softmax_block(S, P, l0, l1);
    fence_regs(O);
    wg_fence();
    issue_pv<true>(O, P, vdesc0(kv + SLOT));
    wg_commit();
    wg_wait<0>();
    fence_regs(O);
  }
#pragma unroll
  for (int o = 1; o < 4; o <<= 1) {
    l0 += __shfl_xor_sync(0xffffffffu, l0, o);
    l1 += __shfl_xor_sync(0xffffffffu, l1, o);
  }
  epilogue_part<0, 12>(O, rcp(l0), rcp(l1), lane_addr);
  asm volatile("fence.proxy.async.shared::cta;" ::: "memory");
  asm volatile("bar.sync %0, 128;" ::"r"(wg_bar) : "memory");
  if (leader) {
    for (int i = 0; i < 64 && row + i < SQ; i += OROWS) tma_store(tmO, qo + i / 8 * RGRP, row + i, head, pol);
    asm volatile("cp.async.bulk.commit_group;" ::: "memory");
    asm volatile("cp.async.bulk.wait_group 0;" ::: "memory");
  }
}

__device__ __forceinline__ void wg_barrier() { asm volatile("bar.sync 3, 128;" ::: "memory"); }

__device__ __forceinline__ void tail_reduce(float (&v)[4], uint32_t red, int warp, int lane) {
#pragma unroll
  for (int o = 4; o < 32; o <<= 1)
#pragma unroll
    for (int i = 0; i < 4; i++) v[i] += __shfl_xor_sync(0xffffffffu, v[i], o);
  if (lane < 4)
    asm volatile("st.shared.v4.f32 [%0], {%1, %2, %3, %4};" ::"r"(red + (warp * 4 + lane) * 16), "f"(v[0]), "f"(v[1]), "f"(v[2]), "f"(v[3]) : "memory");
  wg_barrier();
#pragma unroll
  for (int ww = 0; ww < 4; ww++) {
    float x0, x1, x2, x3;
    asm volatile("ld.shared.v4.f32 {%0, %1, %2, %3}, [%4];" : "=f"(x0), "=f"(x1), "=f"(x2), "=f"(x3) : "r"(red + (ww * 4 + (lane & 3)) * 16) : "memory");
    if (ww == 0) { v[0] = x0; v[1] = x1; v[2] = x2; v[3] = x3; }
    else { v[0] += x0; v[1] += x1; v[2] += x2; v[3] += x3; }
  }
}

__device__ __forceinline__ void tail_softmax(const float (&S)[8], float (&l)[4], uint32_t pt_addr) {
  float e[8];
#pragma unroll
  for (int i = 0; i < 8; i++) e[i] = ex2(S[i] * SCALE_LOG2);
  stsm_x4_trans(pt_addr, pack_bf16(e[0], e[1]), pack_bf16(e[2], e[3]), pack_bf16(e[4], e[5]), pack_bf16(e[6], e[7]));
  l[0] += e[0] + e[2]; l[1] += e[1] + e[3]; l[2] += e[4] + e[6]; l[3] += e[5] + e[7];
}

__device__ __forceinline__ void issue_qkT(float (&S8)[8], uint32_t kdesc, uint32_t qt_addr) {
  const uint64_t da = DESC_HI | kdesc;
  const uint64_t db = DESC_HI | (uint64_t)(((qt_addr & 0x3FFFFu) >> 4) | (1u << 16));
  wgmma_qkT0(S8, da, db);
#pragma unroll
  for (int kk = 1; kk < 12; kk++)
    wgmma_qkT(S8, da + (uint64_t)((kk / 4) * (SLAB / 16) + (kk % 4) * 2), db + (uint64_t)((kk / 4) * (SLAB / 16) + (kk % 4) * 2), 1);
}
template <bool ACCUMULATE>
__device__ __forceinline__ void issue_pvT(float (&O)[3][8], uint32_t vdesc, uint32_t pt_base) {
  const uint64_t da = DESC_HI | vdesc;
  const uint64_t db = DESC_HI_PT | (uint64_t)(((pt_base & 0x3FFFFu) >> 4) | (1u << 16));
#pragma unroll
  for (int kk = 0; kk < 4; kk++)
#pragma unroll
    for (int b = 0; b < 3; b++) {
      if (kk == 0 && !ACCUMULATE) wgmma_pvT0(O[b], da + (uint64_t)(b * (SLAB / 16)), db);
      else wgmma_pvT(O[b], da + (uint64_t)(b * (SLAB / 16) + kk * (2 * RGRP / 16)), db + (uint64_t)(kk * 2), 1);
    }
}

template <bool B> struct Bool { static constexpr bool value = B; };

constexpr int MAX_CLUSTERS = 72;
constexpr int MAX_ROUNDS = 32;
struct Schedule {
  uint32_t tails[MAX_CLUSTERS];
  uint16_t start[MAX_CLUSTERS + 1];
  uint16_t list[NROUNDS + 1];
};

#define TRACE_TILE()

__global__ void __cluster_dims__(2, 1, 1) __launch_bounds__(NTHREADS, 1)
attn_kernel(const __grid_constant__ CUtensorMap tmQ, const __grid_constant__ CUtensorMap tmQT, const __grid_constant__ CUtensorMap tmK,
            const __grid_constant__ CUtensorMap tmV, const __grid_constant__ CUtensorMap tmO, const __grid_constant__ Schedule sched) {
  extern __shared__ __align__(1024) uint8_t smem_raw[];
  const uint32_t c_entry = (uint32_t)clock();
  const uint32_t sbase = smem_u32(smem_raw);
  const uint32_t s_qo = sbase + OFF_QO;
  const uint32_t s_kv = sbase + OFF_KV;
  const uint32_t s_bar = sbase + OFF_BAR;
  const uint32_t bar_full = s_bar;
  const uint32_t bar_empty = s_bar + 8 * NSLOT;
  const uint32_t bar_qfull = s_bar + 16 * NSLOT;
  const uint32_t bar_ostg = bar_qfull + 16;
  const uint32_t bar_qreq = bar_ostg + 16;
  const uint32_t bar_redo = bar_qreq + 16;
  const uint32_t s_redo = bar_redo + 16;

  uint32_t rank;
  asm("mov.u32 %0, %%cluster_ctarank;" : "=r"(rank));
  const int cluster = blockIdx.x >> 1;
  auto get_rounds = [&](int& first, int& count) {
    int c = cluster;
    asm volatile("" : "+r"(c));
    first = sched.start[c];
    count = sched.start[c + 1] - first;
  };

  if (threadIdx.x == 0) {
    asm volatile("prefetch.tensormap [%0];" ::"l"(&tmK) : "memory");
    asm volatile("prefetch.tensormap [%0];" ::"l"(&tmQ) : "memory");
    asm volatile("prefetch.tensormap [%0];" ::"l"(&tmV) : "memory");
    for (int i = 0; i < 3; i++) mbar_init(bar_full + 8 * i, 1);
    for (int i = 0; i < 2; i++) mbar_init(bar_qfull + 8 * i, 1);
    asm volatile("fence.mbarrier_init.release.cluster;" ::: "memory");
    asm volatile("fence.proxy.async.shared::cta;" ::: "memory");
    const int head = cluster / 3, qrow = cluster % 3 * 256 + rank * 128;
    uint64_t polq, polk;
    asm volatile("createpolicy.fractional.L2::evict_first.b64 %0, 1.0;" : "=l"(polq));
    asm volatile("createpolicy.fractional.L2::evict_unchanged.b64 %0, 1.0;" : "=l"(polk));
    while ((uint32_t)clock() - c_entry < (uint32_t)(cluster / 3 * STAGGER)) {}
    mbar_expect_tx(bar_full, SLOT);
    tma_load(s_kv, &tmK, bar_full, 0, head, polk);
    mbar_expect_tx(bar_qfull, SLOT);
    tma_load(s_qo, &tmQ, bar_qfull, qrow, head, polq);
    mbar_expect_tx(bar_full + 8, SLOT);
    tma_load(s_kv + SLOT, &tmK, bar_full + 8, BN, head, polk);
    mbar_expect_tx(bar_full + 16, SLOT);
    tma_load(s_kv + 2 * SLOT, &tmV, bar_full + 16, 0, head, polk);
    mbar_expect_tx(bar_qfull + 8, SLOT);
    tma_load(s_qo + SLOT, &tmQ, bar_qfull + 8, qrow + 64, head, polq);
  } else if (threadIdx.x == 32) {
    for (int i = 0; i < NSLOT; i++) {
      if (i >= 3) mbar_init(bar_full + 8 * i, 1);
      mbar_init(bar_empty + 8 * i, 4);
    }
    for (int i = 0; i < 2; i++) {
      mbar_init(bar_ostg + 8 * i, 4);
      mbar_init(bar_qreq + 8 * i, 1);
      mbar_init(bar_redo + 8 * i, 1);
      asm volatile("st.shared.u32 [%0], %1;" ::"r"(s_redo + 4 * i), "r"(0) : "memory");
    }
    asm volatile("fence.mbarrier_init.release.cluster;" ::: "memory");
    asm volatile("fence.proxy.async.shared::cta;" ::: "memory");
  }
  __syncthreads();
  asm volatile("barrier.cluster.arrive.relaxed.aligned;\nbarrier.cluster.wait.aligned;" ::: "memory");

  const int wg = __shfl_sync(0xffffffffu, threadIdx.x >> 7, 0);
  const int warp = __shfl_sync(0xffffffffu, (threadIdx.x >> 5) & 3, 0);
  const int lane = threadIdx.x & 31;

  if (wg == 0) {
    asm volatile("setmaxnreg.dec.sync.aligned.u32 24;");
    int first_round, nrounds;
    get_rounds(first_round, nrounds);
    const int nblocks = nrounds * NBLK;
    if (warp == 0 && lane == 0) {
      uint64_t pol;
      asm volatile("createpolicy.fractional.L2::evict_unchanged.b64 %0, 1.0;" : "=l"(pol));
      uint32_t slot = 3, phase = 1;
      auto load = [&](const CUtensorMap* tm, int n, uint32_t owner) {
        const Round r = decode_round(sched.list[first_round + (n >> 3)], rank);
        mbar_wait_sleep(bar_empty + 8 * slot, phase);
        if (n < nblocks) {
          mbar_expect_tx(bar_full + 8 * slot, SLOT);
          if (!r.mc) tma_load(s_kv + slot * SLOT, tm, bar_full + 8 * slot, (n & 7) * BN, r.head, pol);
          else if (rank == owner) tma_load_mc(s_kv + slot * SLOT, tm, bar_full + 8 * slot, (n & 7) * BN, r.head, pol);
        }
        if (++slot == NSLOT) { slot = 0; phase ^= 1; }
      };
      auto request_q = [&](int n, int pos) {
        pos += (n & 7) * 2 + ((sched.list[first_round + (n >> 3)] & 0x8000) ? QREQT : 0);
        if (pos == QREQ0) mbar_arrive(bar_qreq);
        if (pos == QREQ1) mbar_arrive(bar_qreq + 8);
      };
      for (int n = 1; n < nblocks; n++) {
        load(&tmK, n + 1, 0);
        if (!(QREQ0 & QREQ1 & 1) || (QREQT & 1)) request_q(n, 0);
        load(&tmV, n, 1);
        if (((QREQ0 | QREQ1) & 1) || (QREQT & 1)) request_q(n, 1);
      }
      for (int i = 0; i < NSLOT; i++) {
        if (i != NSLOT - 2) mbar_wait_sleep(bar_empty + 8 * slot, phase);
        if (++slot == NSLOT) { slot = 0; phase ^= 1; }
      }
    } else if ((warp == 1 || warp == 2) && lane == 0) {
      const int w = warp - 1;
      uint64_t pol;
      asm volatile("createpolicy.fractional.L2::evict_first.b64 %0, 1.0;" : "=l"(pol));
      const uint32_t buf = s_qo + w * SLOT;
      mbar_wait_sleep(bar_ostg + 8 * w, 0);
      for (int t = 0; t < nrounds; t++) {
        if (t + 1 < nrounds) {
          const uint32_t e = sched.list[first_round + t + 1];
          const Round r = decode_round(e, rank);
          const bool tail = w == 1 && (e & 0x8000);
          mbar_wait_sleep(bar_qreq + 8 * w, t & 1);
          mbar_expect_tx(bar_qfull + 8 * w, tail ? 3 * 2048 : SLOT);
          tma_load(tail ? sbase + OFF_QT : buf, tail ? &tmQT : &tmQ, bar_qfull + 8 * w, r.qrow + w * 64, r.head, pol);
        } else {
          mbar_arrive(bar_qfull + 8 * w);
        }
        const Round r = decode_round(sched.list[first_round + t], rank);
        const int row0 = r.qrow + w * 64;
        const int nrows = row0 + 64 <= SQ ? 64 : SQ % 64;
        mbar_wait_sleep(bar_ostg + 8 * w, ~t & 1);
        asm volatile("fence.proxy.async.shared::cta;" ::: "memory");
#pragma unroll 1
        for (int i = 0; i < nrows; i += OROWS) {
          tma_store(&tmO, buf + i / 8 * RGRP, row0 + i, r.head, pol);
          asm volatile("cp.async.bulk.commit_group;" ::: "memory");
          if (t + 1 < nrounds) asm volatile("cp.async.bulk.wait_group.read 0;" ::: "memory");
        }
      }
      asm volatile("cp.async.bulk.wait_group 0;" ::: "memory");
      mbar_arrive(bar_redo + 8 * w);
    } else if (warp == 3) {
      uint32_t slot = 1, phase = 0;
      for (int n = 0; n < nblocks; n++) {
        if (n + 1 < nblocks) mbar_wait(bar_full + 8 * slot, phase);
        if (++slot == NSLOT) { slot = 0; phase ^= 1; }
        mbar_wait(bar_full + 8 * slot, phase);
        if (++slot == NSLOT) { slot = 0; phase ^= 1; }
        asm volatile("bar.sync 1, 288;" ::: "memory");
        asm volatile("bar.arrive 2, 288;" ::: "memory");
        TRACE_TILE();
      }
    }
  } else {
    asm volatile("setmaxnreg.inc.sync.aligned.u32 240;");
    const int w = wg - 1;
    int first_round, nrounds;
    get_rounds(first_round, nrounds);
    const int nblocks = nrounds * NBLK;
    float O[96], S[32];
    uint32_t Q[48], P0[16], P1[16];
    float l0 = 0.f, l1 = 0.f, inv0 = 1.f, inv1 = 1.f;
    uint32_t redo = 0;
    const uint32_t lane_addr = s_qo + w * SLOT + (warp * 2 + ((lane >> 3) & 1)) * RGRP + (lane & 7) * 128 + (((lane >> 4) ^ (lane & 7)) << 4);
    const uint32_t sum_addr = s_qo + w * SLOT + warp * 2 * RGRP + lane * 8;
    const uint32_t my_qfull = bar_qfull + 8 * w, my_ostg = bar_ostg + 8 * w;

    uint32_t empty_remote;
    asm("mapa.shared::cluster.u32 %0, %1, %2;" : "=r"(empty_remote) : "r"(bar_empty), "r"(threadIdx.x & 1));
    const bool releaser = (threadIdx.x & 127) < 2;
    auto release = [&](uint32_t s) {
      if (releaser) asm volatile("mbarrier.arrive.shared::cluster.b64 _, [%0];" ::"r"(empty_remote + s) : "memory");
    };
    uint32_t ks = 8, vs = 16, kp = 0, vp = 0;
    const uint32_t kd0 = kdesc0(s_kv), vd0 = vdesc0(s_kv);
    uint32_t kd = kd0 + ks * (SLOT / 128), vd = vd0 + vs * (SLOT / 128);
    auto advance = [&]() {
      kp = ks; vp = vs;
      ks = ks >= 8 * (NSLOT - 2) ? ks - 8 * (NSLOT - 2) : ks + 16;
      vs = vs >= 8 * (NSLOT - 2) ? vs - 8 * (NSLOT - 2) : vs + 16;
      kd = kd0 + ks * (SLOT / 128); vd = vd0 + vs * (SLOT / 128);
      asm volatile("" : "+r"(ks), "+r"(vs), "+r"(kd), "+r"(vd));
    };

    uint32_t tails = w == 1 ? sched.tails[cluster] : 0u;
    auto turn_wait = [&]() { asm volatile("bar.sync %0, 288;" ::"r"(1 + w) : "memory"); };
    auto turn_pass = [&]() { asm volatile("bar.arrive %0, 288;" ::"r"(2 - w) : "memory"); };
    if (w == 1) turn_pass();

    mbar_wait(my_qfull, 0);
    load_q(Q, lane_addr);
    scale_q(Q);
    mbar_wait(bar_full, 0);
    wg_fence();
    issue_qk(S, Q, kd0);
    wg_commit();
    wg_wait<0>();
    fence_regs(S);
    release(0);
    __syncwarp();
    if (lane == 0) mbar_arrive(my_ostg);
    bool pending = false;

    int n = 0;
    auto finish_sums = [&]() {
      float s0, s1;
      sums_get(sum_addr, s0, s1);
      inv0 = rcp(s0); inv1 = rcp(s1);
      l0 = l1 = 0.f;
      asm volatile("" : "+f"(inv0), "+f"(inv1)::"memory");
    };
    auto check_sums = [&](int t) { check_inv(inv0, inv1, redo, 1u << (t & 31)); };

    int exit_n = -1;
#pragma unroll 1
    while (true) {
#pragma unroll 1
      while (true) {
        const int j = n & 7;
        softmax_block(S, P0, l0, l1);
        asm volatile("" : "+f"(l0), "+f"(l1)::"memory");
        if (j != 0) {
          wg_wait<0>();
          release(vp);
          turn_wait();
          wg_fence();
          issue_qk3(S, Q, kd);
          wg_commit();
          issue_pv<true>(O, P0, vd);
          wg_commit();
          turn_pass();
          advance();
          if (j == 6) {
            mbar_wait(my_qfull, ((n >> 3) + 1) & 1);
            wg_wait<3>();
            load_q<0, 4>(Q, lane_addr);
            wg_wait<2>();
            load_q<4, 8>(Q, lane_addr);
          }
          wg_wait<1>();
          fence_regs(S);
          fence_regs(P1);
        } else {
          wg_wait<0>();
          fence_regs(O);
          fence_regs(P1);
          if (pending) {
            release(vp);
            epilogue_part<0, ESPLIT>(O, inv0, inv1, lane_addr);
          }
          turn_wait();
          wg_fence();
          issue_qk32(S, Q, kd);
          wg_commit();
          if (pending) {
            epilogue_part<ESPLIT, 12>(O, inv0, inv1, lane_addr);
            epilogue_done(my_ostg, lane);
          }
          wg_fence();
          issue_pv<false>(O, P0, vd);
          wg_commit();
          turn_pass();
          advance();
          check_sums((n >> 3) - 1);
          exit_n = ((tails & 2) || n + 8 == nblocks) ? n + 6 : -1;
          tails >>= 1;
          asm volatile("" : "+r"(exit_n), "+r"(tails), "+r"(redo));
          wg_wait<1>();
          fence_regs(S);
          pending = true;
        }
        release(kp);
        if (j == 6) load_q<8, 12>(Q, lane_addr);
        softmax_block(S, P1, l0, l1);
        sums_put(sum_addr, l0, l1, j == 6);
        wg_wait<0>();
        release(vp);
        if (j == 6) {
          scale_q(Q);
          if (n == exit_n) {
            turn_wait();
            wg_fence();
            issue_pv<true>(O, P1, vd);
            wg_commit();
            break;
          }
          asm volatile("" ::: "memory");
          turn_wait();
          wg_fence();
          issue_qk32(S, Q, kd);
          wg_commit();
          issue_pv<true>(O, P1, vd);
          wg_commit();
          turn_pass();
          advance();
          if (pending) finish_sums();
          wg_wait<1>();
        } else {
          turn_wait();
          wg_fence();
          issue_qk(S, Q, kd);
          wg_commit();
          issue_pv<true>(O, P1, vd);
          wg_commit();
          turn_pass();
          advance();
          wg_wait<1>();
        }
        fence_regs(S);
        fence_regs(P0);
        release(kp);
        n += 2;
      }
      if (n + 2 == nblocks) {
        if (w == 0) turn_pass();
        finish_sums();
        check_sums(n >> 3);
        wg_wait<0>();
        fence_regs(O);
        release(vs);
        epilogue_part<0, 12>(O, inv0, inv1, lane_addr);
        epilogue_done(my_ostg, lane);
        break;
      }
      const int t = n >> 3;
      const uint32_t qt = sbase + OFF_QT, pt = sbase + OFF_PT, red = sbase + OFF_RED;
      const uint32_t tl = ((lane & 7) + (lane >> 4) * 8) * 128 + (((warp * 2 + ((lane >> 3) & 1)) ^ (lane & 7)) << 4);
      const bool tlast = n + 10 == nblocks;
      float lt[4] = {0.f, 0.f, 0.f, 0.f};
      float ST[8], OT[3][8];
      wg_fence();
      issue_qkT(ST, kd, qt);
      wg_commit();
      turn_pass();
      finish_sums();
      check_sums(t);
      wg_wait<0>();
      fence_regs(ST);
      fence_regs(O);
      release(ks);
      release(vs);
      advance();
      epilogue_part<0, NT_SPLIT>(O, inv0, inv1, lane_addr);
      if (NT_SPLIT == 12) epilogue_done(my_ostg, lane);
      tail_softmax(ST, lt, pt + tl);
      auto tail_step = [&](auto first_c, int jj) {
        constexpr bool FIRST = decltype(first_c)::value;
        asm volatile("fence.proxy.async.shared::cta;" ::: "memory");
        turn_wait();
        wg_fence();
        issue_qkT(ST, kd, qt);
        wg_commit();
        issue_pvT<!FIRST>(OT, vd, pt + (jj & 1) * 2048);
        wg_commit();
        turn_pass();
        advance();
        wg_wait<1>();
        fence_regs(ST);
        release(kp);
        tail_softmax(ST, lt, pt + (~jj & 1) * 2048 + tl);
        wg_wait<0>();
        fence_regs(OT[0]); fence_regs(OT[1]); fence_regs(OT[2]);
        release(vp);
      };
      tail_step(Bool<true>(), 0);
      if (NT_SPLIT < 12) {
        epilogue_part<NT_SPLIT, 12>(O, inv0, inv1, lane_addr);
        epilogue_done(my_ostg, lane);
      }
#pragma unroll 1
      for (int jj = 1; jj < 7; jj++) tail_step(Bool<false>(), jj);
      mbar_wait(my_qfull, t & 1);
      load_q(Q, lane_addr);
      scale_q(Q);
      tail_reduce(lt, red, warp, lane);
#pragma unroll
      for (int i = 0; i < 4; i++) lt[i] = rcp(lt[i]);
      check_inv(lt[0], lt[1], redo, 1u << ((t + 1) & 31));
      check_inv(lt[2], lt[3], redo, 1u << ((t + 1) & 31));
      inv0 = inv1 = 1.f;
      asm volatile("fence.proxy.async.shared::cta;" ::: "memory");
      turn_wait();
      wg_fence();
      issue_pvT<true>(OT, vd, pt + 2048);
      wg_commit();
      issue_qk(S, Q, kd);
      wg_commit();
      if (!tlast) turn_pass();
      wg_wait<1>();
      fence_regs(OT[0]); fence_regs(OT[1]); fence_regs(OT[2]);
      release(vs);
#pragma unroll
      for (int b = 0; b < 3; b++)
        stsm_x4_trans(s_qo + SLOT + b * SLAB + tl + (lane >> 4) * (RGRP - 1024),
                      pack_bf16(OT[b][0] * lt[0], OT[b][1] * lt[1]), pack_bf16(OT[b][2] * lt[0], OT[b][3] * lt[1]),
                      pack_bf16(OT[b][4] * lt[2], OT[b][5] * lt[3]), pack_bf16(OT[b][6] * lt[2], OT[b][7] * lt[3]));
      epilogue_done(my_ostg, lane);
      wg_wait<0>();
      fence_regs(S);
      if (tlast) break;
      release(ks);
      advance();
#pragma unroll
      for (int i = 0; i < 96; i++) O[i] = 0.f;
      pending = false;
      n += 10;
      tails >>= 1;
    }
    if (redo) asm volatile("red.shared.or.b32 [%0], %1;" ::"r"(s_redo + 4 * w), "r"(redo) : "memory");
    asm volatile("bar.sync 4, 256;" ::: "memory");
    asm volatile("ld.shared.u32 %0, [%1];" : "=r"(redo) : "r"(s_redo + 4 * w) : "memory");
    redo = __shfl_sync(0xffffffffu, redo, 0);
    if (redo) {
      mbar_wait_sleep(bar_redo + 8 * w, 0);
      asm volatile("bar.sync %0, 128;" ::"r"(5 + w) : "memory");
      uint32_t phase = 1;
      get_rounds(first_round, nrounds);
      uint32_t rank;
      asm volatile("mov.u32 %0, %%cluster_ctarank;" : "=r"(rank));
#pragma unroll 1
      for (int t = 0; t < nrounds; t++) {
        if (!(redo >> (t & 31) & 1)) continue;
        const Round r = decode_round(sched.list[first_round + t], rank);
        redo_tile(&tmQ, &tmK, &tmV, &tmO, r.head, r.qrow + w * 64, s_qo + w * SLOT, s_kv + 2 * w * SLOT, lane_addr, bar_redo + 8 * w, phase, 5 + w);
      }
    }
  }
}

typedef CUresult (*EncodeFn)(CUtensorMap*, CUtensorMapDataType, cuuint32_t, void*, const cuuint64_t*, const cuuint64_t*,
                             const cuuint32_t*, const cuuint32_t*, CUtensorMapInterleave, CUtensorMapSwizzle,
                             CUtensorMapL2promotion, CUtensorMapFloatOOBfill);

void make_map(EncodeFn fn, CUtensorMap* tm, const void* ptr, int rows, int box_rows) {
  cuuint64_t dims[5] = {64, 8, 3, (cuuint64_t)rows / 8, (cuuint64_t)NHEADS};
  cuuint64_t strides[4] = {HD * 2, 128, 8 * HD * 2, (cuuint64_t)rows * HD * 2};
  cuuint32_t box[5] = {64, 8, 3, (cuuint32_t)box_rows / 8, 1};
  cuuint32_t estr[5] = {1, 1, 1, 1, 1};
  fn(tm, CU_TENSOR_MAP_DATA_TYPE_BFLOAT16, 5, const_cast<void*>(ptr), dims, strides, box, estr,
     CU_TENSOR_MAP_INTERLEAVE_NONE, CU_TENSOR_MAP_SWIZZLE_128B, CU_TENSOR_MAP_L2_PROMOTION_L2_128B, CU_TENSOR_MAP_FLOAT_OOB_FILL_NONE);
}

#define COST_N 12690
#define COST_T 10800
#define COST_TN 12720
#define TAIL_LATE 36
#define TAIL_MAX 60
#define HEAVY_STEP 3
static_assert(MAX_CLUSTERS / 3 * STAGGER < COST_T, "the first wave has to be handed out in the order of the clusters");
void make_schedule(Schedule& s, int nclusters) {
  static uint16_t lists[MAX_CLUSTERS][NROUNDS];
  int cnt[MAX_CLUSTERS] = {0}, len[MAX_CLUSTERS], ntail[MAX_CLUSTERS] = {0}, quota[MAX_CLUSTERS] = {0};
  long long busy[MAX_CLUSTERS], fin[MAX_CLUSTERS];
  const int ntails = NROUNDS / 7, base = NROUNDS / nclusters, nheavy = NROUNDS % nclusters;
  const int step = nheavy * HEAVY_STEP <= nclusters ? HEAVY_STEP : 1;
  for (int c = 0; c < nclusters; c++) {
    len[c] = base + (c % step == 0 && c / step < nheavy);
    busy[c] = c / 3 * STAGGER;
    fin[c] = busy[c] + (long long)len[c] * COST_N;
  }
  for (int k = 0; k < ntails; k++) {
    int c = -1;
    for (int i = 0; i < nclusters; i++)
      if (quota[i] < len[i] / 2 && (c < 0 || fin[i] > fin[c])) c = i;
    quota[c]++;
    fin[c] -= 2 * COST_N - COST_T - COST_TN;
  }
  int gn = 0, gt = 3;
  for (int k = 0; k < NROUNDS; k++) {
    int c = -1;
    for (int i = 0; i < nclusters; i++)
      if (cnt[i] < len[i] && (c < 0 || busy[i] < busy[c])) c = i;
    const bool after_tail = cnt[c] > 0 && (lists[c][cnt[c] - 1] & 0x8000);
    const bool may_t = cnt[c] > 0 && !after_tail;
    const int left = len[c] - cnt[c], q = quota[c] - ntail[c];
    const bool due = (long long)(gt / 7) * quota[c] * 8 >= (long long)(ntail[c] * 8 + (c * 5 & 7)) * ntails;
    bool tail = may_t && q > 0 && (2 * q > left || (gn - gt >= TAIL_LATE && due) || gn - gt >= TAIL_MAX);
    if (4 * quota[c] >= len[c]) {
      const int m = len[c] - 1, phase = c / step * 11 % m;
      tail = may_t && q > 0 && (2 * q > left || (cnt[c] * quota[c] + phase) / m > ntail[c]);
    }
    if (gt >= NROUNDS) tail = false;
    if (gn >= NROUNDS) tail = true;
    const int g = tail ? gt : gn;
    if (tail) { gt += 7; ntail[c]++; }
    else { gn++; if (gn % 7 == 3) gn++; }
    const bool form_t = tail && may_t;
    lists[c][cnt[c]++] = (uint16_t)(g | (form_t ? 0x8000 : 0));
    busy[c] += form_t ? COST_T : after_tail ? COST_TN : COST_N;
  }
  bool use_tail = true;
  for (int c = 0; c < nclusters; c++) if (cnt[c] > MAX_ROUNDS) use_tail = false;
  if (!use_tail) for (int c = 0; c < nclusters; c++) for (int i = 0; i < cnt[c]; i++) lists[c][i] &= 0x7fff;
  int pos = 0;
  for (int c = 0; c < nclusters; c++) {
    s.start[c] = (uint16_t)pos;
    s.tails[c] = 0;
    for (int i = 0; i < cnt[c]; i++) {
      if (lists[c][i] & 0x8000) s.tails[c] |= 1u << i;
      const int g = lists[c][i] & 0x7ff, p = g / 7, r = g % 7;
      s.list[pos++] = (uint16_t)((2 * p + (r > 3)) | (r & 3) << 9 | (lists[c][i] & 0x8000));
    }
  }
  for (int c = nclusters; c <= MAX_CLUSTERS; c++) s.start[c] = (uint16_t)pos;
  s.list[NROUNDS] = 0;
}

}

extern "C" void kernel_launch(void* const* d_in, const int* in_sizes, int n_in, void* d_out, int out_size) {
  static EncodeFn encode = nullptr;
  static int nclusters = 0;
  static Schedule sched;
  if (!encode) {
    void* fn = nullptr;
    cudaDriverEntryPointQueryResult qr;
    cudaGetDriverEntryPoint("cuTensorMapEncodeTiled", &fn, cudaEnableDefault, &qr);
    encode = (EncodeFn)fn;
    int dev = 0, nsm = 0;
    cudaGetDevice(&dev);
    cudaDeviceGetAttribute(&nsm, cudaDevAttrMultiProcessorCount, dev);
    nclusters = nsm / 2 < MAX_CLUSTERS ? nsm / 2 : MAX_CLUSTERS;
    make_schedule(sched, nclusters);
    cudaFuncSetAttribute(attn_kernel, cudaFuncAttributeMaxDynamicSharedMemorySize, SMEM_BYTES);
  }
  CUtensorMap tmQ, tmQT, tmK, tmV, tmO;
  make_map(encode, &tmQ, d_in[0], SQ, 64);
  make_map(encode, &tmQT, d_in[0], SQ, 16);
  make_map(encode, &tmK, d_in[1], SK, 64);
  make_map(encode, &tmV, d_in[2], SK, 64);
  make_map(encode, &tmO, d_out, SQ, OROWS);
  attn_kernel<<<2 * nclusters, NTHREADS, SMEM_BYTES>>>(tmQ, tmQT, tmK, tmV, tmO, sched);
}
```

```cpp
#include <cuda_runtime.h>
#include <cuda_bf16.h>
#include <cuda.h>
#include <stdint.h>

namespace {

constexpr int NHEADS = 512;
constexpr int SQ = 848;
constexpr int SK = 512;
constexpr int HD = 192;
constexpr int BN = 64;
constexpr int NBLK = SK / BN;
constexpr int SLOT = 64 * HD * 2;
constexpr int SLAB = 1024;
constexpr int RGRP = 3 * SLAB;
constexpr int NSLOT = 7;
constexpr int NROUNDS = (NHEADS / 2) * 7;
constexpr int NTHREADS = 384;
constexpr int OFF_QO = 0;
constexpr int OFF_KV = 2 * SLOT;
constexpr int OFF_QT = (2 + NSLOT) * SLOT;
constexpr int OFF_PT = OFF_QT + 3 * 2048;
constexpr int OFF_RED = OFF_PT + 2 * 2048;
constexpr int OFF_BAR = OFF_RED + 256;
constexpr int SMEM_BYTES = OFF_BAR + 256;

#define ESPLIT 8
#define OROWS 16
#define STAGGER 250
#define NT_SPLIT 4
#define QREQ0 12
#define QREQ1 14
constexpr uint32_t WAIT_LIMIT = 1u << 18;
#define SUSPEND 20000
constexpr uint32_t SUSPEND_NS = SUSPEND;

constexpr float SCALE_LOG2 = 0.07216878364870322f * 1.4426950408889634f;
__device__ __forceinline__ void check_inv(float a, float b, uint32_t& mask, uint32_t bit) {
  asm("{\n.reg .pred p;\nsetp.ge.f32 p, %1, 0f1F800000;\nsetp.le.and.f32 p, %1, 0f53800000, p;\n"
      "setp.ge.and.f32 p, %2, 0f1F800000, p;\nsetp.le.and.f32 p, %2, 0f53800000, p;\n@!p or.b32 %0, %0, %3;\n}\n"
      : "+r"(mask) : "f"(a), "f"(b), "r"(bit));
}

__device__ __forceinline__ uint32_t smem_u32(const void* p) { return (uint32_t)__cvta_generic_to_shared(p); }
__device__ __forceinline__ void wg_fence() { asm volatile("wgmma.fence.sync.aligned;" ::: "memory"); }
__device__ __forceinline__ void wg_commit() { asm volatile("wgmma.commit_group.sync.aligned;" ::: "memory"); }
template <int N> __device__ __forceinline__ void wg_wait() { asm volatile("wgmma.wait_group.sync.aligned %0;" ::"n"(N) : "memory"); }
template <int N> __device__ __forceinline__ void fence_regs(float (&r)[N]) {
#pragma unroll
  for (int i = 0; i < N; i++) asm volatile("" : "+f"(r[i])::"memory");
}
template <int N> __device__ __forceinline__ void fence_regs(uint32_t (&r)[N]) {
#pragma unroll
  for (int i = 0; i < N; i++) asm volatile("" : "+r"(r[i])::"memory");
}

__device__ __forceinline__ void mbar_init(uint32_t bar, uint32_t cnt) {
  asm volatile("mbarrier.init.shared::cta.b64 [%0], %1;" ::"r"(bar), "r"(cnt));
}
__device__ __forceinline__ void mbar_expect_tx(uint32_t bar, uint32_t bytes) {
  asm volatile("mbarrier.arrive.expect_tx.shared::cta.b64 _, [%0], %1;" ::"r"(bar), "r"(bytes) : "memory");
}
__device__ __forceinline__ void mbar_arrive(uint32_t bar) {
  asm volatile("mbarrier.arrive.shared::cta.b64 _, [%0];" ::"r"(bar) : "memory");
}
__device__ __forceinline__ bool mbar_try(uint32_t bar, uint32_t parity) {
  uint32_t ok;
  asm volatile(
      "{\n.reg .pred p;\nmbarrier.try_wait.parity.shared::cta.b64 p, [%1], %2;\nselp.b32 %0, 1, 0, p;\n}\n"
      : "=r"(ok)
      : "r"(bar), "r"(parity)
      : "memory");
  return ok;
}
__device__ __forceinline__ bool mbar_try_sleep(uint32_t bar, uint32_t parity) {
  uint32_t ok;
  asm volatile(
      "{\n.reg .pred p;\nmbarrier.try_wait.parity.shared::cta.b64 p, [%1], %2, %3;\nselp.b32 %0, 1, 0, p;\n}\n"
      : "=r"(ok)
      : "r"(bar), "r"(parity), "r"(SUSPEND_NS)
      : "memory");
  return ok;
}
__device__ __forceinline__ void mbar_wait(uint32_t bar, uint32_t parity) {
  if (mbar_try(bar, parity)) return;
  for (uint32_t n = 0; n < WAIT_LIMIT; n++)
    if (mbar_try(bar, parity)) break;
}
__device__ __forceinline__ void mbar_wait_sleep(uint32_t bar, uint32_t parity) {
  for (uint32_t n = 0; n < WAIT_LIMIT; n++) {
    if (mbar_try_sleep(bar, parity)) break;
  }
}

__device__ __forceinline__ void tma_load(uint32_t dst, const CUtensorMap* tm, uint32_t bar, int row, int head, uint64_t pol) {
  asm volatile(
      "cp.async.bulk.tensor.5d.shared::cluster.global.mbarrier::complete_tx::bytes.L2::cache_hint"
      " [%0], [%1, {%3, %3, %3, %4, %5}], [%2], %6;" ::"r"(dst),
      "l"(tm), "r"(bar), "r"(0), "r"(row >> 3), "r"(head), "l"(pol)
      : "memory");
}
__device__ __forceinline__ void tma_load_mc(uint32_t dst, const CUtensorMap* tm, uint32_t bar, int row, int head, uint64_t pol) {
  asm volatile(
      "cp.async.bulk.tensor.5d.shared::cluster.global.mbarrier::complete_tx::bytes.multicast::cluster.L2::cache_hint"
      " [%0], [%1, {%3, %3, %3, %4, %5}], [%2], %7, %6;" ::"r"(dst),
      "l"(tm), "r"(bar), "r"(0), "r"(row >> 3), "r"(head), "l"(pol), "h"((uint16_t)3)
      : "memory");
}
__device__ __forceinline__ void tma_store(const CUtensorMap* tm, uint32_t src, int row, int head, uint64_t pol) {
  asm volatile(
      "cp.async.bulk.tensor.5d.global.shared::cta.bulk_group.L2::cache_hint"
      " [%0, {%2, %2, %2, %3, %4}], [%1], %5;" ::"l"(tm),
      "r"(src), "r"(0), "r"(row >> 3), "r"(head), "l"(pol)
      : "memory");
}
__device__ __forceinline__ void ldsm_x4(uint32_t addr, uint32_t& r0, uint32_t& r1, uint32_t& r2, uint32_t& r3) {
  asm volatile("ldmatrix.sync.aligned.m8n8.x4.shared.b16 {%0, %1, %2, %3}, [%4];"
               : "=r"(r0), "=r"(r1), "=r"(r2), "=r"(r3)
               : "r"(addr)
               : "memory");
}
__device__ __forceinline__ void stsm_x4(uint32_t addr, uint32_t r0, uint32_t r1, uint32_t r2, uint32_t r3) {
  asm volatile("stmatrix.sync.aligned.m8n8.x4.shared.b16 [%0], {%1, %2, %3, %4};" ::"r"(addr), "r"(r0), "r"(r1), "r"(r2), "r"(r3)
               : "memory");
}
__device__ __forceinline__ void stsm_x4_trans(uint32_t addr, uint32_t r0, uint32_t r1, uint32_t r2, uint32_t r3) {
  asm volatile("stmatrix.sync.aligned.m8n8.x4.trans.shared.b16 [%0], {%1, %2, %3, %4};" ::"r"(addr), "r"(r0), "r"(r1), "r"(r2), "r"(r3)
               : "memory");
}
__device__ __forceinline__ float ex2(float x) {
  float y;
  asm("ex2.approx.ftz.f32 %0, %1;" : "=f"(y) : "f"(x));
  return y;
}
__device__ __forceinline__ float rcp(float x) {
  float y;
  asm("rcp.approx.ftz.f32 %0, %1;" : "=f"(y) : "f"(x));
  return y;
}
__device__ __forceinline__ uint32_t pack_bf16(float lo, float hi) {
  uint32_t r;
  asm("cvt.rn.bf16x2.f32 %0, %1, %2;" : "=r"(r) : "f"(hi), "f"(lo));
  return r;
}
__device__ __forceinline__ void wgmma_qk(float (&d)[32], uint32_t a0, uint32_t a1, uint32_t a2, uint32_t a3, uint64_t db, int scale_d) {
  asm volatile("{\n.reg .pred p;\nsetp.ne.b32 p, %37, 0;\n"
    "wgmma.mma_async.sync.aligned.m64n64k16.f32.bf16.bf16 "
    "{%0, %1, %2, %3, %4, %5, %6, %7, %8, %9, %10, %11, %12, %13, %14, %15, %16, %17, %18, %19, %20, %21, %22, %23, %24, %25, %26, %27, %28, %29, %30, %31}, "
    "{%32, %33, %34, %35}, %36, p, 1, 1, 0;\n}\n"
    : "+f"(d[0]), "+f"(d[1]), "+f"(d[2]), "+f"(d[3]), "+f"(d[4]), "+f"(d[5]), "+f"(d[6]), "+f"(d[7]), "+f"(d[8]), "+f"(d[9]), "+f"(d[10]), "+f"(d[11]), "+f"(d[12]), "+f"(d[13]), "+f"(d[14]), "+f"(d[15]), "+f"(d[16]), "+f"(d[17]), "+f"(d[18]), "+f"(d[19]), "+f"(d[20]), "+f"(d[21]), "+f"(d[22]), "+f"(d[23]), "+f"(d[24]), "+f"(d[25]), "+f"(d[26]), "+f"(d[27]), "+f"(d[28]), "+f"(d[29]), "+f"(d[30]), "+f"(d[31])
    : "r"(a0), "r"(a1), "r"(a2), "r"(a3), "l"(db), "r"(scale_d));
}

__device__ __forceinline__ void wgmma_pv(float (&d)[96], uint32_t a0, uint32_t a1, uint32_t a2, uint32_t a3, uint64_t db, int scale_d) {
  asm volatile("{\n.reg .pred p;\nsetp.ne.b32 p, %101, 0;\n"
    "wgmma.mma_async.sync.aligned.m64n192k16.f32.bf16.bf16 "
    "{%0, %1, %2, %3, %4, %5, %6, %7, %8, %9, %10, %11, %12, %13, %14, %15, %16, %17, %18, %19, %20, %21, %22, %23, %24, %25, %26, %27, %28, %29, %30, %31, %32, %33, %34, %35, %36, %37, %38, %39, %40, %41, %42, %43, %44, %45, %46, %47, %48, %49, %50, %51, %52, %53, %54, %55, %56, %57, %58, %59, %60, %61, %62, %63, %64, %65, %66, %67, %68, %69, %70, %71, %72, %73, %74, %75, %76, %77, %78, %79, %80, %81, %82, %83, %84, %85, %86, %87, %88, %89, %90, %91, %92, %93, %94, %95}, "
    "{%96, %97, %98, %99}, %100, p, 1, 1, 1;\n}\n"
    : "+f"(d[0]), "+f"(d[1]), "+f"(d[2]), "+f"(d[3]), "+f"(d[4]), "+f"(d[5]), "+f"(d[6]), "+f"(d[7]), "+f"(d[8]), "+f"(d[9]), "+f"(d[10]), "+f"(d[11]), "+f"(d[12]), "+f"(d[13]), "+f"(d[14]), "+f"(d[15]), "+f"(d[16]), "+f"(d[17]), "+f"(d[18]), "+f"(d[19]), "+f"(d[20]), "+f"(d[21]), "+f"(d[22]), "+f"(d[23]), "+f"(d[24]), "+f"(d[25]), "+f"(d[26]), "+f"(d[27]), "+f"(d[28]), "+f"(d[29]), "+f"(d[30]), "+f"(d[31]), "+f"(d[32]), "+f"(d[33]), "+f"(d[34]), "+f"(d[35]), "+f"(d[36]), "+f"(d[37]), "+f"(d[38]), "+f"(d[39]), "+f"(d[40]), "+f"(d[41]), "+f"(d[42]), "+f"(d[43]), "+f"(d[44]), "+f"(d[45]), "+f"(d[46]), "+f"(d[47]), "+f"(d[48]), "+f"(d[49]), "+f"(d[50]), "+f"(d[51]), "+f"(d[52]), "+f"(d[53]), "+f"(d[54]), "+f"(d[55]), "+f"(d[56]), "+f"(d[57]), "+f"(d[58]), "+f"(d[59]), "+f"(d[60]), "+f"(d[61]), "+f"(d[62]), "+f"(d[63]), "+f"(d[64]), "+f"(d[65]), "+f"(d[66]), "+f"(d[67]), "+f"(d[68]), "+f"(d[69]), "+f"(d[70]), "+f"(d[71]), "+f"(d[72]), "+f"(d[73]), "+f"(d[74]), "+f"(d[75]), "+f"(d[76]), "+f"(d[77]), "+f"(d[78]), "+f"(d[79]), "+f"(d[80]), "+f"(d[81]), "+f"(d[82]), "+f"(d[83]), "+f"(d[84]), "+f"(d[85]), "+f"(d[86]), "+f"(d[87]), "+f"(d[88]), "+f"(d[89]), "+f"(d[90]), "+f"(d[91]), "+f"(d[92]), "+f"(d[93]), "+f"(d[94]), "+f"(d[95])
    : "r"(a0), "r"(a1), "r"(a2), "r"(a3), "l"(db), "r"(scale_d));
}

__device__ __forceinline__ void wgmma_qkT(float (&d)[8], uint64_t da, uint64_t db, int scale_d) {
  asm volatile("{\n.reg .pred p;\nsetp.ne.b32 p, %10, 0;\n"
    "wgmma.mma_async.sync.aligned.m64n16k16.f32.bf16.bf16 "
    "{%0, %1, %2, %3, %4, %5, %6, %7}, "
    "%8, %9, p, 1, 1, 0, 0;\n}\n"
    : "+f"(d[0]), "+f"(d[1]), "+f"(d[2]), "+f"(d[3]), "+f"(d[4]), "+f"(d[5]), "+f"(d[6]), "+f"(d[7])
    : "l"(da), "l"(db), "r"(scale_d));
}
__device__ __forceinline__ void wgmma_pvT(float (&d)[8], uint64_t da, uint64_t db, int scale_d) {
  asm volatile("{\n.reg .pred p;\nsetp.ne.b32 p, %10, 0;\n"
    "wgmma.mma_async.sync.aligned.m64n16k16.f32.bf16.bf16 "
    "{%0, %1, %2, %3, %4, %5, %6, %7}, "
    "%8, %9, p, 1, 1, 1, 0;\n}\n"
    : "+f"(d[0]), "+f"(d[1]), "+f"(d[2]), "+f"(d[3]), "+f"(d[4]), "+f"(d[5]), "+f"(d[6]), "+f"(d[7])
    : "l"(da), "l"(db), "r"(scale_d));
}

__device__ __forceinline__ void wgmma_qk0(float (&d)[32], uint32_t a0, uint32_t a1, uint32_t a2, uint32_t a3, uint64_t db) {
  asm volatile("{\n.reg .pred p;\nsetp.ne.b32 p, 0, 0;\n"
    "wgmma.mma_async.sync.aligned.m64n64k16.f32.bf16.bf16 "
    "{%0, %1, %2, %3, %4, %5, %6, %7, %8, %9, %10, %11, %12, %13, %14, %15, %16, %17, %18, %19, %20, %21, %22, %23, %24, %25, %26, %27, %28, %29, %30, %31}, "
    "{%32, %33, %34, %35}, %36, p, 1, 1, 0;\n}\n"
    : "=f"(d[0]), "=f"(d[1]), "=f"(d[2]), "=f"(d[3]), "=f"(d[4]), "=f"(d[5]), "=f"(d[6]), "=f"(d[7]), "=f"(d[8]), "=f"(d[9]), "=f"(d[10]), "=f"(d[11]), "=f"(d[12]), "=f"(d[13]), "=f"(d[14]), "=f"(d[15]), "=f"(d[16]), "=f"(d[17]), "=f"(d[18]), "=f"(d[19]), "=f"(d[20]), "=f"(d[21]), "=f"(d[22]), "=f"(d[23]), "=f"(d[24]), "=f"(d[25]), "=f"(d[26]), "=f"(d[27]), "=f"(d[28]), "=f"(d[29]), "=f"(d[30]), "=f"(d[31])
    : "r"(a0), "r"(a1), "r"(a2), "r"(a3), "l"(db));
}
__device__ __forceinline__ void wgmma_pv0(float (&d)[96], uint32_t a0, uint32_t a1, uint32_t a2, uint32_t a3, uint64_t db) {
  asm volatile("{\n.reg .pred p;\nsetp.ne.b32 p, 0, 0;\n"
    "wgmma.mma_async.sync.aligned.m64n192k16.f32.bf16.bf16 "
    "{%0, %1, %2, %3, %4, %5, %6, %7, %8, %9, %10, %11, %12, %13, %14, %15, %16, %17, %18, %19, %20, %21, %22, %23, %24, %25, %26, %27, %28, %29, %30, %31, %32, %33, %34, %35, %36, %37, %38, %39, %40, %41, %42, %43, %44, %45, %46, %47, %48, %49, %50, %51, %52, %53, %54, %55, %56, %57, %58, %59, %60, %61, %62, %63, %64, %65, %66, %67, %68, %69, %70, %71, %72, %73, %74, %75, %76, %77, %78, %79, %80, %81, %82, %83, %84, %85, %86, %87, %88, %89, %90, %91, %92, %93, %94, %95}, "
    "{%96, %97, %98, %99}, %100, p, 1, 1, 1;\n}\n"
    : "=f"(d[0]), "=f"(d[1]), "=f"(d[2]), "=f"(d[3]), "=f"(d[4]), "=f"(d[5]), "=f"(d[6]), "=f"(d[7]), "=f"(d[8]), "=f"(d[9]), "=f"(d[10]), "=f"(d[11]), "=f"(d[12]), "=f"(d[13]), "=f"(d[14]), "=f"(d[15]), "=f"(d[16]), "=f"(d[17]), "=f"(d[18]), "=f"(d[19]), "=f"(d[20]), "=f"(d[21]), "=f"(d[22]), "=f"(d[23]), "=f"(d[24]), "=f"(d[25]), "=f"(d[26]), "=f"(d[27]), "=f"(d[28]), "=f"(d[29]), "=f"(d[30]), "=f"(d[31]), "=f"(d[32]), "=f"(d[33]), "=f"(d[34]), "=f"(d[35]), "=f"(d[36]), "=f"(d[37]), "=f"(d[38]), "=f"(d[39]), "=f"(d[40]), "=f"(d[41]), "=f"(d[42]), "=f"(d[43]), "=f"(d[44]), "=f"(d[45]), "=f"(d[46]), "=f"(d[47]), "=f"(d[48]), "=f"(d[49]), "=f"(d[50]), "=f"(d[51]), "=f"(d[52]), "=f"(d[53]), "=f"(d[54]), "=f"(d[55]), "=f"(d[56]), "=f"(d[57]), "=f"(d[58]), "=f"(d[59]), "=f"(d[60]), "=f"(d[61]), "=f"(d[62]), "=f"(d[63]), "=f"(d[64]), "=f"(d[65]), "=f"(d[66]), "=f"(d[67]), "=f"(d[68]), "=f"(d[69]), "=f"(d[70]), "=f"(d[71]), "=f"(d[72]), "=f"(d[73]), "=f"(d[74]), "=f"(d[75]), "=f"(d[76]), "=f"(d[77]), "=f"(d[78]), "=f"(d[79]), "=f"(d[80]), "=f"(d[81]), "=f"(d[82]), "=f"(d[83]), "=f"(d[84]), "=f"(d[85]), "=f"(d[86]), "=f"(d[87]), "=f"(d[88]), "=f"(d[89]), "=f"(d[90]), "=f"(d[91]), "=f"(d[92]), "=f"(d[93]), "=f"(d[94]), "=f"(d[95])
    : "r"(a0), "r"(a1), "r"(a2), "r"(a3), "l"(db));
}
__device__ __forceinline__ void wgmma_qkT0(float (&d)[8], uint64_t da, uint64_t db) {
  asm volatile("{\n.reg .pred p;\nsetp.ne.b32 p, 0, 0;\n"
    "wgmma.mma_async.sync.aligned.m64n16k16.f32.bf16.bf16 "
    "{%0, %1, %2, %3, %4, %5, %6, %7}, "
    "%8, %9, p, 1, 1, 0, 0;\n}\n"
    : "=f"(d[0]), "=f"(d[1]), "=f"(d[2]), "=f"(d[3]), "=f"(d[4]), "=f"(d[5]), "=f"(d[6]), "=f"(d[7])
    : "l"(da), "l"(db));
}
__device__ __forceinline__ void wgmma_pvT0(float (&d)[8], uint64_t da, uint64_t db) {
  asm volatile("{\n.reg .pred p;\nsetp.ne.b32 p, 0, 0;\n"
    "wgmma.mma_async.sync.aligned.m64n16k16.f32.bf16.bf16 "
    "{%0, %1, %2, %3, %4, %5, %6, %7}, "
    "%8, %9, p, 1, 1, 1, 0;\n}\n"
    : "=f"(d[0]), "=f"(d[1]), "=f"(d[2]), "=f"(d[3]), "=f"(d[4]), "=f"(d[5]), "=f"(d[6]), "=f"(d[7])
    : "l"(da), "l"(db));
}

struct Round { int head, qrow, mc; };
__device__ __forceinline__ Round decode_round(uint32_t e, uint32_t rank) {
  Round o;
  o.mc = (e & 0x600) != 0x600;
  o.head = (e & 0x1ff) + (o.mc ? 0 : rank);
  o.qrow = (e >> 1 & 0x300) + (o.mc ? rank * 128 : 0);
  return o;
}

__device__ __forceinline__ uint32_t kdesc0(uint32_t s_kv) { return ((s_kv & 0x3FFFFu) >> 4) | (1u << 16); }
__device__ __forceinline__ uint32_t vdesc0(uint32_t s_kv) { return ((s_kv & 0x3FFFFu) >> 4) | ((uint32_t)(SLAB >> 4) << 16); }
constexpr uint64_t DESC_HI = ((uint64_t)(RGRP >> 4) << 32) | ((uint64_t)1 << 62);
constexpr uint64_t DESC_HI_PT = ((uint64_t)(1024 >> 4) << 32) | ((uint64_t)1 << 62);

__device__ __forceinline__ void issue_qk(float (&S)[32], const uint32_t (&Q)[48], uint32_t kdesc) {
  const uint64_t d = DESC_HI | kdesc;
  wgmma_qk0(S, Q[0], Q[1], Q[2], Q[3], d);
#pragma unroll
  for (int kk = 1; kk < 12; kk++)
    wgmma_qk(S, Q[kk * 4], Q[kk * 4 + 1], Q[kk * 4 + 2], Q[kk * 4 + 3], d + (uint64_t)((kk / 4) * (SLAB / 16) + (kk % 4) * 2), 1);
}
__device__ __forceinline__ void issue_qk32(float (&S)[32], const uint32_t (&Q)[48], uint32_t kdesc) {
  uint32_t d[12];
#pragma unroll
  for (int kk = 0; kk < 12; kk++) {
    d[kk] = kdesc + ((kk / 4) * (SLAB / 16) + (kk % 4) * 2);
    asm volatile("" : "+r"(d[kk]));
  }
  wgmma_qk0(S, Q[0], Q[1], Q[2], Q[3], DESC_HI | d[0]);
#pragma unroll
  for (int kk = 1; kk < 12; kk++) wgmma_qk(S, Q[kk * 4], Q[kk * 4 + 1], Q[kk * 4 + 2], Q[kk * 4 + 3], DESC_HI | d[kk], 1);
}
__device__ __forceinline__ void issue_qk3(float (&S)[32], const uint32_t (&Q)[48], uint32_t kdesc) {
  const uint64_t d = DESC_HI | kdesc;
  wgmma_qk0(S, Q[0], Q[1], Q[2], Q[3], d);
#pragma unroll
  for (int kk = 1; kk < 12; kk++) {
    if (kk % 4 == 0) wg_commit();
    wgmma_qk(S, Q[kk * 4], Q[kk * 4 + 1], Q[kk * 4 + 2], Q[kk * 4 + 3], d + (uint64_t)((kk / 4) * (SLAB / 16) + (kk % 4) * 2), 1);
  }
}
template <bool ACCUMULATE>
__device__ __forceinline__ void issue_pv(float (&O)[96], const uint32_t (&P)[16], uint32_t vdesc) {
  const uint64_t d = DESC_HI | vdesc;
  if (ACCUMULATE) wgmma_pv(O, P[0], P[1], P[2], P[3], d, 1);
  else wgmma_pv0(O, P[0], P[1], P[2], P[3], d);
#pragma unroll
  for (int kk = 1; kk < 4; kk++)
    wgmma_pv(O, P[kk * 4], P[kk * 4 + 1], P[kk * 4 + 2], P[kk * 4 + 3], d + (uint64_t)(kk * (2 * RGRP / 16)), 1);
}

template <int K0 = 0, int K1 = 12>
__device__ __forceinline__ void load_q(uint32_t (&Q)[48], uint32_t lane_addr) {
#pragma unroll
  for (int kk = K0; kk < K1; kk++)
    ldsm_x4((lane_addr ^ ((kk % 4) << 5)) + (kk / 4) * SLAB, Q[kk * 4], Q[kk * 4 + 1], Q[kk * 4 + 2], Q[kk * 4 + 3]);
}

__device__ __forceinline__ void scale_q(uint32_t (&Q)[48]) {
  constexpr uint32_t C2 = 0x3DD53DD5u;
#pragma unroll
  for (int i = 0; i < 48; i++) asm("mul.rn.bf16x2 %0, %1, %2;" : "=r"(Q[i]) : "r"(Q[i]), "r"(C2));
  fence_regs(Q);
}
__device__ __forceinline__ void softmax_block(const float (&S)[32], uint32_t (&P)[16], float& l0, float& l1) {
#pragma unroll
  for (int i = 0; i < 8; i++) {
    const float a = ex2(S[4 * i + 0]);
    const float b = ex2(S[4 * i + 1]);
    const float c = ex2(S[4 * i + 2]);
    const float d = ex2(S[4 * i + 3]);
    l0 += a + b;
    l1 += c + d;
    P[2 * i] = pack_bf16(a, b);
    P[2 * i + 1] = pack_bf16(c, d);
  }
  fence_regs(P);
}

__device__ __forceinline__ void sums_put(uint32_t addr, float l0, float l1, uint32_t on) {
  asm volatile("{\n.reg .pred p;\nsetp.ne.u32 p, %3, 0;\n@p st.shared.v2.f32 [%0], {%1, %2};\n}\n" ::"r"(addr), "f"(l0), "f"(l1), "r"(on) : "memory");
}
__device__ __forceinline__ void sums_get(uint32_t addr, float& s0, float& s1) {
  float a, b, c, d, e, f, g, h;
  asm volatile("ld.shared.v4.f32 {%0, %1, %2, %3}, [%8];\nld.shared.v4.f32 {%4, %5, %6, %7}, [%8 + 16];\n"
               : "=f"(a), "=f"(b), "=f"(c), "=f"(d), "=f"(e), "=f"(f), "=f"(g), "=f"(h) : "r"(addr & ~31u) : "memory");
  s0 = (a + c) + (e + g);
  s1 = (b + d) + (f + h);
}

template <int K0, int K1>
__device__ __forceinline__ void epilogue_part(const float (&O)[96], float i0, float i1, uint32_t lane_addr) {
#pragma unroll
  for (int kk = K0; kk < K1; kk++) {
    const int b = kk * 8;
    stsm_x4((lane_addr ^ ((kk % 4) << 5)) + (kk / 4) * SLAB,
            pack_bf16(O[b] * i0, O[b + 1] * i0), pack_bf16(O[b + 2] * i1, O[b + 3] * i1),
            pack_bf16(O[b + 4] * i0, O[b + 5] * i0), pack_bf16(O[b + 6] * i1, O[b + 7] * i1));
  }
}
__device__ __forceinline__ void epilogue_done(uint32_t bar, int lane) {
  __syncwarp();
  if (lane == 0) mbar_arrive(bar);
}

__device__ __forceinline__ void redo_tile(const CUtensorMap* tmQ, const CUtensorMap* tmK, const CUtensorMap* tmV, const CUtensorMap* tmO,
                                          int head, int row, uint32_t qo, uint32_t kv, uint32_t lane_addr, uint32_t bar, uint32_t& phase,
                                          uint32_t wg_bar) {
  float O[96], S[32];
  uint32_t Q[48], P[16];
  uint64_t pol;
  asm volatile("createpolicy.fractional.L2::evict_normal.b64 %0, 1.0;" : "=l"(pol));
  const bool leader = (threadIdx.x & 127) == 0;
  if (leader) {
    mbar_expect_tx(bar, SLOT);
    tma_load(qo, tmQ, bar, row, head, pol);
  }
  mbar_wait(bar, phase);
  phase ^= 1;
  load_q(Q, lane_addr);
  float m0 = -INFINITY, m1 = -INFINITY, l0 = 0.f, l1 = 0.f;
#pragma unroll
  for (int i = 0; i < 96; i++) O[i] = 0.f;
#pragma unroll 1
  for (int j = 0; j < NBLK; j++) {
    asm volatile("bar.sync %0, 128;" ::"r"(wg_bar) : "memory");
    if (leader) {
      mbar_expect_tx(bar, 2 * SLOT);
      tma_load(kv, tmK, bar, j * BN, head, pol);
      tma_load(kv + SLOT, tmV, bar, j * BN, head, pol);
    }
    mbar_wait(bar, phase);
    phase ^= 1;
    wg_fence();
    issue_qk(S, Q, kdesc0(kv));
    wg_commit();
    wg_wait<0>();
    fence_regs(S);
    float n0 = m0, n1 = m1;
#pragma unroll
    for (int i = 0; i < 8; i++) {
      n0 = fmaxf(n0, fmaxf(S[4 * i], S[4 * i + 1]));
      n1 = fmaxf(n1, fmaxf(S[4 * i + 2], S[4 * i + 3]));
    }
#pragma unroll
    for (int o = 1; o < 4; o <<= 1) {
      n0 = fmaxf(n0, __shfl_xor_sync(0xffffffffu, n0, o));
      n1 = fmaxf(n1, __shfl_xor_sync(0xffffffffu, n1, o));
    }
    const float f0 = ex2((m0 - n0) * SCALE_LOG2), f1 = ex2((m1 - n1) * SCALE_LOG2);
    m0 = n0; m1 = n1;
    l0 *= f0; l1 *= f1;
#pragma unroll
    for (int i = 0; i < 24; i++) {
      O[4 * i] *= f0; O[4 * i + 1] *= f0; O[4 * i + 2] *= f1; O[4 * i + 3] *= f1;
    }
#pragma unroll
    for (int i = 0; i < 8; i++) {
      S[4 * i] = (S[4 * i] - m0) * SCALE_LOG2; S[4 * i + 1] = (S[4 * i + 1] - m0) * SCALE_LOG2;
      S[4 * i + 2] = (S[4 * i + 2] - m1) * SCALE_LOG2; S[4 * i + 3] = (S[4 * i + 3] - m1) * SCALE_LOG2;
    }
    softmax_block(S, P, l0, l1);
    fence_regs(O);
    wg_fence();
    issue_pv<true>(O, P, vdesc0(kv + SLOT));
    wg_commit();
    wg_wait<0>();
    fence_regs(O);
  }
#pragma unroll
  for (int o = 1; o < 4; o <<= 1) {
    l0 += __shfl_xor_sync(0xffffffffu, l0, o);
    l1 += __shfl_xor_sync(0xffffffffu, l1, o);
  }
  epilogue_part<0, 12>(O, rcp(l0), rcp(l1), lane_addr);
  asm volatile("fence.proxy.async.shared::cta;" ::: "memory");
  asm volatile("bar.sync %0, 128;" ::"r"(wg_bar) : "memory");
  if (leader) {
    for (int i = 0; i < 64 && row + i < SQ; i += OROWS) tma_store(tmO, qo + i / 8 * RGRP, row + i, head, pol);
    asm volatile("cp.async.bulk.commit_group;" ::: "memory");
    asm volatile("cp.async.bulk.wait_group 0;" ::: "memory");
  }
}

__device__ __forceinline__ void wg_barrier() { asm volatile("bar.sync 3, 128;" ::: "memory"); }

__device__ __forceinline__ void tail_reduce(float (&v)[4], uint32_t red, int warp, int lane) {
#pragma unroll
  for (int o = 4; o < 32; o <<= 1)
#pragma unroll
    for (int i = 0; i < 4; i++) v[i] += __shfl_xor_sync(0xffffffffu, v[i], o);
  if (lane < 4)
    asm volatile("st.shared.v4.f32 [%0], {%1, %2, %3, %4};" ::"r"(red + (warp * 4 + lane) * 16), "f"(v[0]), "f"(v[1]), "f"(v[2]), "f"(v[3]) : "memory");
  wg_barrier();
#pragma unroll
  for (int ww = 0; ww < 4; ww++) {
    float x0, x1, x2, x3;
    asm volatile("ld.shared.v4.f32 {%0, %1, %2, %3}, [%4];" : "=f"(x0), "=f"(x1), "=f"(x2), "=f"(x3) : "r"(red + (ww * 4 + (lane & 3)) * 16) : "memory");
    if (ww == 0) { v[0] = x0; v[1] = x1; v[2] = x2; v[3] = x3; }
    else { v[0] += x0; v[1] += x1; v[2] += x2; v[3] += x3; }
  }
}

__device__ __forceinline__ void tail_softmax(const float (&S)[8], float (&l)[4], uint32_t pt_addr) {
  float e[8];
#pragma unroll
  for (int i = 0; i < 8; i++) e[i] = ex2(S[i] * SCALE_LOG2);
  stsm_x4_trans(pt_addr, pack_bf16(e[0], e[1]), pack_bf16(e[2], e[3]), pack_bf16(e[4], e[5]), pack_bf16(e[6], e[7]));
  l[0] += e[0] + e[2]; l[1] += e[1] + e[3]; l[2] += e[4] + e[6]; l[3] += e[5] + e[7];
}

__device__ __forceinline__ void issue_qkT(float (&S8)[8], uint32_t kdesc, uint32_t qt_addr) {
  const uint64_t da = DESC_HI | kdesc;
  const uint64_t db = DESC_HI | (uint64_t)(((qt_addr & 0x3FFFFu) >> 4) | (1u << 16));
  wgmma_qkT0(S8, da, db);
#pragma unroll
  for (int kk = 1; kk < 12; kk++)
    wgmma_qkT(S8, da + (uint64_t)((kk / 4) * (SLAB / 16) + (kk % 4) * 2), db + (uint64_t)((kk / 4) * (SLAB / 16) + (kk % 4) * 2), 1);
}
template <bool ACCUMULATE>
__device__ __forceinline__ void issue_pvT(float (&O)[3][8], uint32_t vdesc, uint32_t pt_base) {
  const uint64_t da = DESC_HI | vdesc;
  const uint64_t db = DESC_HI_PT | (uint64_t)(((pt_base & 0x3FFFFu) >> 4) | (1u << 16));
#pragma unroll
  for (int kk = 0; kk < 4; kk++)
#pragma unroll
    for (int b = 0; b < 3; b++) {
      if (kk == 0 && !ACCUMULATE) wgmma_pvT0(O[b], da + (uint64_t)(b * (SLAB / 16)), db);
      else wgmma_pvT(O[b], da + (uint64_t)(b * (SLAB / 16) + kk * (2 * RGRP / 16)), db + (uint64_t)(kk * 2), 1);
    }
}

template <bool B> struct Bool { static constexpr bool value = B; };

constexpr int MAX_CLUSTERS = 72;
constexpr int MAX_ROUNDS = 32;
struct Schedule {
  uint32_t tails[MAX_CLUSTERS];
  uint16_t start[MAX_CLUSTERS + 1];
  uint16_t list[NROUNDS + 1];
};

#define TRACE_TILE()

__global__ void __cluster_dims__(2, 1, 1) __launch_bounds__(NTHREADS, 1)
attn_kernel(const __grid_constant__ CUtensorMap tmQ, const __grid_constant__ CUtensorMap tmQT, const __grid_constant__ CUtensorMap tmK,
            const __grid_constant__ CUtensorMap tmV, const __grid_constant__ CUtensorMap tmO, const __grid_constant__ Schedule sched) {
  extern __shared__ __align__(1024) uint8_t smem_raw[];
  const uint32_t c_entry = (uint32_t)clock();
  const uint32_t sbase = smem_u32(smem_raw);
  const uint32_t s_qo = sbase + OFF_QO;
  const uint32_t s_kv = sbase + OFF_KV;
  const uint32_t s_bar = sbase + OFF_BAR;
  const uint32_t bar_full = s_bar;
  const uint32_t bar_empty = s_bar + 8 * NSLOT;
  const uint32_t bar_qfull = s_bar + 16 * NSLOT;
  const uint32_t bar_ostg = bar_qfull + 16;
  const uint32_t bar_qreq = bar_ostg + 16;
  const uint32_t bar_redo = bar_qreq + 16;
  const uint32_t s_redo = bar_redo + 16;

  uint32_t rank;
  asm("mov.u32 %0, %%cluster_ctarank;" : "=r"(rank));
  const int cluster = blockIdx.x >> 1;
  auto get_rounds = [&](int& first, int& count) {
    int c = cluster;
    asm volatile("" : "+r"(c));
    first = sched.start[c];
    count = sched.start[c + 1] - first;
  };

  if (threadIdx.x == 0) {
    asm volatile("prefetch.tensormap [%0];" ::"l"(&tmK) : "memory");
    asm volatile("prefetch.tensormap [%0];" ::"l"(&tmQ) : "memory");
    asm volatile("prefetch.tensormap [%0];" ::"l"(&tmV) : "memory");
    for (int i = 0; i < 3; i++) mbar_init(bar_full + 8 * i, 1);
    for (int i = 0; i < 2; i++) mbar_init(bar_qfull + 8 * i, 1);
    asm volatile("fence.mbarrier_init.release.cluster;" ::: "memory");
    asm volatile("fence.proxy.async.shared::cta;" ::: "memory");
    const int head = cluster / 3, qrow = cluster % 3 * 256 + rank * 128;
    uint64_t polq, polk;
    asm volatile("createpolicy.fractional.L2::evict_first.b64 %0, 1.0;" : "=l"(polq));
    asm volatile("createpolicy.fractional.L2::evict_unchanged.b64 %0, 1.0;" : "=l"(polk));
    while ((uint32_t)clock() - c_entry < (uint32_t)(cluster / 3 * STAGGER)) {}
    mbar_expect_tx(bar_full, SLOT);
    tma_load(s_kv, &tmK, bar_full, 0, head, polk);
    mbar_expect_tx(bar_qfull, SLOT);
    tma_load(s_qo, &tmQ, bar_qfull, qrow, head, polq);
    mbar_expect_tx(bar_full + 8, SLOT);
    tma_load(s_kv + SLOT, &tmK, bar_full + 8, BN, head, polk);
    mbar_expect_tx(bar_full + 16, SLOT);
    tma_load(s_kv + 2 * SLOT, &tmV, bar_full + 16, 0, head, polk);
    mbar_expect_tx(bar_qfull + 8, SLOT);
    tma_load(s_qo + SLOT, &tmQ, bar_qfull + 8, qrow + 64, head, polq);
  } else if (threadIdx.x == 32) {
    for (int i = 0; i < NSLOT; i++) {
      if (i >= 3) mbar_init(bar_full + 8 * i, 1);
      mbar_init(bar_empty + 8 * i, 4);
    }
    for (int i = 0; i < 2; i++) {
      mbar_init(bar_ostg + 8 * i, 4);
      mbar_init(bar_qreq + 8 * i, 1);
      mbar_init(bar_redo + 8 * i, 1);
      asm volatile("st.shared.u32 [%0], %1;" ::"r"(s_redo + 4 * i), "r"(0) : "memory");
    }
    asm volatile("fence.mbarrier_init.release.cluster;" ::: "memory");
    asm volatile("fence.proxy.async.shared::cta;" ::: "memory");
  }
  __syncthreads();
  asm volatile("barrier.cluster.arrive.relaxed.aligned;\nbarrier.cluster.wait.aligned;" ::: "memory");

  const int wg = __shfl_sync(0xffffffffu, threadIdx.x >> 7, 0);
  const int warp = __shfl_sync(0xffffffffu, (threadIdx.x >> 5) & 3, 0);
  const int lane = threadIdx.x & 31;

  if (wg == 0) {
    asm volatile("setmaxnreg.dec.sync.aligned.u32 24;");
    int first_round, nrounds;
    get_rounds(first_round, nrounds);
    const int nblocks = nrounds * NBLK;
    if (warp == 0 && lane == 0) {
      uint64_t pol;
      asm volatile("createpolicy.fractional.L2::evict_unchanged.b64 %0, 1.0;" : "=l"(pol));
      uint32_t slot = 3, phase = 1;
      auto load = [&](const CUtensorMap* tm, int n, uint32_t owner) {
        const Round r = decode_round(sched.list[first_round + (n >> 3)], rank);
        mbar_wait_sleep(bar_empty + 8 * slot, phase);
        if (n < nblocks) {
          mbar_expect_tx(bar_full + 8 * slot, SLOT);
          if (!r.mc) tma_load(s_kv + slot * SLOT, tm, bar_full + 8 * slot, (n & 7) * BN, r.head, pol);
          else if (rank == owner) tma_load_mc(s_kv + slot * SLOT, tm, bar_full + 8 * slot, (n & 7) * BN, r.head, pol);
        }
        if (++slot == NSLOT) { slot = 0; phase ^= 1; }
      };
      auto request_q = [&](int n, int pos) {
        pos += (n & 7) * 2;
        if (pos == QREQ0) mbar_arrive(bar_qreq);
        if (pos == QREQ1) mbar_arrive(bar_qreq + 8);
      };
      for (int n = 1; n < nblocks; n++) {
        load(&tmK, n + 1, 0);
        request_q(n, 0);
        load(&tmV, n, 1);
        request_q(n, 1);
      }
      for (int i = 0; i < NSLOT; i++) {
        if (i != NSLOT - 2) mbar_wait_sleep(bar_empty + 8 * slot, phase);
        if (++slot == NSLOT) { slot = 0; phase ^= 1; }
      }
    } else if ((warp == 1 || warp == 2) && lane == 0) {
      const int w = warp - 1;
      uint64_t pol;
      asm volatile("createpolicy.fractional.L2::evict_first.b64 %0, 1.0;" : "=l"(pol));
      const uint32_t buf = s_qo + w * SLOT;
      mbar_wait_sleep(bar_ostg + 8 * w, 0);
      asm volatile("prefetch.tensormap [%0];" ::"l"(w ? &tmQT : &tmO) : "memory");
      for (int t = 0; t < nrounds; t++) {
        if (t + 1 < nrounds) {
          const uint32_t e = sched.list[first_round + t + 1];
          const Round r = decode_round(e, rank);
          const bool tail = w == 1 && (e & 0x8000);
          mbar_wait_sleep(bar_qreq + 8 * w, t & 1);
          mbar_expect_tx(bar_qfull + 8 * w, tail ? 3 * 2048 : SLOT);
          tma_load(tail ? sbase + OFF_QT : buf, tail ? &tmQT : &tmQ, bar_qfull + 8 * w, r.qrow + w * 64, r.head, pol);
        } else {
          mbar_arrive(bar_qfull + 8 * w);
        }
        const Round r = decode_round(sched.list[first_round + t], rank);
        const int row0 = r.qrow + w * 64;
        const int nrows = row0 + 64 <= SQ ? 64 : SQ % 64;
        mbar_wait_sleep(bar_ostg + 8 * w, ~t & 1);
        asm volatile("fence.proxy.async.shared::cta;" ::: "memory");
#pragma unroll 1
        for (int i = 0; i < nrows; i += OROWS) {
          tma_store(&tmO, buf + i / 8 * RGRP, row0 + i, r.head, pol);
          asm volatile("cp.async.bulk.commit_group;" ::: "memory");
          if (t + 1 < nrounds) asm volatile("cp.async.bulk.wait_group.read 0;" ::: "memory");
        }
      }
      asm volatile("cp.async.bulk.wait_group 0;" ::: "memory");
      mbar_arrive(bar_redo + 8 * w);
    } else if (warp == 3) {
      uint32_t slot = 1, phase = 0;
      for (int n = 0; n < nblocks; n++) {
        if (n + 1 < nblocks) mbar_wait(bar_full + 8 * slot, phase);
        if (++slot == NSLOT) { slot = 0; phase ^= 1; }
        mbar_wait(bar_full + 8 * slot, phase);
        if (++slot == NSLOT) { slot = 0; phase ^= 1; }
        asm volatile("bar.sync 1, 288;" ::: "memory");
        asm volatile("bar.arrive 2, 288;" ::: "memory");
        TRACE_TILE();
      }
    }
  } else {
    asm volatile("setmaxnreg.inc.sync.aligned.u32 240;");
    const int w = wg - 1;
    int first_round, nrounds;
    get_rounds(first_round, nrounds);
    const int nblocks = nrounds * NBLK;
    float O[96], S[32];
    uint32_t Q[48], P0[16], P1[16];
    float l0 = 0.f, l1 = 0.f, inv0 = 1.f, inv1 = 1.f;
    uint32_t redo = 0;
    const uint32_t lane_addr = s_qo + w * SLOT + (warp * 2 + ((lane >> 3) & 1)) * RGRP + (lane & 7) * 128 + (((lane >> 4) ^ (lane & 7)) << 4);
    const uint32_t sum_addr = s_qo + w * SLOT + warp * 2 * RGRP + lane * 8;
    const uint32_t my_qfull = bar_qfull + 8 * w, my_ostg = bar_ostg + 8 * w;

    uint32_t empty_remote;
    asm("mapa.shared::cluster.u32 %0, %1, %2;" : "=r"(empty_remote) : "r"(bar_empty), "r"(threadIdx.x & 1));
    const bool releaser = (threadIdx.x & 127) < 2;
    auto release = [&](uint32_t s) {
      if (releaser) asm volatile("mbarrier.arrive.shared::cluster.b64 _, [%0];" ::"r"(empty_remote + s) : "memory");
    };
    uint32_t ks = 8, vs = 16, kp = 0, vp = 0;
    const uint32_t kd0 = kdesc0(s_kv), vd0 = vdesc0(s_kv);
    uint32_t kd = kd0 + ks * (SLOT / 128), vd = vd0 + vs * (SLOT / 128);
    auto advance = [&]() {
      kp = ks; vp = vs;
      ks = ks >= 8 * (NSLOT - 2) ? ks - 8 * (NSLOT - 2) : ks + 16;
      vs = vs >= 8 * (NSLOT - 2) ? vs - 8 * (NSLOT - 2) : vs + 16;
      kd = kd0 + ks * (SLOT / 128); vd = vd0 + vs * (SLOT / 128);
      asm volatile("" : "+r"(ks), "+r"(vs), "+r"(kd), "+r"(vd));
    };

    uint32_t tails = w == 1 ? sched.tails[cluster] : 0u;
    auto turn_wait = [&]() { asm volatile("bar.sync %0, 288;" ::"r"(1 + w) : "memory"); };
    auto turn_pass = [&]() { asm volatile("bar.arrive %0, 288;" ::"r"(2 - w) : "memory"); };
    if (w == 1) asm volatile("bar.arrive %0, 288;" ::"r"(1 + (tails & 1)) : "memory");

    mbar_wait(my_qfull, 0);
    load_q(Q, lane_addr);
    scale_q(Q);
    mbar_wait(bar_full, 0);
    wg_fence();
    issue_qk(S, Q, kd0);
    wg_commit();
    wg_wait<0>();
    fence_regs(S);
    release(0);
    __syncwarp();
    if (lane == 0) mbar_arrive(my_ostg);
    uint32_t pending = 0;

    int n = 0;
    auto finish_sums = [&]() {
      float s0, s1;
      sums_get(sum_addr, s0, s1);
      inv0 = rcp(s0); inv1 = rcp(s1);
      l0 = l1 = 0.f;
      asm volatile("" : "+f"(inv0), "+f"(inv1)::"memory");
    };
    auto check_sums = [&](int t) { check_inv(inv0, inv1, redo, 1u << (t & 31)); };

    int exit_n = -1;
#pragma unroll 1
    while (true) {
#pragma unroll 1
      while (true) {
        const int j = n & 7;
        softmax_block(S, P0, l0, l1);
        asm volatile("" : "+f"(l0), "+f"(l1)::"memory");
        if (j != 0) {
          wg_wait<0>();
          release(vp);
          turn_wait();
          wg_fence();
          issue_qk3(S, Q, kd);
          wg_commit();
          issue_pv<true>(O, P0, vd);
          wg_commit();
          turn_pass();
          advance();
          if (j == 6) {
            mbar_wait(my_qfull, ((n >> 3) + 1) & 1);
            wg_wait<3>();
            load_q<0, 4>(Q, lane_addr);
            wg_wait<2>();
            load_q<4, 8>(Q, lane_addr);
          }
          wg_wait<1>();
          fence_regs(S);
          fence_regs(P1);
        } else {
          wg_wait<0>();
          fence_regs(O);
          fence_regs(P1);
          if (pending) {
            release(vp);
            epilogue_part<0, ESPLIT>(O, inv0, inv1, lane_addr);
          }
          turn_wait();
          wg_fence();
          issue_qk32(S, Q, kd);
          wg_commit();
          if (pending) {
            epilogue_part<ESPLIT, 12>(O, inv0, inv1, lane_addr);
            epilogue_done(my_ostg, lane);
          }
          wg_fence();
          issue_pv<false>(O, P0, vd);
          wg_commit();
          turn_pass();
          advance();
          check_sums((n >> 3) - 1);
          exit_n = ((tails & 2) || n + 8 == nblocks) ? n + 6 : -1;
          tails >>= 1;
          asm volatile("" : "+r"(exit_n), "+r"(tails), "+r"(redo));
          wg_wait<1>();
          fence_regs(S);
          pending = true;
        }
        release(kp);
        if (j == 6) load_q<8, 12>(Q, lane_addr);
        softmax_block(S, P1, l0, l1);
        sums_put(sum_addr, l0, l1, j == 6);
        wg_wait<0>();
        release(vp);
        if (j == 6) {
          scale_q(Q);
          if (n == exit_n) {
            turn_wait();
            wg_fence();
            issue_pv<true>(O, P1, vd);
            wg_commit();
            break;
          }
          asm volatile("" ::: "memory");
          turn_wait();
          wg_fence();
          issue_qk32(S, Q, kd);
          wg_commit();
          issue_pv<true>(O, P1, vd);
          wg_commit();
          turn_pass();
          advance();
          if (pending) finish_sums();
          wg_wait<1>();
        } else {
          turn_wait();
          wg_fence();
          issue_qk(S, Q, kd);
          wg_commit();
          issue_pv<true>(O, P1, vd);
          wg_commit();
          turn_pass();
          advance();
          wg_wait<1>();
        }
        fence_regs(S);
        fence_regs(P0);
        release(kp);
        n += 2;
      }
      if (n + 2 == nblocks) {
        if (w == 0) turn_pass();
        finish_sums();
        check_sums(n >> 3);
        wg_wait<0>();
        fence_regs(O);
        release(vs);
        epilogue_part<0, 12>(O, inv0, inv1, lane_addr);
        epilogue_done(my_ostg, lane);
        break;
      }
      const int t = n >> 3;
      const uint32_t qt = sbase + OFF_QT, pt = sbase + OFF_PT, red = sbase + OFF_RED;
      const uint32_t tl = ((lane & 7) + (lane >> 4) * 8) * 128 + (((warp * 2 + ((lane >> 3) & 1)) ^ (lane & 7)) << 4);
      const bool tlast = n + 10 == nblocks;
      float lt[4] = {0.f, 0.f, 0.f, 0.f};
      float ST[8], OT[3][8];
      wg_fence();
      issue_qkT(ST, kd, qt);
      wg_commit();
      turn_pass();
      finish_sums();
      check_sums(t);
      wg_wait<0>();
      fence_regs(ST);
      fence_regs(O);
      release(ks);
      release(vs);
      advance();
      epilogue_part<0, NT_SPLIT>(O, inv0, inv1, lane_addr);
      if (NT_SPLIT == 12) epilogue_done(my_ostg, lane);
      tail_softmax(ST, lt, pt + tl);
      auto tail_step = [&](auto first_c, int jj) {
        constexpr bool FIRST = decltype(first_c)::value;
        asm volatile("fence.proxy.async.shared::cta;" ::: "memory");
        turn_wait();
        wg_fence();
        issue_qkT(ST, kd, qt);
        wg_commit();
        issue_pvT<!FIRST>(OT, vd, pt + (jj & 1) * 2048);
        wg_commit();
        turn_pass();
        advance();
        wg_wait<1>();
        fence_regs(ST);
        release(kp);
        tail_softmax(ST, lt, pt + (~jj & 1) * 2048 + tl);
        wg_wait<0>();
        fence_regs(OT[0]); fence_regs(OT[1]); fence_regs(OT[2]);
        release(vp);
      };
      tail_step(Bool<true>(), 0);
      if (NT_SPLIT < 12) {
        epilogue_part<NT_SPLIT, 12>(O, inv0, inv1, lane_addr);
        epilogue_done(my_ostg, lane);
      }
#pragma unroll 1
      for (int jj = 1; jj < 7; jj++) tail_step(Bool<false>(), jj);
      mbar_wait(my_qfull, t & 1);
      load_q(Q, lane_addr);
      scale_q(Q);
      tail_reduce(lt, red, warp, lane);
#pragma unroll
      for (int i = 0; i < 4; i++) lt[i] = rcp(lt[i]);
      check_inv(lt[0], lt[1], redo, 1u << ((t + 1) & 31));
      check_inv(lt[2], lt[3], redo, 1u << ((t + 1) & 31));
      inv0 = inv1 = 1.f;
      asm volatile("fence.proxy.async.shared::cta;" ::: "memory");
      turn_wait();
      wg_fence();
      issue_pvT<true>(OT, vd, pt + 2048);
      wg_commit();
      issue_qk(S, Q, kd);
      wg_commit();
      if (!tlast) turn_pass();
      wg_wait<1>();
      fence_regs(OT[0]); fence_regs(OT[1]); fence_regs(OT[2]);
      release(vs);
#pragma unroll
      for (int b = 0; b < 3; b++)
        stsm_x4_trans(s_qo + SLOT + b * SLAB + tl + (lane >> 4) * (RGRP - 1024),
                      pack_bf16(OT[b][0] * lt[0], OT[b][1] * lt[1]), pack_bf16(OT[b][2] * lt[0], OT[b][3] * lt[1]),
                      pack_bf16(OT[b][4] * lt[2], OT[b][5] * lt[3]), pack_bf16(OT[b][6] * lt[2], OT[b][7] * lt[3]));
      epilogue_done(my_ostg, lane);
      wg_wait<0>();
      fence_regs(S);
      if (tlast) break;
      release(ks);
      advance();
#pragma unroll
      for (int i = 0; i < 96; i++) O[i] = 0.f;
      pending = false;
      n += 10;
      tails >>= 1;
    }
    if (redo) asm volatile("red.shared.or.b32 [%0], %1;" ::"r"(s_redo + 4 * w), "r"(redo) : "memory");
    asm volatile("bar.sync 4, 256;" ::: "memory");
    asm volatile("ld.shared.u32 %0, [%1];" : "=r"(redo) : "r"(s_redo + 4 * w) : "memory");
    redo = __shfl_sync(0xffffffffu, redo, 0);
    if (redo) {
      mbar_wait_sleep(bar_redo + 8 * w, 0);
      asm volatile("bar.sync %0, 128;" ::"r"(5 + w) : "memory");
      uint32_t phase = 1;
      get_rounds(first_round, nrounds);
      uint32_t rank;
      asm volatile("mov.u32 %0, %%cluster_ctarank;" : "=r"(rank));
#pragma unroll 1
      for (int t = 0; t < nrounds; t++) {
        if (!(redo >> (t & 31) & 1)) continue;
        const Round r = decode_round(sched.list[first_round + t], rank);
        redo_tile(&tmQ, &tmK, &tmV, &tmO, r.head, r.qrow + w * 64, s_qo + w * SLOT, s_kv + 2 * w * SLOT, lane_addr, bar_redo + 8 * w, phase, 5 + w);
      }
    }
  }
}

typedef CUresult (*EncodeFn)(CUtensorMap*, CUtensorMapDataType, cuuint32_t, void*, const cuuint64_t*, const cuuint64_t*,
                             const cuuint32_t*, const cuuint32_t*, CUtensorMapInterleave, CUtensorMapSwizzle,
                             CUtensorMapL2promotion, CUtensorMapFloatOOBfill);

void make_map(EncodeFn fn, CUtensorMap* tm, const void* ptr, int rows, int box_rows) {
  cuuint64_t dims[5] = {64, 8, 3, (cuuint64_t)rows / 8, (cuuint64_t)NHEADS};
  cuuint64_t strides[4] = {HD * 2, 128, 8 * HD * 2, (cuuint64_t)rows * HD * 2};
  cuuint32_t box[5] = {64, 8, 3, (cuuint32_t)box_rows / 8, 1};
  cuuint32_t estr[5] = {1, 1, 1, 1, 1};
  fn(tm, CU_TENSOR_MAP_DATA_TYPE_BFLOAT16, 5, const_cast<void*>(ptr), dims, strides, box, estr,
     CU_TENSOR_MAP_INTERLEAVE_NONE, CU_TENSOR_MAP_SWIZZLE_128B, CU_TENSOR_MAP_L2_PROMOTION_L2_128B, CU_TENSOR_MAP_FLOAT_OOB_FILL_NONE);
}

#define COST_N 12690
#define COST_T 10800
#define COST_TN 12720
#define TAIL_LATE 36
#define TAIL_MAX 60
#define HEAVY_STEP 3
static_assert(MAX_CLUSTERS / 3 * STAGGER < COST_T, "the first wave has to be handed out in the order of the clusters");
void make_schedule(Schedule& s, int nclusters) {
  static uint16_t lists[MAX_CLUSTERS][NROUNDS];
  int cnt[MAX_CLUSTERS] = {0}, len[MAX_CLUSTERS], ntail[MAX_CLUSTERS] = {0}, quota[MAX_CLUSTERS] = {0};
  long long busy[MAX_CLUSTERS], fin[MAX_CLUSTERS];
  const int ntails = NROUNDS / 7, base = NROUNDS / nclusters, nheavy = NROUNDS % nclusters;
  const int step = nheavy * HEAVY_STEP <= nclusters ? HEAVY_STEP : 1;
  for (int c = 0; c < nclusters; c++) {
    len[c] = base + (c % step == 0 && c / step < nheavy);
    busy[c] = c / 3 * STAGGER;
    fin[c] = busy[c] + (long long)len[c] * COST_N;
  }
  for (int k = 0; k < ntails; k++) {
    int c = -1;
    for (int i = 0; i < nclusters; i++)
      if (quota[i] < len[i] / 2 && (c < 0 || fin[i] > fin[c])) c = i;
    quota[c]++;
    fin[c] -= 2 * COST_N - COST_T - COST_TN;
  }
  int gn = 0, gt = 3;
  for (int k = 0; k < NROUNDS; k++) {
    int c = -1;
    for (int i = 0; i < nclusters; i++)
      if (cnt[i] < len[i] && (c < 0 || busy[i] < busy[c])) c = i;
    const bool after_tail = cnt[c] > 0 && (lists[c][cnt[c] - 1] & 0x8000);
    const bool may_t = cnt[c] > 0 && !after_tail;
    const int left = len[c] - cnt[c], q = quota[c] - ntail[c];
    const bool due = (long long)(gt / 7) * quota[c] * 8 >= (long long)(ntail[c] * 8 + (c * 5 & 7)) * ntails;
    bool tail = may_t && q > 0 && (2 * q > left || (gn - gt >= TAIL_LATE && due) || gn - gt >= TAIL_MAX);
    if (4 * quota[c] >= len[c]) {
      const int m = len[c] - 1, phase = c / step * 11 % m;
      tail = may_t && q > 0 && (2 * q > left || (cnt[c] * quota[c] + phase) / m > ntail[c]);
    }
    if (gt >= NROUNDS) tail = false;
    if (gn >= NROUNDS) tail = true;
    const int g = tail ? gt : gn;
    if (tail) { gt += 7; ntail[c]++; }
    else { gn++; if (gn % 7 == 3) gn++; }
    const bool form_t = tail && may_t;
    lists[c][cnt[c]++] = (uint16_t)(g | (form_t ? 0x8000 : 0));
    busy[c] += form_t ? COST_T : after_tail ? COST_TN : COST_N;
  }
  bool use_tail = true;
  for (int c = 0; c < nclusters; c++) if (cnt[c] > MAX_ROUNDS) use_tail = false;
  if (!use_tail) for (int c = 0; c < nclusters; c++) for (int i = 0; i < cnt[c]; i++) lists[c][i] &= 0x7fff;
  int pos = 0;
  for (int c = 0; c < nclusters; c++) {
    s.start[c] = (uint16_t)pos;
    s.tails[c] = 0;
    for (int i = 0; i < cnt[c]; i++) {
      if (lists[c][i] & 0x8000) s.tails[c] |= 1u << i;
      const int g = lists[c][i] & 0x7ff, p = g / 7, r = g % 7;
      s.list[pos++] = (uint16_t)((2 * p + (r > 3)) | (r & 3) << 9 | (lists[c][i] & 0x8000));
    }
  }
  for (int c = nclusters; c <= MAX_CLUSTERS; c++) s.start[c] = (uint16_t)pos;
  s.list[NROUNDS] = 0;
}

}

extern "C" void kernel_launch(void* const* d_in, const int* in_sizes, int n_in, void* d_out, int out_size) {
  static EncodeFn encode = nullptr;
  static int nclusters = 0;
  static Schedule sched;
  if (!encode) {
    void* fn = nullptr;
    cudaDriverEntryPointQueryResult qr;
    cudaGetDriverEntryPoint("cuTensorMapEncodeTiled", &fn, cudaEnableDefault, &qr);
    encode = (EncodeFn)fn;
    int dev = 0, nsm = 0;
    cudaGetDevice(&dev);
    cudaDeviceGetAttribute(&nsm, cudaDevAttrMultiProcessorCount, dev);
    nclusters = nsm / 2 < MAX_CLUSTERS ? nsm / 2 : MAX_CLUSTERS;
    make_schedule(sched, nclusters);
    cudaFuncSetAttribute(attn_kernel, cudaFuncAttributeMaxDynamicSharedMemorySize, SMEM_BYTES);
  }
  CUtensorMap tmQ, tmQT, tmK, tmV, tmO;
  make_map(encode, &tmQ, d_in[0], SQ, 64);
  make_map(encode, &tmQT, d_in[0], SQ, 16);
  make_map(encode, &tmK, d_in[1], SK, 64);
  make_map(encode, &tmV, d_in[2], SK, 64);
  make_map(encode, &tmO, d_out, SQ, OROWS);
  attn_kernel<<<2 * nclusters, NTHREADS, SMEM_BYTES>>>(tmQ, tmQT, tmK, tmV, tmO, sched);
}
```

```cpp
#include <cuda_runtime.h>
#include <cuda_bf16.h>
#include <cuda.h>
#include <stdint.h>

namespace {

constexpr int NHEADS = 512;
constexpr int SQ = 848;
constexpr int SK = 512;
constexpr int HD = 192;
constexpr int BN = 64;
constexpr int NBLK = SK / BN;
constexpr int SLOT = 64 * HD * 2;
constexpr int SLAB = 1024;
constexpr int RGRP = 3 * SLAB;
constexpr int NSLOT = 7;
constexpr int NROUNDS = (NHEADS / 2) * 7;
constexpr int NTHREADS = 384;
constexpr int OFF_QO = 0;
constexpr int OFF_KV = 2 * SLOT;
constexpr int OFF_QT = (2 + NSLOT) * SLOT;
constexpr int OFF_PT = OFF_QT + 3 * 2048;
constexpr int OFF_RED = OFF_PT + 2 * 2048;
constexpr int OFF_BAR = OFF_RED + 256;
constexpr int SMEM_BYTES = OFF_BAR + 256;

#define ESPLIT 8
#define OROWS 16
#define STAGGER 250
#define NT_SPLIT 4
#define QREQ0 12
#define QREQ1 14
constexpr uint32_t WAIT_LIMIT = 1u << 18;
#define SUSPEND 20000
constexpr uint32_t SUSPEND_NS = SUSPEND;

constexpr float SCALE_LOG2 = 0.07216878364870322f * 1.4426950408889634f;
__device__ __forceinline__ void check_inv(float a, float b, uint32_t& mask, uint32_t bit) {
  asm("{\n.reg .pred p;\nsetp.ge.f32 p, %1, 0f1F800000;\nsetp.le.and.f32 p, %1, 0f53800000, p;\n"
      "setp.ge.and.f32 p, %2, 0f1F800000, p;\nsetp.le.and.f32 p, %2, 0f53800000, p;\n@!p or.b32 %0, %0, %3;\n}\n"
      : "+r"(mask) : "f"(a), "f"(b), "r"(bit));
}

__device__ __forceinline__ uint32_t smem_u32(const void* p) { return (uint32_t)__cvta_generic_to_shared(p); }
__device__ __forceinline__ void wg_fence() { asm volatile("wgmma.fence.sync.aligned;" ::: "memory"); }
__device__ __forceinline__ void wg_commit() { asm volatile("wgmma.commit_group.sync.aligned;" ::: "memory"); }
template <int N> __device__ __forceinline__ void wg_wait() { asm volatile("wgmma.wait_group.sync.aligned %0;" ::"n"(N) : "memory"); }
template <int N> __device__ __forceinline__ void fence_regs(float (&r)[N]) {
#pragma unroll
  for (int i = 0; i < N; i++) asm volatile("" : "+f"(r[i])::"memory");
}
template <int N> __device__ __forceinline__ void fence_regs(uint32_t (&r)[N]) {
#pragma unroll
  for (int i = 0; i < N; i++) asm volatile("" : "+r"(r[i])::"memory");
}

__device__ __forceinline__ void mbar_init(uint32_t bar, uint32_t cnt) {
  asm volatile("mbarrier.init.shared::cta.b64 [%0], %1;" ::"r"(bar), "r"(cnt));
}
__device__ __forceinline__ void mbar_expect_tx(uint32_t bar, uint32_t bytes) {
  asm volatile("mbarrier.arrive.expect_tx.shared::cta.b64 _, [%0], %1;" ::"r"(bar), "r"(bytes) : "memory");
}
__device__ __forceinline__ void mbar_arrive(uint32_t bar) {
  asm volatile("mbarrier.arrive.shared::cta.b64 _, [%0];" ::"r"(bar) : "memory");
}
__device__ __forceinline__ bool mbar_try(uint32_t bar, uint32_t parity) {
  uint32_t ok;
  asm volatile(
      "{\n.reg .pred p;\nmbarrier.try_wait.parity.shared::cta.b64 p, [%1], %2;\nselp.b32 %0, 1, 0, p;\n}\n"
      : "=r"(ok)
      : "r"(bar), "r"(parity)
      : "memory");
  return ok;
}
__device__ __forceinline__ bool mbar_try_sleep(uint32_t bar, uint32_t parity) {
  uint32_t ok;
  asm volatile(
      "{\n.reg .pred p;\nmbarrier.try_wait.parity.shared::cta.b64 p, [%1], %2, %3;\nselp.b32 %0, 1, 0, p;\n}\n"
      : "=r"(ok)
      : "r"(bar), "r"(parity), "r"(SUSPEND_NS)
      : "memory");
  return ok;
}
__device__ __forceinline__ void mbar_wait(uint32_t bar, uint32_t parity) {
  if (mbar_try(bar, parity)) return;
  for (uint32_t n = 0; n < WAIT_LIMIT; n++)
    if (mbar_try(bar, parity)) break;
}
__device__ __forceinline__ void mbar_wait_sleep(uint32_t bar, uint32_t parity) {
  for (uint32_t n = 0; n < WAIT_LIMIT; n++) {
    if (mbar_try_sleep(bar, parity)) break;
  }
}

__device__ __forceinline__ void tma_load(uint32_t dst, const CUtensorMap* tm, uint32_t bar, int row, int head, uint64_t pol) {
  asm volatile(
      "cp.async.bulk.tensor.5d.shared::cluster.global.mbarrier::complete_tx::bytes.L2::cache_hint"
      " [%0], [%1, {%3, %3, %3, %4, %5}], [%2], %6;" ::"r"(dst),
      "l"(tm), "r"(bar), "r"(0), "r"(row >> 3), "r"(head), "l"(pol)
      : "memory");
}
__device__ __forceinline__ void tma_load_mc(uint32_t dst, const CUtensorMap* tm, uint32_t bar, int row, int head, uint64_t pol) {
  asm volatile(
      "cp.async.bulk.tensor.5d.shared::cluster.global.mbarrier::complete_tx::bytes.multicast::cluster.L2::cache_hint"
      " [%0], [%1, {%3, %3, %3, %4, %5}], [%2], %7, %6;" ::"r"(dst),
      "l"(tm), "r"(bar), "r"(0), "r"(row >> 3), "r"(head), "l"(pol), "h"((uint16_t)3)
      : "memory");
}
__device__ __forceinline__ void tma_store(const CUtensorMap* tm, uint32_t src, int row, int head, uint64_t pol) {
  asm volatile(
      "cp.async.bulk.tensor.5d.global.shared::cta.bulk_group.L2::cache_hint"
      " [%0, {%2, %2, %2, %3, %4}], [%1], %5;" ::"l"(tm),
      "r"(src), "r"(0), "r"(row >> 3), "r"(head), "l"(pol)
      : "memory");
}
__device__ __forceinline__ void ldsm_x4(uint32_t addr, uint32_t& r0, uint32_t& r1, uint32_t& r2, uint32_t& r3) {
  asm volatile("ldmatrix.sync.aligned.m8n8.x4.shared.b16 {%0, %1, %2, %3}, [%4];"
               : "=r"(r0), "=r"(r1), "=r"(r2), "=r"(r3)
               : "r"(addr)
               : "memory");
}
__device__ __forceinline__ void stsm_x4(uint32_t addr, uint32_t r0, uint32_t r1, uint32_t r2, uint32_t r3) {
  asm volatile("stmatrix.sync.aligned.m8n8.x4.shared.b16 [%0], {%1, %2, %3, %4};" ::"r"(addr), "r"(r0), "r"(r1), "r"(r2), "r"(r3)
               : "memory");
}
__device__ __forceinline__ void stsm_x4_trans(uint32_t addr, uint32_t r0, uint32_t r1, uint32_t r2, uint32_t r3) {
  asm volatile("stmatrix.sync.aligned.m8n8.x4.trans.shared.b16 [%0], {%1, %2, %3, %4};" ::"r"(addr), "r"(r0), "r"(r1), "r"(r2), "r"(r3)
               : "memory");
}
__device__ __forceinline__ float ex2(float x) {
  float y;
  asm("ex2.approx.ftz.f32 %0, %1;" : "=f"(y) : "f"(x));
  return y;
}
__device__ __forceinline__ float rcp(float x) {
  float y;
  asm("rcp.approx.ftz.f32 %0, %1;" : "=f"(y) : "f"(x));
  return y;
}
__device__ __forceinline__ uint32_t pack_bf16(float lo, float hi) {
  uint32_t r;
  asm("cvt.rn.bf16x2.f32 %0, %1, %2;" : "=r"(r) : "f"(hi), "f"(lo));
  return r;
}
__device__ __forceinline__ void wgmma_qk(float (&d)[32], uint32_t a0, uint32_t a1, uint32_t a2, uint32_t a3, uint64_t db, int scale_d) {
  asm volatile("{\n.reg .pred p;\nsetp.ne.b32 p, %37, 0;\n"
    "wgmma.mma_async.sync.aligned.m64n64k16.f32.bf16.bf16 "
    "{%0, %1, %2, %3, %4, %5, %6, %7, %8, %9, %10, %11, %12, %13, %14, %15, %16, %17, %18, %19, %20, %21, %22, %23, %24, %25, %26, %27, %28, %29, %30, %31}, "
    "{%32, %33, %34, %35}, %36, p, 1, 1, 0;\n}\n"
    : "+f"(d[0]), "+f"(d[1]), "+f"(d[2]), "+f"(d[3]), "+f"(d[4]), "+f"(d[5]), "+f"(d[6]), "+f"(d[7]), "+f"(d[8]), "+f"(d[9]), "+f"(d[10]), "+f"(d[11]), "+f"(d[12]), "+f"(d[13]), "+f"(d[14]), "+f"(d[15]), "+f"(d[16]), "+f"(d[17]), "+f"(d[18]), "+f"(d[19]), "+f"(d[20]), "+f"(d[21]), "+f"(d[22]), "+f"(d[23]), "+f"(d[24]), "+f"(d[25]), "+f"(d[26]), "+f"(d[27]), "+f"(d[28]), "+f"(d[29]), "+f"(d[30]), "+f"(d[31])
    : "r"(a0), "r"(a1), "r"(a2), "r"(a3), "l"(db), "r"(scale_d));
}

__device__ __forceinline__ void wgmma_pv(float (&d)[96], uint32_t a0, uint32_t a1, uint32_t a2, uint32_t a3, uint64_t db, int scale_d) {
  asm volatile("{\n.reg .pred p;\nsetp.ne.b32 p, %101, 0;\n"
    "wgmma.mma_async.sync.aligned.m64n192k16.f32.bf16.bf16 "
    "{%0, %1, %2, %3, %4, %5, %6, %7, %8, %9, %10, %11, %12, %13, %14, %15, %16, %17, %18, %19, %20, %21, %22, %23, %24, %25, %26, %27, %28, %29, %30, %31, %32, %33, %34, %35, %36, %37, %38, %39, %40, %41, %42, %43, %44, %45, %46, %47, %48, %49, %50, %51, %52, %53, %54, %55, %56, %57, %58, %59, %60, %61, %62, %63, %64, %65, %66, %67, %68, %69, %70, %71, %72, %73, %74, %75, %76, %77, %78, %79, %80, %81, %82, %83, %84, %85, %86, %87, %88, %89, %90, %91, %92, %93, %94, %95}, "
    "{%96, %97, %98, %99}, %100, p, 1, 1, 1;\n}\n"
    : "+f"(d[0]), "+f"(d[1]), "+f"(d[2]), "+f"(d[3]), "+f"(d[4]), "+f"(d[5]), "+f"(d[6]), "+f"(d[7]), "+f"(d[8]), "+f"(d[9]), "+f"(d[10]), "+f"(d[11]), "+f"(d[12]), "+f"(d[13]), "+f"(d[14]), "+f"(d[15]), "+f"(d[16]), "+f"(d[17]), "+f"(d[18]), "+f"(d[19]), "+f"(d[20]), "+f"(d[21]), "+f"(d[22]), "+f"(d[23]), "+f"(d[24]), "+f"(d[25]), "+f"(d[26]), "+f"(d[27]), "+f"(d[28]), "+f"(d[29]), "+f"(d[30]), "+f"(d[31]), "+f"(d[32]), "+f"(d[33]), "+f"(d[34]), "+f"(d[35]), "+f"(d[36]), "+f"(d[37]), "+f"(d[38]), "+f"(d[39]), "+f"(d[40]), "+f"(d[41]), "+f"(d[42]), "+f"(d[43]), "+f"(d[44]), "+f"(d[45]), "+f"(d[46]), "+f"(d[47]), "+f"(d[48]), "+f"(d[49]), "+f"(d[50]), "+f"(d[51]), "+f"(d[52]), "+f"(d[53]), "+f"(d[54]), "+f"(d[55]), "+f"(d[56]), "+f"(d[57]), "+f"(d[58]), "+f"(d[59]), "+f"(d[60]), "+f"(d[61]), "+f"(d[62]), "+f"(d[63]), "+f"(d[64]), "+f"(d[65]), "+f"(d[66]), "+f"(d[67]), "+f"(d[68]), "+f"(d[69]), "+f"(d[70]), "+f"(d[71]), "+f"(d[72]), "+f"(d[73]), "+f"(d[74]), "+f"(d[75]), "+f"(d[76]), "+f"(d[77]), "+f"(d[78]), "+f"(d[79]), "+f"(d[80]), "+f"(d[81]), "+f"(d[82]), "+f"(d[83]), "+f"(d[84]), "+f"(d[85]), "+f"(d[86]), "+f"(d[87]), "+f"(d[88]), "+f"(d[89]), "+f"(d[90]), "+f"(d[91]), "+f"(d[92]), "+f"(d[93]), "+f"(d[94]), "+f"(d[95])
    : "r"(a0), "r"(a1), "r"(a2), "r"(a3), "l"(db), "r"(scale_d));
}

__device__ __forceinline__ void wgmma_qkT(float (&d)[8], uint64_t da, uint64_t db, int scale_d) {
  asm volatile("{\n.reg .pred p;\nsetp.ne.b32 p, %10, 0;\n"
    "wgmma.mma_async.sync.aligned.m64n16k16.f32.bf16.bf16 "
    "{%0, %1, %2, %3, %4, %5, %6, %7}, "
    "%8, %9, p, 1, 1, 0, 0;\n}\n"
    : "+f"(d[0]), "+f"(d[1]), "+f"(d[2]), "+f"(d[3]), "+f"(d[4]), "+f"(d[5]), "+f"(d[6]), "+f"(d[7])
    : "l"(da), "l"(db), "r"(scale_d));
}
__device__ __forceinline__ void wgmma_pvT(float (&d)[8], uint64_t da, uint64_t db, int scale_d) {
  asm volatile("{\n.reg .pred p;\nsetp.ne.b32 p, %10, 0;\n"
    "wgmma.mma_async.sync.aligned.m64n16k16.f32.bf16.bf16 "
    "{%0, %1, %2, %3, %4, %5, %6, %7}, "
    "%8, %9, p, 1, 1, 1, 0;\n}\n"
    : "+f"(d[0]), "+f"(d[1]), "+f"(d[2]), "+f"(d[3]), "+f"(d[4]), "+f"(d[5]), "+f"(d[6]), "+f"(d[7])
    : "l"(da), "l"(db), "r"(scale_d));
}

__device__ __forceinline__ void wgmma_qk0(float (&d)[32], uint32_t a0, uint32_t a1, uint32_t a2, uint32_t a3, uint64_t db) {
  asm volatile("{\n.reg .pred p;\nsetp.ne.b32 p, 0, 0;\n"
    "wgmma.mma_async.sync.aligned.m64n64k16.f32.bf16.bf16 "
    "{%0, %1, %2, %3, %4, %5, %6, %7, %8, %9, %10, %11, %12, %13, %14, %15, %16, %17, %18, %19, %20, %21, %22, %23, %24, %25, %26, %27, %28, %29, %30, %31}, "
    "{%32, %33, %34, %35}, %36, p, 1, 1, 0;\n}\n"
    : "=f"(d[0]), "=f"(d[1]), "=f"(d[2]), "=f"(d[3]), "=f"(d[4]), "=f"(d[5]), "=f"(d[6]), "=f"(d[7]), "=f"(d[8]), "=f"(d[9]), "=f"(d[10]), "=f"(d[11]), "=f"(d[12]), "=f"(d[13]), "=f"(d[14]), "=f"(d[15]), "=f"(d[16]), "=f"(d[17]), "=f"(d[18]), "=f"(d[19]), "=f"(d[20]), "=f"(d[21]), "=f"(d[22]), "=f"(d[23]), "=f"(d[24]), "=f"(d[25]), "=f"(d[26]), "=f"(d[27]), "=f"(d[28]), "=f"(d[29]), "=f"(d[30]), "=f"(d[31])
    : "r"(a0), "r"(a1), "r"(a2), "r"(a3), "l"(db));
}
__device__ __forceinline__ void wgmma_pv0(float (&d)[96], uint32_t a0, uint32_t a1, uint32_t a2, uint32_t a3, uint64_t db) {
  asm volatile("{\n.reg .pred p;\nsetp.ne.b32 p, 0, 0;\n"
    "wgmma.mma_async.sync.aligned.m64n192k16.f32.bf16.bf16 "
    "{%0, %1, %2, %3, %4, %5, %6, %7, %8, %9, %10, %11, %12, %13, %14, %15, %16, %17, %18, %19, %20, %21, %22, %23, %24, %25, %26, %27, %28, %29, %30, %31, %32, %33, %34, %35, %36, %37, %38, %39, %40, %41, %42, %43, %44, %45, %46, %47, %48, %49, %50, %51, %52, %53, %54, %55, %56, %57, %58, %59, %60, %61, %62, %63, %64, %65, %66, %67, %68, %69, %70, %71, %72, %73, %74, %75, %76, %77, %78, %79, %80, %81, %82, %83, %84, %85, %86, %87, %88, %89, %90, %91, %92, %93, %94, %95}, "
    "{%96, %97, %98, %99}, %100, p, 1, 1, 1;\n}\n"
    : "=f"(d[0]), "=f"(d[1]), "=f"(d[2]), "=f"(d[3]), "=f"(d[4]), "=f"(d[5]), "=f"(d[6]), "=f"(d[7]), "=f"(d[8]), "=f"(d[9]), "=f"(d[10]), "=f"(d[11]), "=f"(d[12]), "=f"(d[13]), "=f"(d[14]), "=f"(d[15]), "=f"(d[16]), "=f"(d[17]), "=f"(d[18]), "=f"(d[19]), "=f"(d[20]), "=f"(d[21]), "=f"(d[22]), "=f"(d[23]), "=f"(d[24]), "=f"(d[25]), "=f"(d[26]), "=f"(d[27]), "=f"(d[28]), "=f"(d[29]), "=f"(d[30]), "=f"(d[31]), "=f"(d[32]), "=f"(d[33]), "=f"(d[34]), "=f"(d[35]), "=f"(d[36]), "=f"(d[37]), "=f"(d[38]), "=f"(d[39]), "=f"(d[40]), "=f"(d[41]), "=f"(d[42]), "=f"(d[43]), "=f"(d[44]), "=f"(d[45]), "=f"(d[46]), "=f"(d[47]), "=f"(d[48]), "=f"(d[49]), "=f"(d[50]), "=f"(d[51]), "=f"(d[52]), "=f"(d[53]), "=f"(d[54]), "=f"(d[55]), "=f"(d[56]), "=f"(d[57]), "=f"(d[58]), "=f"(d[59]), "=f"(d[60]), "=f"(d[61]), "=f"(d[62]), "=f"(d[63]), "=f"(d[64]), "=f"(d[65]), "=f"(d[66]), "=f"(d[67]), "=f"(d[68]), "=f"(d[69]), "=f"(d[70]), "=f"(d[71]), "=f"(d[72]), "=f"(d[73]), "=f"(d[74]), "=f"(d[75]), "=f"(d[76]), "=f"(d[77]), "=f"(d[78]), "=f"(d[79]), "=f"(d[80]), "=f"(d[81]), "=f"(d[82]), "=f"(d[83]), "=f"(d[84]), "=f"(d[85]), "=f"(d[86]), "=f"(d[87]), "=f"(d[88]), "=f"(d[89]), "=f"(d[90]), "=f"(d[91]), "=f"(d[92]), "=f"(d[93]), "=f"(d[94]), "=f"(d[95])
    : "r"(a0), "r"(a1), "r"(a2), "r"(a3), "l"(db));
}
__device__ __forceinline__ void wgmma_qkT0(float (&d)[8], uint64_t da, uint64_t db) {
  asm volatile("{\n.reg .pred p;\nsetp.ne.b32 p, 0, 0;\n"
    "wgmma.mma_async.sync.aligned.m64n16k16.f32.bf16.bf16 "
    "{%0, %1, %2, %3, %4, %5, %6, %7}, "
    "%8, %9, p, 1, 1, 0, 0;\n}\n"
    : "=f"(d[0]), "=f"(d[1]), "=f"(d[2]), "=f"(d[3]), "=f"(d[4]), "=f"(d[5]), "=f"(d[6]), "=f"(d[7])
    : "l"(da), "l"(db));
}
__device__ __forceinline__ void wgmma_pvT0(float (&d)[8], uint64_t da, uint64_t db) {
  asm volatile("{\n.reg .pred p;\nsetp.ne.b32 p, 0, 0;\n"
    "wgmma.mma_async.sync.aligned.m64n16k16.f32.bf16.bf16 "
    "{%0, %1, %2, %3, %4, %5, %6, %7}, "
    "%8, %9, p, 1, 1, 1, 0;\n}\n"
    : "=f"(d[0]), "=f"(d[1]), "=f"(d[2]), "=f"(d[3]), "=f"(d[4]), "=f"(d[5]), "=f"(d[6]), "=f"(d[7])
    : "l"(da), "l"(db));
}

struct Round { int head, qrow, mc; };
__device__ __forceinline__ Round decode_round(uint32_t e, uint32_t rank) {
  Round o;
  o.mc = (e & 0x600) != 0x600;
  o.head = (e & 0x1ff) + (o.mc ? 0 : rank);
  o.qrow = (e >> 1 & 0x300) + (o.mc ? rank * 128 : 0);
  return o;
}

__device__ __forceinline__ uint32_t kdesc0(uint32_t s_kv) { return ((s_kv & 0x3FFFFu) >> 4) | (1u << 16); }
__device__ __forceinline__ uint32_t vdesc0(uint32_t s_kv) { return ((s_kv & 0x3FFFFu) >> 4) | ((uint32_t)(SLAB >> 4) << 16); }
constexpr uint64_t DESC_HI = ((uint64_t)(RGRP >> 4) << 32) | ((uint64_t)1 << 62);
constexpr uint64_t DESC_HI_PT = ((uint64_t)(1024 >> 4) << 32) | ((uint64_t)1 << 62);

__device__ __forceinline__ void issue_qk(float (&S)[32], const uint32_t (&Q)[48], uint32_t kdesc) {
  const uint64_t d = DESC_HI | kdesc;
  wgmma_qk0(S, Q[0], Q[1], Q[2], Q[3], d);
#pragma unroll
  for (int kk = 1; kk < 12; kk++)
    wgmma_qk(S, Q[kk * 4], Q[kk * 4 + 1], Q[kk * 4 + 2], Q[kk * 4 + 3], d + (uint64_t)((kk / 4) * (SLAB / 16) + (kk % 4) * 2), 1);
}
__device__ __forceinline__ void issue_qk32(float (&S)[32], const uint32_t (&Q)[48], uint32_t kdesc) {
  uint32_t d[12];
#pragma unroll
  for (int kk = 0; kk < 12; kk++) {
    d[kk] = kdesc + ((kk / 4) * (SLAB / 16) + (kk % 4) * 2);
    asm volatile("" : "+r"(d[kk]));
  }
  wgmma_qk0(S, Q[0], Q[1], Q[2], Q[3], DESC_HI | d[0]);
#pragma unroll
  for (int kk = 1; kk < 12; kk++) wgmma_qk(S, Q[kk * 4], Q[kk * 4 + 1], Q[kk * 4 + 2], Q[kk * 4 + 3], DESC_HI | d[kk], 1);
}
__device__ __forceinline__ void issue_qk3(float (&S)[32], const uint32_t (&Q)[48], uint32_t kdesc) {
  const uint64_t d = DESC_HI | kdesc;
  wgmma_qk0(S, Q[0], Q[1], Q[2], Q[3], d);
#pragma unroll
  for (int kk = 1; kk < 12; kk++) {
    if (kk % 4 == 0) wg_commit();
    wgmma_qk(S, Q[kk * 4], Q[kk * 4 + 1], Q[kk * 4 + 2], Q[kk * 4 + 3], d + (uint64_t)((kk / 4) * (SLAB / 16) + (kk % 4) * 2), 1);
  }
}
template <bool ACCUMULATE>
__device__ __forceinline__ void issue_pv(float (&O)[96], const uint32_t (&P)[16], uint32_t vdesc) {
  const uint64_t d = DESC_HI | vdesc;
  if (ACCUMULATE) wgmma_pv(O, P[0], P[1], P[2], P[3], d, 1);
  else wgmma_pv0(O, P[0], P[1], P[2], P[3], d);
#pragma unroll
  for (int kk = 1; kk < 4; kk++)
    wgmma_pv(O, P[kk * 4], P[kk * 4 + 1], P[kk * 4 + 2], P[kk * 4 + 3], d + (uint64_t)(kk * (2 * RGRP / 16)), 1);
}

template <int K0 = 0, int K1 = 12>
__device__ __forceinline__ void load_q(uint32_t (&Q)[48], uint32_t lane_addr) {
#pragma unroll
  for (int kk = K0; kk < K1; kk++)
    ldsm_x4((lane_addr ^ ((kk % 4) << 5)) + (kk / 4) * SLAB, Q[kk * 4], Q[kk * 4 + 1], Q[kk * 4 + 2], Q[kk * 4 + 3]);
}

__device__ __forceinline__ void scale_q(uint32_t (&Q)[48]) {
  constexpr uint32_t C2 = 0x3DD53DD5u;
#pragma unroll
  for (int i = 0; i < 48; i++) asm("mul.rn.bf16x2 %0, %1, %2;" : "=r"(Q[i]) : "r"(Q[i]), "r"(C2));
  fence_regs(Q);
}
__device__ __forceinline__ void softmax_block(const float (&S)[32], uint32_t (&P)[16], float& l0, float& l1) {
#pragma unroll
  for (int i = 0; i < 8; i++) {
    const float a = ex2(S[4 * i + 0]);
    const float b = ex2(S[4 * i + 1]);
    const float c = ex2(S[4 * i + 2]);
    const float d = ex2(S[4 * i + 3]);
    l0 += a + b;
    l1 += c + d;
    P[2 * i] = pack_bf16(a, b);
    P[2 * i + 1] = pack_bf16(c, d);
  }
  fence_regs(P);
}

__device__ __forceinline__ void sums_put(uint32_t addr, float l0, float l1) {
  asm volatile("st.shared.v2.f32 [%0], {%1, %2};" ::"r"(addr), "f"(l0), "f"(l1) : "memory");
}
__device__ __forceinline__ void sums_get(uint32_t addr, float& s0, float& s1) {
  float a, b, c, d, e, f, g, h;
  asm volatile("ld.shared.v4.f32 {%0, %1, %2, %3}, [%8];\nld.shared.v4.f32 {%4, %5, %6, %7}, [%8 + 16];\n"
               : "=f"(a), "=f"(b), "=f"(c), "=f"(d), "=f"(e), "=f"(f), "=f"(g), "=f"(h) : "r"(addr & ~31u) : "memory");
  s0 = (a + c) + (e + g);
  s1 = (b + d) + (f + h);
}

template <int K0, int K1>
__device__ __forceinline__ void epilogue_part(const float (&O)[96], float i0, float i1, uint32_t lane_addr) {
#pragma unroll
  for (int kk = K0; kk < K1; kk++) {
    const int b = kk * 8;
    stsm_x4((lane_addr ^ ((kk % 4) << 5)) + (kk / 4) * SLAB,
            pack_bf16(O[b] * i0, O[b + 1] * i0), pack_bf16(O[b + 2] * i1, O[b + 3] * i1),
            pack_bf16(O[b + 4] * i0, O[b + 5] * i0), pack_bf16(O[b + 6] * i1, O[b + 7] * i1));
  }
}
__device__ __forceinline__ void epilogue_done(uint32_t bar, int lane) {
  __syncwarp();
  if (lane == 0) mbar_arrive(bar);
}

__device__ __forceinline__ void redo_tile(const CUtensorMap* tmQ, const CUtensorMap* tmK, const CUtensorMap* tmV, const CUtensorMap* tmO,
                                          int head, int row, uint32_t qo, uint32_t kv, uint32_t lane_addr, uint32_t bar, uint32_t& phase,
                                          uint32_t wg_bar) {
  float O[96], S[32];
  uint32_t Q[48], P[16];
  uint64_t pol;
  asm volatile("createpolicy.fractional.L2::evict_normal.b64 %0, 1.0;" : "=l"(pol));
  const bool leader = (threadIdx.x & 127) == 0;
  if (leader) {
    mbar_expect_tx(bar, SLOT);
    tma_load(qo, tmQ, bar, row, head, pol);
  }
  mbar_wait(bar, phase);
  phase ^= 1;
  load_q(Q, lane_addr);
  float m0 = -INFINITY, m1 = -INFINITY, l0 = 0.f, l1 = 0.f;
#pragma unroll
  for (int i = 0; i < 96; i++) O[i] = 0.f;
#pragma unroll 1
  for (int j = 0; j < NBLK; j++) {
    asm volatile("bar.sync %0, 128;" ::"r"(wg_bar) : "memory");
    if (leader) {
      mbar_expect_tx(bar, 2 * SLOT);
      tma_load(kv, tmK, bar, j * BN, head, pol);
      tma_load(kv + SLOT, tmV, bar, j * BN, head, pol);
    }
    mbar_wait(bar, phase);
    phase ^= 1;
    wg_fence();
    issue_qk(S, Q, kdesc0(kv));
    wg_commit();
    wg_wait<0>();
    fence_regs(S);
    float n0 = m0, n1 = m1;
#pragma unroll
    for (int i = 0; i < 8; i++) {
      n0 = fmaxf(n0, fmaxf(S[4 * i], S[4 * i + 1]));
      n1 = fmaxf(n1, fmaxf(S[4 * i + 2], S[4 * i + 3]));
    }
#pragma unroll
    for (int o = 1; o < 4; o <<= 1) {
      n0 = fmaxf(n0, __shfl_xor_sync(0xffffffffu, n0, o));
      n1 = fmaxf(n1, __shfl_xor_sync(0xffffffffu, n1, o));
    }
    const float f0 = ex2((m0 - n0) * SCALE_LOG2), f1 = ex2((m1 - n1) * SCALE_LOG2);
    m0 = n0; m1 = n1;
    l0 *= f0; l1 *= f1;
#pragma unroll
    for (int i = 0; i < 24; i++) {
      O[4 * i] *= f0; O[4 * i + 1] *= f0; O[4 * i + 2] *= f1; O[4 * i + 3] *= f1;
    }
#pragma unroll
    for (int i = 0; i < 8; i++) {
      S[4 * i] = (S[4 * i] - m0) * SCALE_LOG2; S[4 * i + 1] = (S[4 * i + 1] - m0) * SCALE_LOG2;
      S[4 * i + 2] = (S[4 * i + 2] - m1) * SCALE_LOG2; S[4 * i + 3] = (S[4 * i + 3] - m1) * SCALE_LOG2;
    }
    softmax_block(S, P, l0, l1);
    fence_regs(O);
    wg_fence();
    issue_pv<true>(O, P, vdesc0(kv + SLOT));
    wg_commit();
    wg_wait<0>();
    fence_regs(O);
  }
#pragma unroll
  for (int o = 1; o < 4; o <<= 1) {
    l0 += __shfl_xor_sync(0xffffffffu, l0, o);
    l1 += __shfl_xor_sync(0xffffffffu, l1, o);
  }
  epilogue_part<0, 12>(O, rcp(l0), rcp(l1), lane_addr);
  asm volatile("fence.proxy.async.shared::cta;" ::: "memory");
  asm volatile("bar.sync %0, 128;" ::"r"(wg_bar) : "memory");
  if (leader) {
    for (int i = 0; i < 64 && row + i < SQ; i += OROWS) tma_store(tmO, qo + i / 8 * RGRP, row + i, head, pol);
    asm volatile("cp.async.bulk.commit_group;" ::: "memory");
    asm volatile("cp.async.bulk.wait_group 0;" ::: "memory");
  }
}

__device__ __forceinline__ void wg_barrier() { asm volatile("bar.sync 3, 128;" ::: "memory"); }

__device__ __forceinline__ void tail_reduce(float (&v)[4], uint32_t red, int warp, int lane) {
#pragma unroll
  for (int o = 4; o < 32; o <<= 1)
#pragma unroll
    for (int i = 0; i < 4; i++) v[i] += __shfl_xor_sync(0xffffffffu, v[i], o);
  if (lane < 4)
    asm volatile("st.shared.v4.f32 [%0], {%1, %2, %3, %4};" ::"r"(red + (warp * 4 + lane) * 16), "f"(v[0]), "f"(v[1]), "f"(v[2]), "f"(v[3]) : "memory");
  wg_barrier();
#pragma unroll
  for (int ww = 0; ww < 4; ww++) {
    float x0, x1, x2, x3;
    asm volatile("ld.shared.v4.f32 {%0, %1, %2, %3}, [%4];" : "=f"(x0), "=f"(x1), "=f"(x2), "=f"(x3) : "r"(red + (ww * 4 + (lane & 3)) * 16) : "memory");
    if (ww == 0) { v[0] = x0; v[1] = x1; v[2] = x2; v[3] = x3; }
    else { v[0] += x0; v[1] += x1; v[2] += x2; v[3] += x3; }
  }
}

__device__ __forceinline__ void tail_softmax(const float (&S)[8], float (&l)[4], uint32_t pt_addr) {
  float e[8];
#pragma unroll
  for (int i = 0; i < 8; i++) e[i] = ex2(S[i] * SCALE_LOG2);
  stsm_x4_trans(pt_addr, pack_bf16(e[0], e[1]), pack_bf16(e[2], e[3]), pack_bf16(e[4], e[5]), pack_bf16(e[6], e[7]));
  l[0] += e[0] + e[2]; l[1] += e[1] + e[3]; l[2] += e[4] + e[6]; l[3] += e[5] + e[7];
}

__device__ __forceinline__ void issue_qkT(float (&S8)[8], uint32_t kdesc, uint32_t qt_addr) {
  const uint64_t da = DESC_HI | kdesc;
  const uint64_t db = DESC_HI | (uint64_t)(((qt_addr & 0x3FFFFu) >> 4) | (1u << 16));
  wgmma_qkT0(S8, da, db);
#pragma unroll
  for (int kk = 1; kk < 12; kk++)
    wgmma_qkT(S8, da + (uint64_t)((kk / 4) * (SLAB / 16) + (kk % 4) * 2), db + (uint64_t)((kk / 4) * (SLAB / 16) + (kk % 4) * 2), 1);
}
template <bool ACCUMULATE>
__device__ __forceinline__ void issue_pvT(float (&O)[3][8], uint32_t vdesc, uint32_t pt_base) {
  const uint64_t da = DESC_HI | vdesc;
  const uint64_t db = DESC_HI_PT | (uint64_t)(((pt_base & 0x3FFFFu) >> 4) | (1u << 16));
#pragma unroll
  for (int kk = 0; kk < 4; kk++)
#pragma unroll
    for (int b = 0; b < 3; b++) {
      if (kk == 0 && !ACCUMULATE) wgmma_pvT0(O[b], da + (uint64_t)(b * (SLAB / 16)), db);
      else wgmma_pvT(O[b], da + (uint64_t)(b * (SLAB / 16) + kk * (2 * RGRP / 16)), db + (uint64_t)(kk * 2), 1);
    }
}

template <bool B> struct Bool { static constexpr bool value = B; };

constexpr int MAX_CLUSTERS = 72;
constexpr int MAX_ROUNDS = 32;
struct Schedule {
  uint32_t tails[MAX_CLUSTERS];
  uint16_t start[MAX_CLUSTERS + 1];
  uint16_t list[NROUNDS + 1];
};

#define TRACE_TILE()

__global__ void __cluster_dims__(2, 1, 1) __launch_bounds__(NTHREADS, 1)
attn_kernel(const __grid_constant__ CUtensorMap tmQ, const __grid_constant__ CUtensorMap tmQT, const __grid_constant__ CUtensorMap tmK,
            const __grid_constant__ CUtensorMap tmV, const __grid_constant__ CUtensorMap tmO, const __grid_constant__ Schedule sched) {
  extern __shared__ __align__(1024) uint8_t smem_raw[];
  const uint32_t c_entry = (uint32_t)clock();
  const uint32_t sbase = smem_u32(smem_raw);
  const uint32_t s_qo = sbase + OFF_QO;
  const uint32_t s_kv = sbase + OFF_KV;
  const uint32_t s_bar = sbase + OFF_BAR;
  const uint32_t bar_full = s_bar;
  const uint32_t bar_empty = s_bar + 8 * NSLOT;
  const uint32_t bar_qfull = s_bar + 16 * NSLOT;
  const uint32_t bar_ostg = bar_qfull + 16;
  const uint32_t bar_qreq = bar_ostg + 16;
  const uint32_t bar_redo = bar_qreq + 16;
  const uint32_t s_redo = bar_redo + 16;

  uint32_t rank;
  asm("mov.u32 %0, %%cluster_ctarank;" : "=r"(rank));
  const int cluster = blockIdx.x >> 1;
  auto get_rounds = [&](int& first, int& count) {
    uint32_t c;
    asm volatile("mov.u32 %0, %%ctaid.x;" : "=r"(c));
    c >>= 1;
    first = sched.start[c];
    count = sched.start[c + 1] - first;
  };

  if (threadIdx.x == 0) {
    asm volatile("prefetch.tensormap [%0];" ::"l"(&tmK) : "memory");
    asm volatile("prefetch.tensormap [%0];" ::"l"(&tmQ) : "memory");
    asm volatile("prefetch.tensormap [%0];" ::"l"(&tmV) : "memory");
    for (int i = 0; i < 3; i++) mbar_init(bar_full + 8 * i, 1);
    for (int i = 0; i < 2; i++) mbar_init(bar_qfull + 8 * i, 1);
    asm volatile("fence.mbarrier_init.release.cluster;" ::: "memory");
    asm volatile("fence.proxy.async.shared::cta;" ::: "memory");
    const int head = cluster / 3, qrow = cluster % 3 * 256 + rank * 128;
    uint64_t polq, polk;
    asm volatile("createpolicy.fractional.L2::evict_first.b64 %0, 1.0;" : "=l"(polq));
    asm volatile("createpolicy.fractional.L2::evict_unchanged.b64 %0, 1.0;" : "=l"(polk));
    while ((uint32_t)clock() - c_entry < (uint32_t)(cluster / 3 * STAGGER)) {}
    mbar_expect_tx(bar_full, SLOT);
    tma_load(s_kv, &tmK, bar_full, 0, head, polk);
    mbar_expect_tx(bar_qfull, SLOT);
    tma_load(s_qo, &tmQ, bar_qfull, qrow, head, polq);
    mbar_expect_tx(bar_full + 8, SLOT);
    tma_load(s_kv + SLOT, &tmK, bar_full + 8, BN, head, polk);
    mbar_expect_tx(bar_full + 16, SLOT);
    tma_load(s_kv + 2 * SLOT, &tmV, bar_full + 16, 0, head, polk);
    mbar_expect_tx(bar_qfull + 8, SLOT);
    tma_load(s_qo + SLOT, &tmQ, bar_qfull + 8, qrow + 64, head, polq);
  } else if (threadIdx.x == 32) {
    for (int i = 0; i < NSLOT; i++) {
      if (i >= 3) mbar_init(bar_full + 8 * i, 1);
      mbar_init(bar_empty + 8 * i, 4);
    }
    for (int i = 0; i < 2; i++) {
      mbar_init(bar_ostg + 8 * i, 4);
      mbar_init(bar_qreq + 8 * i, 1);
      mbar_init(bar_redo + 8 * i, 1);
      asm volatile("st.shared.u32 [%0], %1;" ::"r"(s_redo + 4 * i), "r"(0) : "memory");
    }
    asm volatile("fence.mbarrier_init.release.cluster;" ::: "memory");
    asm volatile("fence.proxy.async.shared::cta;" ::: "memory");
  }
  __syncthreads();
  asm volatile("barrier.cluster.arrive.relaxed.aligned;\nbarrier.cluster.wait.aligned;" ::: "memory");

  const int wg = __shfl_sync(0xffffffffu, threadIdx.x >> 7, 0);
  const int warp = __shfl_sync(0xffffffffu, (threadIdx.x >> 5) & 3, 0);
  const int lane = threadIdx.x & 31;

  if (wg == 0) {
    asm volatile("setmaxnreg.dec.sync.aligned.u32 24;");
    int first_round, nrounds;
    get_rounds(first_round, nrounds);
    const int nblocks = nrounds * NBLK;
    if (warp == 0 && lane == 0) {
      uint64_t pol;
      asm volatile("createpolicy.fractional.L2::evict_unchanged.b64 %0, 1.0;" : "=l"(pol));
      uint32_t slot = 3, phase = 1;
      auto load = [&](const CUtensorMap* tm, int n, uint32_t owner) {
        const Round r = decode_round(sched.list[first_round + (n >> 3)], rank);
        mbar_wait_sleep(bar_empty + 8 * slot, phase);
        if (n < nblocks) {
          mbar_expect_tx(bar_full + 8 * slot, SLOT);
          if (!r.mc) tma_load(s_kv + slot * SLOT, tm, bar_full + 8 * slot, (n & 7) * BN, r.head, pol);
          else if (rank == owner) tma_load_mc(s_kv + slot * SLOT, tm, bar_full + 8 * slot, (n & 7) * BN, r.head, pol);
        }
        if (++slot == NSLOT) { slot = 0; phase ^= 1; }
      };
      auto request_q = [&](int n, int pos) {
        pos += (n & 7) * 2;
        if (pos == QREQ0) mbar_arrive(bar_qreq);
        if (pos == QREQ1) mbar_arrive(bar_qreq + 8);
      };
      for (int n = 1; n < nblocks; n++) {
        load(&tmK, n + 1, 0);
        request_q(n, 0);
        load(&tmV, n, 1);
        request_q(n, 1);
      }
      for (int i = 0; i < NSLOT; i++) {
        if (i != NSLOT - 2) mbar_wait_sleep(bar_empty + 8 * slot, phase);
        if (++slot == NSLOT) { slot = 0; phase ^= 1; }
      }
    } else if ((warp == 1 || warp == 2) && lane == 0) {
      const int w = warp - 1;
      uint64_t pol;
      asm volatile("createpolicy.fractional.L2::evict_first.b64 %0, 1.0;" : "=l"(pol));
      const uint32_t buf = s_qo + w * SLOT;
      mbar_wait_sleep(bar_ostg + 8 * w, 0);
      asm volatile("prefetch.tensormap [%0];" ::"l"(w ? &tmQT : &tmO) : "memory");
      for (int t = 0; t < nrounds; t++) {
        if (t + 1 < nrounds) {
          const uint32_t e = sched.list[first_round + t + 1];
          const Round r = decode_round(e, rank);
          const bool tail = w == 1 && (e & 0x8000);
          mbar_wait_sleep(bar_qreq + 8 * w, t & 1);
          mbar_expect_tx(bar_qfull + 8 * w, tail ? 3 * 2048 : SLOT);
          tma_load(tail ? sbase + OFF_QT : buf, tail ? &tmQT : &tmQ, bar_qfull + 8 * w, r.qrow + w * 64, r.head, pol);
        } else {
          mbar_arrive(bar_qfull + 8 * w);
        }
        const Round r = decode_round(sched.list[first_round + t], rank);
        const int row0 = r.qrow + w * 64;
        const int nrows = row0 + 64 <= SQ ? 64 : SQ % 64;
        mbar_wait_sleep(bar_ostg + 8 * w, ~t & 1);
        asm volatile("fence.proxy.async.shared::cta;" ::: "memory");
#pragma unroll 1
        for (int i = 0; i < nrows; i += OROWS) {
          tma_store(&tmO, buf + i / 8 * RGRP, row0 + i, r.head, pol);
          asm volatile("cp.async.bulk.commit_group;" ::: "memory");
          if (t + 1 < nrounds) asm volatile("cp.async.bulk.wait_group.read 0;" ::: "memory");
        }
      }
      asm volatile("cp.async.bulk.wait_group 0;" ::: "memory");
      mbar_arrive(bar_redo + 8 * w);
    } else if (warp == 3) {
      uint32_t slot = 1, phase = 0;
      for (int n = 0; n < nblocks; n++) {
        if (n + 1 < nblocks) mbar_wait(bar_full + 8 * slot, phase);
        if (++slot == NSLOT) { slot = 0; phase ^= 1; }
        mbar_wait(bar_full + 8 * slot, phase);
        if (++slot == NSLOT) { slot = 0; phase ^= 1; }
        asm volatile("bar.sync 1, 288;" ::: "memory");
        asm volatile("bar.arrive 2, 288;" ::: "memory");
        TRACE_TILE();
      }
    }
  } else {
    asm volatile("setmaxnreg.inc.sync.aligned.u32 240;");
    const int w = wg - 1;
    int first_round, nrounds;
    get_rounds(first_round, nrounds);
    const int nblocks = nrounds * NBLK;
    float O[96], S[32];
    uint32_t Q[48], P0[16], P1[16];
    float l0 = 0.f, l1 = 0.f, inv0 = 1.f, inv1 = 1.f;
    uint32_t redo = 0;
    const uint32_t lane_addr = s_qo + w * SLOT + (warp * 2 + ((lane >> 3) & 1)) * RGRP + (lane & 7) * 128 + (((lane >> 4) ^ (lane & 7)) << 4);
    const uint32_t sum_addr = s_qo + w * SLOT + warp * 2 * RGRP + lane * 8;
    const uint32_t my_qfull = bar_qfull + 8 * w, my_ostg = bar_ostg + 8 * w;

    uint32_t empty_remote;
    asm("mapa.shared::cluster.u32 %0, %1, %2;" : "=r"(empty_remote) : "r"(bar_empty), "r"(threadIdx.x & 1));
    const bool releaser = (threadIdx.x & 127) < 2;
    auto release = [&](uint32_t s) {
      if (releaser) asm volatile("mbarrier.arrive.shared::cluster.b64 _, [%0];" ::"r"(empty_remote + s) : "memory");
    };
    uint32_t ks = 8, vs = 16, kp = 0, vp = 0;
    const uint32_t kd0 = kdesc0(s_kv), vd0 = vdesc0(s_kv);
    uint32_t kd = kd0 + ks * (SLOT / 128), vd = vd0 + vs * (SLOT / 128);
    auto advance = [&]() {
      kp = ks; vp = vs;
      ks = ks >= 8 * (NSLOT - 2) ? ks - 8 * (NSLOT - 2) : ks + 16;
      vs = vs >= 8 * (NSLOT - 2) ? vs - 8 * (NSLOT - 2) : vs + 16;
      kd = kd0 + ks * (SLOT / 128); vd = vd0 + vs * (SLOT / 128);
      asm volatile("" : "+r"(ks), "+r"(vs), "+r"(kd), "+r"(vd));
    };

    uint32_t tails = w == 1 ? sched.tails[cluster] : 0u;
    auto turn_wait = [&]() { asm volatile("bar.sync %0, 288;" ::"r"(1 + w) : "memory"); };
    auto turn_pass = [&]() { asm volatile("bar.arrive %0, 288;" ::"r"(2 - w) : "memory"); };
    if (w == 1) asm volatile("bar.arrive %0, 288;" ::"r"(1 + (tails & 1)) : "memory");

    mbar_wait(my_qfull, 0);
    load_q(Q, lane_addr);
    scale_q(Q);
    mbar_wait(bar_full, 0);
    wg_fence();
    issue_qk(S, Q, kd0);
    wg_commit();
    wg_wait<0>();
    fence_regs(S);
    release(0);
    __syncwarp();
    if (lane == 0) mbar_arrive(my_ostg);
    uint32_t pending = 0;

    int n = 0;
    auto finish_sums = [&]() {
      float s0, s1;
      sums_get(sum_addr, s0, s1);
      inv0 = rcp(s0); inv1 = rcp(s1);
      l0 = l1 = 0.f;
      asm volatile("" : "+f"(inv0), "+f"(inv1)::"memory");
    };
    auto check_sums = [&](int t) { check_inv(inv0, inv1, redo, 1u << (t & 31)); };

    int exit_n = -1;
#pragma unroll 1
    while (true) {
#pragma unroll 1
      while (true) {
        const int j = n & 7;
        softmax_block(S, P0, l0, l1);
        asm volatile("" : "+f"(l0), "+f"(l1)::"memory");
        if (j != 0) {
          wg_wait<0>();
          release(vp);
          turn_wait();
          wg_fence();
          issue_qk3(S, Q, kd);
          wg_commit();
          issue_pv<true>(O, P0, vd);
          wg_commit();
          turn_pass();
          advance();
          if (j == 6) {
            mbar_wait(my_qfull, ((n >> 3) + 1) & 1);
            wg_wait<3>();
            load_q<0, 4>(Q, lane_addr);
            wg_wait<2>();
            load_q<4, 8>(Q, lane_addr);
          }
          wg_wait<1>();
          fence_regs(S);
          fence_regs(P1);
        } else {
          wg_wait<0>();
          fence_regs(O);
          fence_regs(P1);
          if (pending) {
            release(vp);
            epilogue_part<0, ESPLIT>(O, inv0, inv1, lane_addr);
          }
          turn_wait();
          wg_fence();
          issue_qk32(S, Q, kd);
          wg_commit();
          if (pending) {
            epilogue_part<ESPLIT, 12>(O, inv0, inv1, lane_addr);
            epilogue_done(my_ostg, lane);
          }
          wg_fence();
          issue_pv<false>(O, P0, vd);
          wg_commit();
          turn_pass();
          advance();
          check_sums((n >> 3) - 1);
          exit_n = ((tails & 2) || n + 8 == nblocks) ? n + 6 : -1;
          tails >>= 1;
          asm volatile("" : "+r"(exit_n), "+r"(tails), "+r"(redo));
          wg_wait<1>();
          fence_regs(S);
          pending = true;
        }
        release(kp);
        softmax_block(S, P1, l0, l1);
        asm volatile("" : "+f"(l0), "+f"(l1)::"memory");
        if (j == 6) {
          load_q<8, 12>(Q, lane_addr);
          sums_put(sum_addr, l0, l1);
          wg_wait<0>();
          release(vp);
          scale_q(Q);
          if (n == exit_n) {
            turn_wait();
            wg_fence();
            issue_pv<true>(O, P1, vd);
            wg_commit();
            break;
          }
          asm volatile("" ::: "memory");
          turn_wait();
          wg_fence();
          issue_qk32(S, Q, kd);
          wg_commit();
          issue_pv<true>(O, P1, vd);
          wg_commit();
          turn_pass();
          advance();
          if (pending) finish_sums();
          wg_wait<1>();
        } else {
          wg_wait<0>();
          release(vp);
          turn_wait();
          wg_fence();
          issue_qk(S, Q, kd);
          wg_commit();
          issue_pv<true>(O, P1, vd);
          wg_commit();
          turn_pass();
          advance();
          wg_wait<1>();
        }
        fence_regs(S);
        fence_regs(P0);
        release(kp);
        n += 2;
      }
      if (n + 2 == nblocks) {
        if (w == 0) turn_pass();
        finish_sums();
        check_sums(n >> 3);
        wg_wait<0>();
        fence_regs(O);
        release(vs);
        epilogue_part<0, 12>(O, inv0, inv1, lane_addr);
        epilogue_done(my_ostg, lane);
        break;
      }
      const int t = n >> 3;
      const uint32_t qt = sbase + OFF_QT, pt = sbase + OFF_PT, red = sbase + OFF_RED;
      const uint32_t tl = ((lane & 7) + (lane >> 4) * 8) * 128 + (((warp * 2 + ((lane >> 3) & 1)) ^ (lane & 7)) << 4);
      const bool tlast = n + 10 == nblocks;
      float lt[4] = {0.f, 0.f, 0.f, 0.f};
      float ST[8], OT[3][8];
      wg_fence();
      issue_qkT(ST, kd, qt);
      wg_commit();
      turn_pass();
      finish_sums();
      check_sums(t);
      wg_wait<0>();
      fence_regs(ST);
      fence_regs(O);
      release(ks);
      release(vs);
      advance();
      epilogue_part<0, NT_SPLIT>(O, inv0, inv1, lane_addr);
      if (NT_SPLIT == 12) epilogue_done(my_ostg, lane);
      tail_softmax(ST, lt, pt + tl);
      auto tail_step = [&](auto first_c, int jj) {
        constexpr bool FIRST = decltype(first_c)::value;
        asm volatile("fence.proxy.async.shared::cta;" ::: "memory");
        turn_wait();
        wg_fence();
        issue_qkT(ST, kd, qt);
        wg_commit();
        issue_pvT<!FIRST>(OT, vd, pt + (jj & 1) * 2048);
        wg_commit();
        turn_pass();
        advance();
        wg_wait<1>();
        fence_regs(ST);
        release(kp);
        tail_softmax(ST, lt, pt + (~jj & 1) * 2048 + tl);
        wg_wait<0>();
        fence_regs(OT[0]); fence_regs(OT[1]); fence_regs(OT[2]);
        release(vp);
      };
      tail_step(Bool<true>(), 0);
      if (NT_SPLIT < 12) {
        epilogue_part<NT_SPLIT, 12>(O, inv0, inv1, lane_addr);
        epilogue_done(my_ostg, lane);
      }
#pragma unroll 1
      for (int jj = 1; jj < 7; jj++) tail_step(Bool<false>(), jj);
      mbar_wait(my_qfull, t & 1);
      load_q(Q, lane_addr);
      scale_q(Q);
      tail_reduce(lt, red, warp, lane);
#pragma unroll
      for (int i = 0; i < 4; i++) lt[i] = rcp(lt[i]);
      check_inv(lt[0], lt[1], redo, 1u << ((t + 1) & 31));
      check_inv(lt[2], lt[3], redo, 1u << ((t + 1) & 31));
      inv0 = inv1 = 1.f;
      asm volatile("fence.proxy.async.shared::cta;" ::: "memory");
      turn_wait();
      wg_fence();
      issue_pvT<true>(OT, vd, pt + 2048);
      wg_commit();
      issue_qk(S, Q, kd);
      wg_commit();
      if (!tlast) turn_pass();
      wg_wait<1>();
      fence_regs(OT[0]); fence_regs(OT[1]); fence_regs(OT[2]);
      release(vs);
#pragma unroll
      for (int b = 0; b < 3; b++)
        stsm_x4_trans(s_qo + SLOT + b * SLAB + tl + (lane >> 4) * (RGRP - 1024),
                      pack_bf16(OT[b][0] * lt[0], OT[b][1] * lt[1]), pack_bf16(OT[b][2] * lt[0], OT[b][3] * lt[1]),
                      pack_bf16(OT[b][4] * lt[2], OT[b][5] * lt[3]), pack_bf16(OT[b][6] * lt[2], OT[b][7] * lt[3]));
      epilogue_done(my_ostg, lane);
      wg_wait<0>();
      fence_regs(S);
      if (tlast) break;
      release(ks);
      advance();
#pragma unroll
      for (int i = 0; i < 96; i++) O[i] = 0.f;
      pending = false;
      n += 10;
      tails >>= 1;
    }
    if (redo) asm volatile("red.shared.or.b32 [%0], %1;" ::"r"(s_redo + 4 * w), "r"(redo) : "memory");
    asm volatile("bar.sync 4, 256;" ::: "memory");
    asm volatile("ld.shared.u32 %0, [%1];" : "=r"(redo) : "r"(s_redo + 4 * w) : "memory");
    redo = __shfl_sync(0xffffffffu, redo, 0);
    if (redo) {
      mbar_wait_sleep(bar_redo + 8 * w, 0);
      asm volatile("bar.sync %0, 128;" ::"r"(5 + w) : "memory");
      uint32_t phase = 1;
      get_rounds(first_round, nrounds);
      uint32_t rank;
      asm volatile("mov.u32 %0, %%cluster_ctarank;" : "=r"(rank));
#pragma unroll 1
      for (int t = 0; t < nrounds; t++) {
        if (!(redo >> (t & 31) & 1)) continue;
        const Round r = decode_round(sched.list[first_round + t], rank);
        redo_tile(&tmQ, &tmK, &tmV, &tmO, r.head, r.qrow + w * 64, s_qo + w * SLOT, s_kv + 2 * w * SLOT, lane_addr, bar_redo + 8 * w, phase, 5 + w);
      }
    }
  }
}

typedef CUresult (*EncodeFn)(CUtensorMap*, CUtensorMapDataType, cuuint32_t, void*, const cuuint64_t*, const cuuint64_t*,
                             const cuuint32_t*, const cuuint32_t*, CUtensorMapInterleave, CUtensorMapSwizzle,
                             CUtensorMapL2promotion, CUtensorMapFloatOOBfill);

void make_map(EncodeFn fn, CUtensorMap* tm, const void* ptr, int rows, int box_rows) {
  cuuint64_t dims[5] = {64, 8, 3, (cuuint64_t)rows / 8, (cuuint64_t)NHEADS};
  cuuint64_t strides[4] = {HD * 2, 128, 8 * HD * 2, (cuuint64_t)rows * HD * 2};
  cuuint32_t box[5] = {64, 8, 3, (cuuint32_t)box_rows / 8, 1};
  cuuint32_t estr[5] = {1, 1, 1, 1, 1};
  fn(tm, CU_TENSOR_MAP_DATA_TYPE_BFLOAT16, 5, const_cast<void*>(ptr), dims, strides, box, estr,
     CU_TENSOR_MAP_INTERLEAVE_NONE, CU_TENSOR_MAP_SWIZZLE_128B, CU_TENSOR_MAP_L2_PROMOTION_L2_128B, CU_TENSOR_MAP_FLOAT_OOB_FILL_NONE);
}

#define COST_N 12690
#define COST_T 10800
#define COST_TN 12720
#define TAIL_LATE 36
#define TAIL_MAX 60
#define HEAVY_STEP 3
static_assert(MAX_CLUSTERS / 3 * STAGGER < COST_T, "the first wave has to be handed out in the order of the clusters");
void make_schedule(Schedule& s, int nclusters) {
  static uint16_t lists[MAX_CLUSTERS][NROUNDS];
  int cnt[MAX_CLUSTERS] = {0}, len[MAX_CLUSTERS], ntail[MAX_CLUSTERS] = {0}, quota[MAX_CLUSTERS] = {0};
  long long busy[MAX_CLUSTERS], fin[MAX_CLUSTERS];
  const int ntails = NROUNDS / 7, base = NROUNDS / nclusters, nheavy = NROUNDS % nclusters;
  const int step = nheavy * HEAVY_STEP <= nclusters ? HEAVY_STEP : 1;
  for (int c = 0; c < nclusters; c++) {
    len[c] = base + (c % step == 0 && c / step < nheavy);
    busy[c] = c / 3 * STAGGER;
    fin[c] = busy[c] + (long long)len[c] * COST_N;
  }
  for (int k = 0; k < ntails; k++) {
    int c = -1;
    for (int i = 0; i < nclusters; i++)
      if (quota[i] < len[i] / 2 && (c < 0 || fin[i] > fin[c])) c = i;
    quota[c]++;
    fin[c] -= 2 * COST_N - COST_T - COST_TN;
  }
  int gn = 0, gt = 3;
  for (int k = 0; k < NROUNDS; k++) {
    int c = -1;
    for (int i = 0; i < nclusters; i++)
      if (cnt[i] < len[i] && (c < 0 || busy[i] < busy[c])) c = i;
    const bool after_tail = cnt[c] > 0 && (lists[c][cnt[c] - 1] & 0x8000);
    const bool may_t = cnt[c] > 0 && !after_tail;
    const int left = len[c] - cnt[c], q = quota[c] - ntail[c];
    const bool due = (long long)(gt / 7) * quota[c] * 8 >= (long long)(ntail[c] * 8 + (c * 5 & 7)) * ntails;
    bool tail = may_t && q > 0 && (2 * q > left || (gn - gt >= TAIL_LATE && due) || gn - gt >= TAIL_MAX);
    if (4 * quota[c] >= len[c]) {
      const int m = len[c] - 1, phase = c / step * 11 % m;
      tail = may_t && q > 0 && (2 * q > left || (cnt[c] * quota[c] + phase) / m > ntail[c]);
    }
    if (gt >= NROUNDS) tail = false;
    if (gn >= NROUNDS) tail = true;
    const int g = tail ? gt : gn;
    if (tail) { gt += 7; ntail[c]++; }
    else { gn++; if (gn % 7 == 3) gn++; }
    const bool form_t = tail && may_t;
    lists[c][cnt[c]++] = (uint16_t)(g | (form_t ? 0x8000 : 0));
    busy[c] += form_t ? COST_T : after_tail ? COST_TN : COST_N;
  }
  bool use_tail = true;
  for (int c = 0; c < nclusters; c++) if (cnt[c] > MAX_ROUNDS) use_tail = false;
  if (!use_tail) for (int c = 0; c < nclusters; c++) for (int i = 0; i < cnt[c]; i++) lists[c][i] &= 0x7fff;
  int pos = 0;
  for (int c = 0; c < nclusters; c++) {
    s.start[c] = (uint16_t)pos;
    s.tails[c] = 0;
    for (int i = 0; i < cnt[c]; i++) {
      if (lists[c][i] & 0x8000) s.tails[c] |= 1u << i;
      const int g = lists[c][i] & 0x7ff, p = g / 7, r = g % 7;
      s.list[pos++] = (uint16_t)((2 * p + (r > 3)) | (r & 3) << 9 | (lists[c][i] & 0x8000));
    }
  }
  for (int c = nclusters; c <= MAX_CLUSTERS; c++) s.start[c] = (uint16_t)pos;
  s.list[NROUNDS] = 0;
}

}

extern "C" void kernel_launch(void* const* d_in, const int* in_sizes, int n_in, void* d_out, int out_size) {
  static EncodeFn encode = nullptr;
  static int nclusters = 0;
  static Schedule sched;
  if (!encode) {
    void* fn = nullptr;
    cudaDriverEntryPointQueryResult qr;
    cudaGetDriverEntryPoint("cuTensorMapEncodeTiled", &fn, cudaEnableDefault, &qr);
    encode = (EncodeFn)fn;
    int dev = 0, nsm = 0;
    cudaGetDevice(&dev);
    cudaDeviceGetAttribute(&nsm, cudaDevAttrMultiProcessorCount, dev);
    nclusters = nsm / 2 < MAX_CLUSTERS ? nsm / 2 : MAX_CLUSTERS;
    make_schedule(sched, nclusters);
    cudaFuncSetAttribute(attn_kernel, cudaFuncAttributeMaxDynamicSharedMemorySize, SMEM_BYTES);
  }
  CUtensorMap tmQ, tmQT, tmK, tmV, tmO;
  make_map(encode, &tmQ, d_in[0], SQ, 64);
  make_map(encode, &tmQT, d_in[0], SQ, 16);
  make_map(encode, &tmK, d_in[1], SK, 64);
  make_map(encode, &tmV, d_in[2], SK, 64);
  make_map(encode, &tmO, d_out, SQ, OROWS);
  attn_kernel<<<2 * nclusters, NTHREADS, SMEM_BYTES>>>(tmQ, tmQT, tmK, tmV, tmO, sched);
}
```

```cpp
#include <cuda_runtime.h>
#include <cuda_bf16.h>
#include <cuda.h>
#include <stdint.h>

namespace {

constexpr int NHEADS = 512;
constexpr int SQ = 848;
constexpr int SK = 512;
constexpr int HD = 192;
constexpr int BN = 64;
constexpr int NBLK = SK / BN;
constexpr int SLOT = 64 * HD * 2;
constexpr int SLAB = 1024;
constexpr int RGRP = 3 * SLAB;
constexpr int NSLOT = 7;
constexpr int NROUNDS = (NHEADS / 2) * 7;
constexpr int NTHREADS = 384;
constexpr int OFF_QO = 0;
constexpr int OFF_KV = 2 * SLOT;
constexpr int OFF_QT = (2 + NSLOT) * SLOT;
constexpr int OFF_PT = OFF_QT + 3 * 2048;
constexpr int OFF_RED = OFF_PT + 2 * 2048;
constexpr int OFF_BAR = OFF_RED + 256;
constexpr int SMEM_BYTES = OFF_BAR + 256;

#define ESPLIT 8
#define OROWS 16
#define STAGGER 250
#define NT_SPLIT 4
#define QREQ0 8
#define QREQ1 14
constexpr uint32_t WAIT_LIMIT = 1u << 18;
#define SUSPEND 20000
constexpr uint32_t SUSPEND_NS = SUSPEND;

constexpr float SCALE_LOG2 = 0.07216878364870322f * 1.4426950408889634f;
__device__ __forceinline__ void check_inv(float a, float b, uint32_t& mask, uint32_t bit) {
  asm("{\n.reg .pred p;\nsetp.ge.f32 p, %1, 0f1F800000;\nsetp.le.and.f32 p, %1, 0f53800000, p;\n"
      "setp.ge.and.f32 p, %2, 0f1F800000, p;\nsetp.le.and.f32 p, %2, 0f53800000, p;\n@!p or.b32 %0, %0, %3;\n}\n"
      : "+r"(mask) : "f"(a), "f"(b), "r"(bit));
}

__device__ __forceinline__ uint32_t smem_u32(const void* p) { return (uint32_t)__cvta_generic_to_shared(p); }
__device__ __forceinline__ void wg_fence() { asm volatile("wgmma.fence.sync.aligned;" ::: "memory"); }
__device__ __forceinline__ void wg_commit() { asm volatile("wgmma.commit_group.sync.aligned;" ::: "memory"); }
template <int N> __device__ __forceinline__ void wg_wait() { asm volatile("wgmma.wait_group.sync.aligned %0;" ::"n"(N) : "memory"); }
template <int N> __device__ __forceinline__ void fence_regs(float (&r)[N]) {
#pragma unroll
  for (int i = 0; i < N; i++) asm volatile("" : "+f"(r[i])::"memory");
}
template <int N> __device__ __forceinline__ void fence_regs(uint32_t (&r)[N]) {
#pragma unroll
  for (int i = 0; i < N; i++) asm volatile("" : "+r"(r[i])::"memory");
}

__device__ __forceinline__ void mbar_init(uint32_t bar, uint32_t cnt) {
  asm volatile("mbarrier.init.shared::cta.b64 [%0], %1;" ::"r"(bar), "r"(cnt));
}
__device__ __forceinline__ void mbar_expect_tx(uint32_t bar, uint32_t bytes) {
  asm volatile("mbarrier.arrive.expect_tx.shared::cta.b64 _, [%0], %1;" ::"r"(bar), "r"(bytes) : "memory");
}
__device__ __forceinline__ void mbar_arrive(uint32_t bar) {
  asm volatile("mbarrier.arrive.shared::cta.b64 _, [%0];" ::"r"(bar) : "memory");
}
__device__ __forceinline__ bool mbar_try(uint32_t bar, uint32_t parity) {
  uint32_t ok;
  asm volatile(
      "{\n.reg .pred p;\nmbarrier.try_wait.parity.shared::cta.b64 p, [%1], %2;\nselp.b32 %0, 1, 0, p;\n}\n"
      : "=r"(ok)
      : "r"(bar), "r"(parity)
      : "memory");
  return ok;
}
__device__ __forceinline__ bool mbar_try_sleep(uint32_t bar, uint32_t parity) {
  uint32_t ok;
  asm volatile(
      "{\n.reg .pred p;\nmbarrier.try_wait.parity.shared::cta.b64 p, [%1], %2, %3;\nselp.b32 %0, 1, 0, p;\n}\n"
      : "=r"(ok)
      : "r"(bar), "r"(parity), "r"(SUSPEND_NS)
      : "memory");
  return ok;
}
__device__ __forceinline__ void mbar_wait(uint32_t bar, uint32_t parity) {
  if (mbar_try(bar, parity)) return;
  for (uint32_t n = 0; n < WAIT_LIMIT; n++)
    if (mbar_try(bar, parity)) break;
}
__device__ __forceinline__ void mbar_wait_sleep(uint32_t bar, uint32_t parity) {
  for (uint32_t n = 0; n < WAIT_LIMIT; n++) {
    if (mbar_try_sleep(bar, parity)) break;
  }
}

__device__ __forceinline__ void tma_load(uint32_t dst, const CUtensorMap* tm, uint32_t bar, int row, int head, uint64_t pol) {
  asm volatile(
      "cp.async.bulk.tensor.5d.shared::cluster.global.mbarrier::complete_tx::bytes.L2::cache_hint"
      " [%0], [%1, {%3, %3, %3, %4, %5}], [%2], %6;" ::"r"(dst),
      "l"(tm), "r"(bar), "r"(0), "r"(row >> 3), "r"(head), "l"(pol)
      : "memory");
}
__device__ __forceinline__ void tma_load_mc(uint32_t dst, const CUtensorMap* tm, uint32_t bar, int row, int head, uint64_t pol) {
  asm volatile(
      "cp.async.bulk.tensor.5d.shared::cluster.global.mbarrier::complete_tx::bytes.multicast::cluster.L2::cache_hint"
      " [%0], [%1, {%3, %3, %3, %4, %5}], [%2], %7, %6;" ::"r"(dst),
      "l"(tm), "r"(bar), "r"(0), "r"(row >> 3), "r"(head), "l"(pol), "h"((uint16_t)3)
      : "memory");
}
__device__ __forceinline__ bool elect_one() {
  uint32_t r;
  asm volatile("{\n.reg .pred e;\nelect.sync _|e, 0xffffffff;\nselp.b32 %0, 1, 0, e;\n}\n" : "=r"(r));
  return r;
}
__device__ __forceinline__ void tma_store(const CUtensorMap* tm, uint32_t src, int row, int head, uint64_t pol) {
  asm volatile(
      "cp.async.bulk.tensor.5d.global.shared::cta.bulk_group.L2::cache_hint"
      " [%0, {%2, %2, %2, %3, %4}], [%1], %5;" ::"l"(tm),
      "r"(src), "r"(0), "r"(row >> 3), "r"(head), "l"(pol)
      : "memory");
}
__device__ __forceinline__ void ldsm_x4(uint32_t addr, uint32_t& r0, uint32_t& r1, uint32_t& r2, uint32_t& r3) {
  asm volatile("ldmatrix.sync.aligned.m8n8.x4.shared.b16 {%0, %1, %2, %3}, [%4];"
               : "=r"(r0), "=r"(r1), "=r"(r2), "=r"(r3)
               : "r"(addr)
               : "memory");
}
__device__ __forceinline__ void stsm_x4(uint32_t addr, uint32_t r0, uint32_t r1, uint32_t r2, uint32_t r3) {
  asm volatile("stmatrix.sync.aligned.m8n8.x4.shared.b16 [%0], {%1, %2, %3, %4};" ::"r"(addr), "r"(r0), "r"(r1), "r"(r2), "r"(r3)
               : "memory");
}
__device__ __forceinline__ void stsm_x4_trans(uint32_t addr, uint32_t r0, uint32_t r1, uint32_t r2, uint32_t r3) {
  asm volatile("stmatrix.sync.aligned.m8n8.x4.trans.shared.b16 [%0], {%1, %2, %3, %4};" ::"r"(addr), "r"(r0), "r"(r1), "r"(r2), "r"(r3)
               : "memory");
}
__device__ __forceinline__ float ex2(float x) {
  float y;
  asm("ex2.approx.ftz.f32 %0, %1;" : "=f"(y) : "f"(x));
  return y;
}
__device__ __forceinline__ float rcp(float x) {
  float y;
  asm("rcp.approx.ftz.f32 %0, %1;" : "=f"(y) : "f"(x));
  return y;
}
__device__ __forceinline__ uint32_t pack_bf16(float lo, float hi) {
  uint32_t r;
  asm("cvt.rn.bf16x2.f32 %0, %1, %2;" : "=r"(r) : "f"(hi), "f"(lo));
  return r;
}
__device__ __forceinline__ void wgmma_qk(float (&d)[32], uint32_t a0, uint32_t a1, uint32_t a2, uint32_t a3, uint64_t db, int scale_d) {
  asm volatile("{\n.reg .pred p;\nsetp.ne.b32 p, %37, 0;\n"
    "wgmma.mma_async.sync.aligned.m64n64k16.f32.bf16.bf16 "
    "{%0, %1, %2, %3, %4, %5, %6, %7, %8, %9, %10, %11, %12, %13, %14, %15, %16, %17, %18, %19, %20, %21, %22, %23, %24, %25, %26, %27, %28, %29, %30, %31}, "
    "{%32, %33, %34, %35}, %36, p, 1, 1, 0;\n}\n"
    : "+f"(d[0]), "+f"(d[1]), "+f"(d[2]), "+f"(d[3]), "+f"(d[4]), "+f"(d[5]), "+f"(d[6]), "+f"(d[7]), "+f"(d[8]), "+f"(d[9]), "+f"(d[10]), "+f"(d[11]), "+f"(d[12]), "+f"(d[13]), "+f"(d[14]), "+f"(d[15]), "+f"(d[16]), "+f"(d[17]), "+f"(d[18]), "+f"(d[19]), "+f"(d[20]), "+f"(d[21]), "+f"(d[22]), "+f"(d[23]), "+f"(d[24]), "+f"(d[25]), "+f"(d[26]), "+f"(d[27]), "+f"(d[28]), "+f"(d[29]), "+f"(d[30]), "+f"(d[31])
    : "r"(a0), "r"(a1), "r"(a2), "r"(a3), "l"(db), "r"(scale_d));
}

__device__ __forceinline__ void wgmma_pv(float (&d)[96], uint32_t a0, uint32_t a1, uint32_t a2, uint32_t a3, uint64_t db, int scale_d) {
  asm volatile("{\n.reg .pred p;\nsetp.ne.b32 p, %101, 0;\n"
    "wgmma.mma_async.sync.aligned.m64n192k16.f32.bf16.bf16 "
    "{%0, %1, %2, %3, %4, %5, %6, %7, %8, %9, %10, %11, %12, %13, %14, %15, %16, %17, %18, %19, %20, %21, %22, %23, %24, %25, %26, %27, %28, %29, %30, %31, %32, %33, %34, %35, %36, %37, %38, %39, %40, %41, %42, %43, %44, %45, %46, %47, %48, %49, %50, %51, %52, %53, %54, %55, %56, %57, %58, %59, %60, %61, %62, %63, %64, %65, %66, %67, %68, %69, %70, %71, %72, %73, %74, %75, %76, %77, %78, %79, %80, %81, %82, %83, %84, %85, %86, %87, %88, %89, %90, %91, %92, %93, %94, %95}, "
    "{%96, %97, %98, %99}, %100, p, 1, 1, 1;\n}\n"
    : "+f"(d[0]), "+f"(d[1]), "+f"(d[2]), "+f"(d[3]), "+f"(d[4]), "+f"(d[5]), "+f"(d[6]), "+f"(d[7]), "+f"(d[8]), "+f"(d[9]), "+f"(d[10]), "+f"(d[11]), "+f"(d[12]), "+f"(d[13]), "+f"(d[14]), "+f"(d[15]), "+f"(d[16]), "+f"(d[17]), "+f"(d[18]), "+f"(d[19]), "+f"(d[20]), "+f"(d[21]), "+f"(d[22]), "+f"(d[23]), "+f"(d[24]), "+f"(d[25]), "+f"(d[26]), "+f"(d[27]), "+f"(d[28]), "+f"(d[29]), "+f"(d[30]), "+f"(d[31]), "+f"(d[32]), "+f"(d[33]), "+f"(d[34]), "+f"(d[35]), "+f"(d[36]), "+f"(d[37]), "+f"(d[38]), "+f"(d[39]), "+f"(d[40]), "+f"(d[41]), "+f"(d[42]), "+f"(d[43]), "+f"(d[44]), "+f"(d[45]), "+f"(d[46]), "+f"(d[47]), "+f"(d[48]), "+f"(d[49]), "+f"(d[50]), "+f"(d[51]), "+f"(d[52]), "+f"(d[53]), "+f"(d[54]), "+f"(d[55]), "+f"(d[56]), "+f"(d[57]), "+f"(d[58]), "+f"(d[59]), "+f"(d[60]), "+f"(d[61]), "+f"(d[62]), "+f"(d[63]), "+f"(d[64]), "+f"(d[65]), "+f"(d[66]), "+f"(d[67]), "+f"(d[68]), "+f"(d[69]), "+f"(d[70]), "+f"(d[71]), "+f"(d[72]), "+f"(d[73]), "+f"(d[74]), "+f"(d[75]), "+f"(d[76]), "+f"(d[77]), "+f"(d[78]), "+f"(d[79]), "+f"(d[80]), "+f"(d[81]), "+f"(d[82]), "+f"(d[83]), "+f"(d[84]), "+f"(d[85]), "+f"(d[86]), "+f"(d[87]), "+f"(d[88]), "+f"(d[89]), "+f"(d[90]), "+f"(d[91]), "+f"(d[92]), "+f"(d[93]), "+f"(d[94]), "+f"(d[95])
    : "r"(a0), "r"(a1), "r"(a2), "r"(a3), "l"(db), "r"(scale_d));
}

__device__ __forceinline__ void wgmma_qkT(float (&d)[8], uint64_t da, uint64_t db, int scale_d) {
  asm volatile("{\n.reg .pred p;\nsetp.ne.b32 p, %10, 0;\n"
    "wgmma.mma_async.sync.aligned.m64n16k16.f32.bf16.bf16 "
    "{%0, %1, %2, %3, %4, %5, %6, %7}, "
    "%8, %9, p, 1, 1, 0, 0;\n}\n"
    : "+f"(d[0]), "+f"(d[1]), "+f"(d[2]), "+f"(d[3]), "+f"(d[4]), "+f"(d[5]), "+f"(d[6]), "+f"(d[7])
    : "l"(da), "l"(db), "r"(scale_d));
}
__device__ __forceinline__ void wgmma_pvT(float (&d)[8], uint64_t da, uint64_t db, int scale_d) {
  asm volatile("{\n.reg .pred p;\nsetp.ne.b32 p, %10, 0;\n"
    "wgmma.mma_async.sync.aligned.m64n16k16.f32.bf16.bf16 "
    "{%0, %1, %2, %3, %4, %5, %6, %7}, "
    "%8, %9, p, 1, 1, 1, 0;\n}\n"
    : "+f"(d[0]), "+f"(d[1]), "+f"(d[2]), "+f"(d[3]), "+f"(d[4]), "+f"(d[5]), "+f"(d[6]), "+f"(d[7])
    : "l"(da), "l"(db), "r"(scale_d));
}

__device__ __forceinline__ void wgmma_qk0(float (&d)[32], uint32_t a0, uint32_t a1, uint32_t a2, uint32_t a3, uint64_t db) {
  asm volatile("{\n.reg .pred p;\nsetp.ne.b32 p, 0, 0;\n"
    "wgmma.mma_async.sync.aligned.m64n64k16.f32.bf16.bf16 "
    "{%0, %1, %2, %3, %4, %5, %6, %7, %8, %9, %10, %11, %12, %13, %14, %15, %16, %17, %18, %19, %20, %21, %22, %23, %24, %25, %26, %27, %28, %29, %30, %31}, "
    "{%32, %33, %34, %35}, %36, p, 1, 1, 0;\n}\n"
    : "=f"(d[0]), "=f"(d[1]), "=f"(d[2]), "=f"(d[3]), "=f"(d[4]), "=f"(d[5]), "=f"(d[6]), "=f"(d[7]), "=f"(d[8]), "=f"(d[9]), "=f"(d[10]), "=f"(d[11]), "=f"(d[12]), "=f"(d[13]), "=f"(d[14]), "=f"(d[15]), "=f"(d[16]), "=f"(d[17]), "=f"(d[18]), "=f"(d[19]), "=f"(d[20]), "=f"(d[21]), "=f"(d[22]), "=f"(d[23]), "=f"(d[24]), "=f"(d[25]), "=f"(d[26]), "=f"(d[27]), "=f"(d[28]), "=f"(d[29]), "=f"(d[30]), "=f"(d[31])
    : "r"(a0), "r"(a1), "r"(a2), "r"(a3), "l"(db));
}
__device__ __forceinline__ void wgmma_pv0(float (&d)[96], uint32_t a0, uint32_t a1, uint32_t a2, uint32_t a3, uint64_t db) {
  asm volatile("{\n.reg .pred p;\nsetp.ne.b32 p, 0, 0;\n"
    "wgmma.mma_async.sync.aligned.m64n192k16.f32.bf16.bf16 "
    "{%0, %1, %2, %3, %4, %5, %6, %7, %8, %9, %10, %11, %12, %13, %14, %15, %16, %17, %18, %19, %20, %21, %22, %23, %24, %25, %26, %27, %28, %29, %30, %31, %32, %33, %34, %35, %36, %37, %38, %39, %40, %41, %42, %43, %44, %45, %46, %47, %48, %49, %50, %51, %52, %53, %54, %55, %56, %57, %58, %59, %60, %61, %62, %63, %64, %65, %66, %67, %68, %69, %70, %71, %72, %73, %74, %75, %76, %77, %78, %79, %80, %81, %82, %83, %84, %85, %86, %87, %88, %89, %90, %91, %92, %93, %94, %95}, "
    "{%96, %97, %98, %99}, %100, p, 1, 1, 1;\n}\n"
    : "=f"(d[0]), "=f"(d[1]), "=f"(d[2]), "=f"(d[3]), "=f"(d[4]), "=f"(d[5]), "=f"(d[6]), "=f"(d[7]), "=f"(d[8]), "=f"(d[9]), "=f"(d[10]), "=f"(d[11]), "=f"(d[12]), "=f"(d[13]), "=f"(d[14]), "=f"(d[15]), "=f"(d[16]), "=f"(d[17]), "=f"(d[18]), "=f"(d[19]), "=f"(d[20]), "=f"(d[21]), "=f"(d[22]), "=f"(d[23]), "=f"(d[24]), "=f"(d[25]), "=f"(d[26]), "=f"(d[27]), "=f"(d[28]), "=f"(d[29]), "=f"(d[30]), "=f"(d[31]), "=f"(d[32]), "=f"(d[33]), "=f"(d[34]), "=f"(d[35]), "=f"(d[36]), "=f"(d[37]), "=f"(d[38]), "=f"(d[39]), "=f"(d[40]), "=f"(d[41]), "=f"(d[42]), "=f"(d[43]), "=f"(d[44]), "=f"(d[45]), "=f"(d[46]), "=f"(d[47]), "=f"(d[48]), "=f"(d[49]), "=f"(d[50]), "=f"(d[51]), "=f"(d[52]), "=f"(d[53]), "=f"(d[54]), "=f"(d[55]), "=f"(d[56]), "=f"(d[57]), "=f"(d[58]), "=f"(d[59]), "=f"(d[60]), "=f"(d[61]), "=f"(d[62]), "=f"(d[63]), "=f"(d[64]), "=f"(d[65]), "=f"(d[66]), "=f"(d[67]), "=f"(d[68]), "=f"(d[69]), "=f"(d[70]), "=f"(d[71]), "=f"(d[72]), "=f"(d[73]), "=f"(d[74]), "=f"(d[75]), "=f"(d[76]), "=f"(d[77]), "=f"(d[78]), "=f"(d[79]), "=f"(d[80]), "=f"(d[81]), "=f"(d[82]), "=f"(d[83]), "=f"(d[84]), "=f"(d[85]), "=f"(d[86]), "=f"(d[87]), "=f"(d[88]), "=f"(d[89]), "=f"(d[90]), "=f"(d[91]), "=f"(d[92]), "=f"(d[93]), "=f"(d[94]), "=f"(d[95])
    : "r"(a0), "r"(a1), "r"(a2), "r"(a3), "l"(db));
}
__device__ __forceinline__ void wgmma_qkT0(float (&d)[8], uint64_t da, uint64_t db) {
  asm volatile("{\n.reg .pred p;\nsetp.ne.b32 p, 0, 0;\n"
    "wgmma.mma_async.sync.aligned.m64n16k16.f32.bf16.bf16 "
    "{%0, %1, %2, %3, %4, %5, %6, %7}, "
    "%8, %9, p, 1, 1, 0, 0;\n}\n"
    : "=f"(d[0]), "=f"(d[1]), "=f"(d[2]), "=f"(d[3]), "=f"(d[4]), "=f"(d[5]), "=f"(d[6]), "=f"(d[7])
    : "l"(da), "l"(db));
}
__device__ __forceinline__ void wgmma_pvT0(float (&d)[8], uint64_t da, uint64_t db) {
  asm volatile("{\n.reg .pred p;\nsetp.ne.b32 p, 0, 0;\n"
    "wgmma.mma_async.sync.aligned.m64n16k16.f32.bf16.bf16 "
    "{%0, %1, %2, %3, %4, %5, %6, %7}, "
    "%8, %9, p, 1, 1, 1, 0;\n}\n"
    : "=f"(d[0]), "=f"(d[1]), "=f"(d[2]), "=f"(d[3]), "=f"(d[4]), "=f"(d[5]), "=f"(d[6]), "=f"(d[7])
    : "l"(da), "l"(db));
}

struct Round { int head, qrow, mc; };
__device__ __forceinline__ Round decode_round(uint32_t e, uint32_t rank) {
  Round o;
  o.mc = (e & 0x600) != 0x600;
  o.head = (e & 0x1ff) + (o.mc ? 0 : rank);
  o.qrow = (e >> 1 & 0x300) + (o.mc ? rank * 128 : 0);
  return o;
}

__device__ __forceinline__ uint32_t kdesc0(uint32_t s_kv) { return ((s_kv & 0x3FFFFu) >> 4) | (1u << 16); }
__device__ __forceinline__ uint32_t vdesc0(uint32_t s_kv) { return ((s_kv & 0x3FFFFu) >> 4) | ((uint32_t)(SLAB >> 4) << 16); }
constexpr uint64_t DESC_HI = ((uint64_t)(RGRP >> 4) << 32) | ((uint64_t)1 << 62);
constexpr uint64_t DESC_HI_PT = ((uint64_t)(1024 >> 4) << 32) | ((uint64_t)1 << 62);

__device__ __forceinline__ void issue_qk(float (&S)[32], const uint32_t (&Q)[48], uint32_t kdesc) {
  const uint64_t d = DESC_HI | kdesc;
  wgmma_qk0(S, Q[0], Q[1], Q[2], Q[3], d);
#pragma unroll
  for (int kk = 1; kk < 12; kk++)
    wgmma_qk(S, Q[kk * 4], Q[kk * 4 + 1], Q[kk * 4 + 2], Q[kk * 4 + 3], d + (uint64_t)((kk / 4) * (SLAB / 16) + (kk % 4) * 2), 1);
}
__device__ __forceinline__ void issue_qk32(float (&S)[32], const uint32_t (&Q)[48], uint32_t kdesc) {
  uint32_t d[12];
#pragma unroll
  for (int kk = 0; kk < 12; kk++) {
    d[kk] = kdesc + ((kk / 4) * (SLAB / 16) + (kk % 4) * 2);
    asm volatile("" : "+r"(d[kk]));
  }
  wgmma_qk0(S, Q[0], Q[1], Q[2], Q[3], DESC_HI | d[0]);
#pragma unroll
  for (int kk = 1; kk < 12; kk++) wgmma_qk(S, Q[kk * 4], Q[kk * 4 + 1], Q[kk * 4 + 2], Q[kk * 4 + 3], DESC_HI | d[kk], 1);
}
__device__ __forceinline__ void issue_qk3(float (&S)[32], const uint32_t (&Q)[48], uint32_t kdesc) {
  const uint64_t d = DESC_HI | kdesc;
  wgmma_qk0(S, Q[0], Q[1], Q[2], Q[3], d);
#pragma unroll
  for (int kk = 1; kk < 12; kk++) {
    if (kk % 4 == 0) wg_commit();
    wgmma_qk(S, Q[kk * 4], Q[kk * 4 + 1], Q[kk * 4 + 2], Q[kk * 4 + 3], d + (uint64_t)((kk / 4) * (SLAB / 16) + (kk % 4) * 2), 1);
  }
}
template <bool ACCUMULATE>
__device__ __forceinline__ void issue_pv(float (&O)[96], const uint32_t (&P)[16], uint32_t vdesc) {
  const uint64_t d = DESC_HI | vdesc;
  if (ACCUMULATE) wgmma_pv(O, P[0], P[1], P[2], P[3], d, 1);
  else wgmma_pv0(O, P[0], P[1], P[2], P[3], d);
#pragma unroll
  for (int kk = 1; kk < 4; kk++)
    wgmma_pv(O, P[kk * 4], P[kk * 4 + 1], P[kk * 4 + 2], P[kk * 4 + 3], d + (uint64_t)(kk * (2 * RGRP / 16)), 1);
}

template <int K0 = 0, int K1 = 12>
__device__ __forceinline__ void load_q(uint32_t (&Q)[48], uint32_t lane_addr) {
#pragma unroll
  for (int kk = K0; kk < K1; kk++)
    ldsm_x4((lane_addr ^ ((kk % 4) << 5)) + (kk / 4) * SLAB, Q[kk * 4], Q[kk * 4 + 1], Q[kk * 4 + 2], Q[kk * 4 + 3]);
}

__device__ __forceinline__ void scale_q(uint32_t (&Q)[48]) {
  constexpr uint32_t C2 = 0x3DD53DD5u;
#pragma unroll
  for (int i = 0; i < 48; i++) asm("mul.rn.bf16x2 %0, %1, %2;" : "=r"(Q[i]) : "r"(Q[i]), "r"(C2));
  fence_regs(Q);
}
__device__ __forceinline__ void softmax_block(const float (&S)[32], uint32_t (&P)[16], float& l0, float& l1) {
#pragma unroll
  for (int i = 0; i < 8; i++) {
    const float a = ex2(S[4 * i + 0]);
    const float b = ex2(S[4 * i + 1]);
    const float c = ex2(S[4 * i + 2]);
    const float d = ex2(S[4 * i + 3]);
    l0 += a + b;
    l1 += c + d;
    P[2 * i] = pack_bf16(a, b);
    P[2 * i + 1] = pack_bf16(c, d);
  }
  fence_regs(P);
}

__device__ __forceinline__ void sums_put(uint32_t addr, float l0, float l1) {
  asm volatile("st.shared.v2.f32 [%0], {%1, %2};" ::"r"(addr), "f"(l0), "f"(l1) : "memory");
}
__device__ __forceinline__ void sums_get(uint32_t addr, float& s0, float& s1) {
  float a, b, c, d, e, f, g, h;
  asm volatile("ld.shared.v4.f32 {%0, %1, %2, %3}, [%8];\nld.shared.v4.f32 {%4, %5, %6, %7}, [%8 + 16];\n"
               : "=f"(a), "=f"(b), "=f"(c), "=f"(d), "=f"(e), "=f"(f), "=f"(g), "=f"(h) : "r"(addr & ~31u) : "memory");
  s0 = (a + c) + (e + g);
  s1 = (b + d) + (f + h);
}

template <int K0, int K1>
__device__ __forceinline__ void epilogue_part(const float (&O)[96], float i0, float i1, uint32_t lane_addr) {
#pragma unroll
  for (int kk = K0; kk < K1; kk++) {
    const int b = kk * 8;
    stsm_x4((lane_addr ^ ((kk % 4) << 5)) + (kk / 4) * SLAB,
            pack_bf16(O[b] * i0, O[b + 1] * i0), pack_bf16(O[b + 2] * i1, O[b + 3] * i1),
            pack_bf16(O[b + 4] * i0, O[b + 5] * i0), pack_bf16(O[b + 6] * i1, O[b + 7] * i1));
  }
}
__device__ __forceinline__ void epilogue_done(uint32_t bar, int lane) {
  __syncwarp();
  if (lane == 0) mbar_arrive(bar);
}

__device__ __forceinline__ void redo_tile(const CUtensorMap* tmQ, const CUtensorMap* tmK, const CUtensorMap* tmV, const CUtensorMap* tmO,
                                          int head, int row, uint32_t qo, uint32_t kv, uint32_t lane_addr, uint32_t bar, uint32_t& phase,
                                          uint32_t wg_bar) {
  float O[96], S[32];
  uint32_t Q[48], P[16];
  uint64_t pol;
  asm volatile("createpolicy.fractional.L2::evict_normal.b64 %0, 1.0;" : "=l"(pol));
  const bool leader = (threadIdx.x & 127) == 0;
  if (leader) {
    mbar_expect_tx(bar, SLOT);
    tma_load(qo, tmQ, bar, row, head, pol);
  }
  mbar_wait(bar, phase);
  phase ^= 1;
  load_q(Q, lane_addr);
  float m0 = -INFINITY, m1 = -INFINITY, l0 = 0.f, l1 = 0.f;
#pragma unroll
  for (int i = 0; i < 96; i++) O[i] = 0.f;
#pragma unroll 1
  for (int j = 0; j < NBLK; j++) {
    asm volatile("bar.sync %0, 128;" ::"r"(wg_bar) : "memory");
    if (leader) {
      mbar_expect_tx(bar, 2 * SLOT);
      tma_load(kv, tmK, bar, j * BN, head, pol);
      tma_load(kv + SLOT, tmV, bar, j * BN, head, pol);
    }
    mbar_wait(bar, phase);
    phase ^= 1;
    wg_fence();
    issue_qk(S, Q, kdesc0(kv));
    wg_commit();
    wg_wait<0>();
    fence_regs(S);
    float n0 = m0, n1 = m1;
#pragma unroll
    for (int i = 0; i < 8; i++) {
      n0 = fmaxf(n0, fmaxf(S[4 * i], S[4 * i + 1]));
      n1 = fmaxf(n1, fmaxf(S[4 * i + 2], S[4 * i + 3]));
    }
#pragma unroll
    for (int o = 1; o < 4; o <<= 1) {
      n0 = fmaxf(n0, __shfl_xor_sync(0xffffffffu, n0, o));
      n1 = fmaxf(n1, __shfl_xor_sync(0xffffffffu, n1, o));
    }
    const float f0 = ex2((m0 - n0) * SCALE_LOG2), f1 = ex2((m1 - n1) * SCALE_LOG2);
    m0 = n0; m1 = n1;
    l0 *= f0; l1 *= f1;
#pragma unroll
    for (int i = 0; i < 24; i++) {
      O[4 * i] *= f0; O[4 * i + 1] *= f0; O[4 * i + 2] *= f1; O[4 * i + 3] *= f1;
    }
#pragma unroll
    for (int i = 0; i < 8; i++) {
      S[4 * i] = (S[4 * i] - m0) * SCALE_LOG2; S[4 * i + 1] = (S[4 * i + 1] - m0) * SCALE_LOG2;
      S[4 * i + 2] = (S[4 * i + 2] - m1) * SCALE_LOG2; S[4 * i + 3] = (S[4 * i + 3] - m1) * SCALE_LOG2;
    }
    softmax_block(S, P, l0, l1);
    fence_regs(O);
    wg_fence();
    issue_pv<true>(O, P, vdesc0(kv + SLOT));
    wg_commit();
    wg_wait<0>();
    fence_regs(O);
  }
#pragma unroll
  for (int o = 1; o < 4; o <<= 1) {
    l0 += __shfl_xor_sync(0xffffffffu, l0, o);
    l1 += __shfl_xor_sync(0xffffffffu, l1, o);
  }
  epilogue_part<0, 12>(O, rcp(l0), rcp(l1), lane_addr);
  asm volatile("fence.proxy.async.shared::cta;" ::: "memory");
  asm volatile("bar.sync %0, 128;" ::"r"(wg_bar) : "memory");
  if (leader) {
    for (int i = 0; i < 64 && row + i < SQ; i += OROWS) tma_store(tmO, qo + i / 8 * RGRP, row + i, head, pol);
    asm volatile("cp.async.bulk.commit_group;" ::: "memory");
    asm volatile("cp.async.bulk.wait_group 0;" ::: "memory");
  }
}

__device__ __forceinline__ void wg_barrier() { asm volatile("bar.sync 3, 128;" ::: "memory"); }

__device__ __forceinline__ void tail_reduce(float (&v)[4], uint32_t red, int warp, int lane) {
#pragma unroll
  for (int o = 4; o < 32; o <<= 1)
#pragma unroll
    for (int i = 0; i < 4; i++) v[i] += __shfl_xor_sync(0xffffffffu, v[i], o);
  if (lane < 4)
    asm volatile("st.shared.v4.f32 [%0], {%1, %2, %3, %4};" ::"r"(red + (warp * 4 + lane) * 16), "f"(v[0]), "f"(v[1]), "f"(v[2]), "f"(v[3]) : "memory");
  wg_barrier();
#pragma unroll
  for (int ww = 0; ww < 4; ww++) {
    float x0, x1, x2, x3;
    asm volatile("ld.shared.v4.f32 {%0, %1, %2, %3}, [%4];" : "=f"(x0), "=f"(x1), "=f"(x2), "=f"(x3) : "r"(red + (ww * 4 + (lane & 3)) * 16) : "memory");
    if (ww == 0) { v[0] = x0; v[1] = x1; v[2] = x2; v[3] = x3; }
    else { v[0] += x0; v[1] += x1; v[2] += x2; v[3] += x3; }
  }
}

__device__ __forceinline__ void tail_softmax(const float (&S)[8], float (&l)[4], uint32_t pt_addr) {
  float e[8];
#pragma unroll
  for (int i = 0; i < 8; i++) e[i] = ex2(S[i] * SCALE_LOG2);
  stsm_x4_trans(pt_addr, pack_bf16(e[0], e[1]), pack_bf16(e[2], e[3]), pack_bf16(e[4], e[5]), pack_bf16(e[6], e[7]));
  l[0] += e[0] + e[2]; l[1] += e[1] + e[3]; l[2] += e[4] + e[6]; l[3] += e[5] + e[7];
}

__device__ __forceinline__ void issue_qkT(float (&S8)[8], uint32_t kdesc, uint32_t qt_addr) {
  const uint64_t da = DESC_HI | kdesc;
  const uint64_t db = DESC_HI | (uint64_t)(((qt_addr & 0x3FFFFu) >> 4) | (1u << 16));
  wgmma_qkT0(S8, da, db);
#pragma unroll
  for (int kk = 1; kk < 12; kk++)
    wgmma_qkT(S8, da + (uint64_t)((kk / 4) * (SLAB / 16) + (kk % 4) * 2), db + (uint64_t)((kk / 4) * (SLAB / 16) + (kk % 4) * 2), 1);
}
template <bool ACCUMULATE>
__device__ __forceinline__ void issue_pvT(float (&O)[3][8], uint32_t vdesc, uint32_t pt_base) {
  const uint64_t da = DESC_HI | vdesc;
  const uint64_t db = DESC_HI_PT | (uint64_t)(((pt_base & 0x3FFFFu) >> 4) | (1u << 16));
#pragma unroll
  for (int kk = 0; kk < 4; kk++)
#pragma unroll
    for (int b = 0; b < 3; b++) {
      if (kk == 0 && !ACCUMULATE) wgmma_pvT0(O[b], da + (uint64_t)(b * (SLAB / 16)), db);
      else wgmma_pvT(O[b], da + (uint64_t)(b * (SLAB / 16) + kk * (2 * RGRP / 16)), db + (uint64_t)(kk * 2), 1);
    }
}

template <bool B> struct Bool { static constexpr bool value = B; };

constexpr int MAX_CLUSTERS = 72;
constexpr int MAX_ROUNDS = 32;
struct Schedule {
  uint32_t tails[MAX_CLUSTERS];
  uint16_t start[MAX_CLUSTERS + 1];
  uint16_t list[NROUNDS + 1];
};

#define TRACE_TILE()

__global__ void __cluster_dims__(2, 1, 1) __launch_bounds__(NTHREADS, 1)
attn_kernel(const __grid_constant__ CUtensorMap tmQ, const __grid_constant__ CUtensorMap tmQT, const __grid_constant__ CUtensorMap tmK,
            const __grid_constant__ CUtensorMap tmV, const __grid_constant__ CUtensorMap tmO, const __grid_constant__ Schedule sched) {
  extern __shared__ __align__(1024) uint8_t smem_raw[];
  const uint32_t c_entry = (uint32_t)clock();
  const uint32_t sbase = smem_u32(smem_raw);
  const uint32_t s_qo = sbase + OFF_QO;
  const uint32_t s_kv = sbase + OFF_KV;
  const uint32_t s_bar = sbase + OFF_BAR;
  const uint32_t bar_full = s_bar;
  const uint32_t bar_empty = s_bar + 8 * NSLOT;
  const uint32_t bar_qfull = s_bar + 16 * NSLOT;
  const uint32_t bar_ostg = bar_qfull + 16;
  const uint32_t bar_qreq = bar_ostg + 16;
  const uint32_t bar_redo = bar_qreq + 16;
  const uint32_t s_redo = bar_redo + 16;

  uint32_t rank;
  asm("mov.u32 %0, %%cluster_ctarank;" : "=r"(rank));
  const int cluster = blockIdx.x >> 1;
  auto get_rounds = [&](int& first, int& count) {
    uint32_t c;
    asm volatile("mov.u32 %0, %%ctaid.x;" : "=r"(c));
    c >>= 1;
    first = sched.start[c];
    count = sched.start[c + 1] - first;
  };

  if (threadIdx.x == 0) {
    asm volatile("prefetch.tensormap [%0];" ::"l"(&tmK) : "memory");
    asm volatile("prefetch.tensormap [%0];" ::"l"(&tmQ) : "memory");
    asm volatile("prefetch.tensormap [%0];" ::"l"(&tmV) : "memory");
    for (int i = 0; i < 3; i++) mbar_init(bar_full + 8 * i, 1);
    for (int i = 0; i < 2; i++) mbar_init(bar_qfull + 8 * i, 1);
    asm volatile("fence.mbarrier_init.release.cluster;" ::: "memory");
    asm volatile("fence.proxy.async.shared::cta;" ::: "memory");
    const int head = cluster / 3, qrow = cluster % 3 * 256 + rank * 128;
    uint64_t polq, polk;
    asm volatile("createpolicy.fractional.L2::evict_first.b64 %0, 1.0;" : "=l"(polq));
    asm volatile("createpolicy.fractional.L2::evict_unchanged.b64 %0, 1.0;" : "=l"(polk));
    while ((uint32_t)clock() - c_entry < (uint32_t)(cluster / 3 * STAGGER)) {}
    mbar_expect_tx(bar_full, SLOT);
    tma_load(s_kv, &tmK, bar_full, 0, head, polk);
    mbar_expect_tx(bar_qfull, SLOT);
    tma_load(s_qo, &tmQ, bar_qfull, qrow, head, polq);
    mbar_expect_tx(bar_full + 8, SLOT);
    tma_load(s_kv + SLOT, &tmK, bar_full + 8, BN, head, polk);
    mbar_expect_tx(bar_full + 16, SLOT);
    tma_load(s_kv + 2 * SLOT, &tmV, bar_full + 16, 0, head, polk);
    mbar_expect_tx(bar_qfull + 8, SLOT);
    tma_load(s_qo + SLOT, &tmQ, bar_qfull + 8, qrow + 64, head, polq);
  } else if (threadIdx.x == 32) {
    for (int i = 0; i < NSLOT; i++) {
      if (i >= 3) mbar_init(bar_full + 8 * i, 1);
      mbar_init(bar_empty + 8 * i, 4);
    }
    for (int i = 0; i < 2; i++) {
      mbar_init(bar_ostg + 8 * i, 4);
      mbar_init(bar_qreq + 8 * i, 1);
      mbar_init(bar_redo + 8 * i, 1);
      asm volatile("st.shared.u32 [%0], %1;" ::"r"(s_redo + 4 * i), "r"(0) : "memory");
    }
    asm volatile("fence.mbarrier_init.release.cluster;" ::: "memory");
    asm volatile("fence.proxy.async.shared::cta;" ::: "memory");
  }
  __syncthreads();
  asm volatile("barrier.cluster.arrive.relaxed.aligned;\nbarrier.cluster.wait.aligned;" ::: "memory");

  const int wg = __shfl_sync(0xffffffffu, threadIdx.x >> 7, 0);
  const int warp = __shfl_sync(0xffffffffu, (threadIdx.x >> 5) & 3, 0);
  const int lane = threadIdx.x & 31;

  if (wg == 0) {
    asm volatile("setmaxnreg.dec.sync.aligned.u32 24;");
    int first_round, nrounds;
    get_rounds(first_round, nrounds);
    const int nblocks = nrounds * NBLK;
    if (warp == 0) {
      uint64_t pol;
      asm volatile("createpolicy.fractional.L2::evict_unchanged.b64 %0, 1.0;" : "=l"(pol));
      uint32_t slot = 3, phase = 1;
      auto load = [&](const CUtensorMap* tm, int n, uint32_t owner) {
        const Round r = decode_round(sched.list[first_round + (n >> 3)], rank);
        uint32_t dst = s_kv + slot * SLOT, bar = bar_full + 8 * slot, mode = !r.mc ? 1 : rank == owner ? 2 : 0;
        int row = (n & 7) * BN, head = r.head;
        asm volatile("" : "+r"(dst), "+r"(bar), "+r"(mode), "+r"(row), "+r"(head));
        if (mode == 2) {
          mbar_wait(bar_empty + 8 * slot, phase);
          if (elect_one()) {
            tma_load_mc(dst, tm, bar, row, head, pol);
            mbar_expect_tx(bar, SLOT);
          }
        } else if (mode == 1) {
          mbar_wait(bar_empty + 8 * slot, phase);
          if (elect_one()) {
            tma_load(dst, tm, bar, row, head, pol);
            mbar_expect_tx(bar, SLOT);
          }
        } else {
          mbar_wait(bar_empty + 8 * slot, phase);
          if (elect_one()) mbar_expect_tx(bar, SLOT);
        }
        if (++slot == NSLOT) { slot = 0; phase ^= 1; }
      };
      auto request_q = [&](int n, int pos) {
        pos += (n & 7) * 2;
        if (lane == 0 && pos == QREQ0) mbar_arrive(bar_qreq);
        if (lane == 0 && pos == QREQ1) mbar_arrive(bar_qreq + 8);
      };
      for (int n = 1; n < nblocks; n++) {
        if (n + 1 < nblocks) {
          load(&tmK, n + 1, 0);
        } else {
          mbar_wait_sleep(bar_empty + 8 * slot, phase);
          if (++slot == NSLOT) { slot = 0; phase ^= 1; }
        }
        request_q(n, 0);
        load(&tmV, n, 1);
        request_q(n, 1);
      }
      for (int i = 0; i < NSLOT; i++) {
        if (i != NSLOT - 2) mbar_wait_sleep(bar_empty + 8 * slot, phase);
        if (++slot == NSLOT) { slot = 0; phase ^= 1; }
      }
    } else if (warp != 3) {
      const int w = warp - 1;
      uint64_t pol;
      asm volatile("createpolicy.fractional.L2::evict_first.b64 %0, 1.0;" : "=l"(pol));
      const uint32_t buf = s_qo + w * SLOT;
      mbar_wait_sleep(bar_ostg + 8 * w, 0);
      if (elect_one()) asm volatile("prefetch.tensormap [%0];" ::"l"(w ? &tmQT : &tmO) : "memory");
      for (int t = 0; t < nrounds; t++) {
        if (t + 1 < nrounds) {
          const uint32_t e = sched.list[first_round + t + 1];
          const Round r = decode_round(e, rank);
          const bool tail = w == 1 && (e & 0x8000);
          mbar_wait_sleep(bar_qreq + 8 * w, t & 1);
          if (elect_one()) {
            tma_load(tail ? sbase + OFF_QT : buf, tail ? &tmQT : &tmQ, bar_qfull + 8 * w, r.qrow + w * 64, r.head, pol);
            mbar_expect_tx(bar_qfull + 8 * w, tail ? 3 * 2048 : SLOT);
          }
        } else {
          if (elect_one()) mbar_arrive(bar_qfull + 8 * w);
        }
        const Round r = decode_round(sched.list[first_round + t], rank);
        const int row0 = r.qrow + w * 64;
        const int nrows = row0 + 64 <= SQ ? 64 : SQ % 64;
        mbar_wait_sleep(bar_ostg + 8 * w, ~t & 1);
        asm volatile("fence.proxy.async.shared::cta;" ::: "memory");
#pragma unroll 1
        for (int i = 0; i < nrows; i += OROWS) {
          if (elect_one()) {
            tma_store(&tmO, buf + i / 8 * RGRP, row0 + i, r.head, pol);
            asm volatile("cp.async.bulk.commit_group;" ::: "memory");
          }
          if (t + 1 < nrounds) asm volatile("cp.async.bulk.wait_group.read 0;" ::: "memory");
        }
      }
      asm volatile("cp.async.bulk.wait_group 0;" ::: "memory");
      if (elect_one()) mbar_arrive(bar_redo + 8 * w);
    } else {
      uint32_t slot = 1, phase = 0;
      for (int n = 0; n < nblocks; n++) {
        if (n + 1 < nblocks) mbar_wait(bar_full + 8 * slot, phase);
        if (++slot == NSLOT) { slot = 0; phase ^= 1; }
        mbar_wait(bar_full + 8 * slot, phase);
        if (++slot == NSLOT) { slot = 0; phase ^= 1; }
        asm volatile("bar.sync 1, 288;" ::: "memory");
        asm volatile("bar.arrive 2, 288;" ::: "memory");
        TRACE_TILE();
      }
    }
  } else {
    asm volatile("setmaxnreg.inc.sync.aligned.u32 240;");
    const int w = wg - 1;
    int first_round, nrounds;
    get_rounds(first_round, nrounds);
    const int nblocks = nrounds * NBLK;
    float O[96], S[32];
    uint32_t Q[48], P0[16], P1[16];
    float l0 = 0.f, l1 = 0.f, inv0 = 1.f, inv1 = 1.f;
    uint32_t redo = 0;
    const uint32_t lane_addr = s_qo + w * SLOT + (warp * 2 + ((lane >> 3) & 1)) * RGRP + (lane & 7) * 128 + (((lane >> 4) ^ (lane & 7)) << 4);
    const uint32_t sum_addr = s_qo + w * SLOT + warp * 2 * RGRP + lane * 8;
    const uint32_t my_qfull = bar_qfull + 8 * w, my_ostg = bar_ostg + 8 * w;

    uint32_t empty_remote;
    asm("mapa.shared::cluster.u32 %0, %1, %2;" : "=r"(empty_remote) : "r"(bar_empty), "r"(threadIdx.x & 1));
    const bool releaser = (threadIdx.x & 127) < 2;
    auto release = [&](uint32_t s) {
      if (releaser) asm volatile("mbarrier.arrive.shared::cluster.b64 _, [%0];" ::"r"(empty_remote + s) : "memory");
    };
    uint32_t ks = 8, vs = 16, kp = 0, vp = 0;
    const uint32_t kd0 = kdesc0(s_kv), vd0 = vdesc0(s_kv);
    uint32_t kd = kd0 + ks * (SLOT / 128), vd = vd0 + vs * (SLOT / 128);
    auto advance = [&]() {
      kp = ks; vp = vs;
      ks = ks >= 8 * (NSLOT - 2) ? ks - 8 * (NSLOT - 2) : ks + 16;
      vs = vs >= 8 * (NSLOT - 2) ? vs - 8 * (NSLOT - 2) : vs + 16;
      kd = kd0 + ks * (SLOT / 128); vd = vd0 + vs * (SLOT / 128);
      asm volatile("" : "+r"(ks), "+r"(vs), "+r"(kd), "+r"(vd));
    };

    uint32_t tails = w == 1 ? sched.tails[cluster] : 0u;
    auto turn_wait = [&]() { asm volatile("bar.sync %0, 288;" ::"r"(1 + w) : "memory"); };
    auto turn_pass = [&]() { asm volatile("bar.arrive %0, 288;" ::"r"(2 - w) : "memory"); };
    if (w == 1) asm volatile("bar.arrive %0, 288;" ::"r"(1 + (tails & 1)) : "memory");

    mbar_wait(my_qfull, 0);
    load_q(Q, lane_addr);
    scale_q(Q);
    mbar_wait(bar_full, 0);
    wg_fence();
    issue_qk(S, Q, kd0);
    wg_commit();
    wg_wait<0>();
    fence_regs(S);
    release(0);
    __syncwarp();
    if (lane == 0) mbar_arrive(my_ostg);
    uint32_t pending = 0;

    int n = 0;
    auto finish_sums = [&]() {
      float s0, s1;
      sums_get(sum_addr, s0, s1);
      inv0 = rcp(s0); inv1 = rcp(s1);
      l0 = l1 = 0.f;
      asm volatile("" : "+f"(inv0), "+f"(inv1)::"memory");
    };
    auto check_sums = [&](int t) { check_inv(inv0, inv1, redo, 1u << (t & 31)); };

    int exit_n = -1;
#pragma unroll 1
    while (true) {
#pragma unroll 1
      while (true) {
        const int j = n & 7;
        softmax_block(S, P0, l0, l1);
        asm volatile("" : "+f"(l0), "+f"(l1)::"memory");
        if (j != 0) {
          wg_wait<0>();
          release(vp);
          turn_wait();
          wg_fence();
          issue_qk3(S, Q, kd);
          wg_commit();
          issue_pv<true>(O, P0, vd);
          wg_commit();
          turn_pass();
          advance();
          if (j == 6) {
            mbar_wait(my_qfull, ((n >> 3) + 1) & 1);
            wg_wait<3>();
            load_q<0, 4>(Q, lane_addr);
            wg_wait<2>();
            load_q<4, 8>(Q, lane_addr);
          }
          wg_wait<1>();
          fence_regs(S);
          fence_regs(P1);
        } else {
          wg_wait<0>();
          fence_regs(O);
          fence_regs(P1);
          if (pending) {
            release(vp);
            epilogue_part<0, ESPLIT>(O, inv0, inv1, lane_addr);
          }
          turn_wait();
          wg_fence();
          issue_qk32(S, Q, kd);
          wg_commit();
          if (pending) {
            epilogue_part<ESPLIT, 12>(O, inv0, inv1, lane_addr);
            epilogue_done(my_ostg, lane);
          }
          wg_fence();
          issue_pv<false>(O, P0, vd);
          wg_commit();
          turn_pass();
          advance();
          check_sums((n >> 3) - 1);
          exit_n = ((tails & 2) || n + 8 == nblocks) ? n + 6 : -1;
          tails >>= 1;
          asm volatile("" : "+r"(exit_n), "+r"(tails), "+r"(redo));
          wg_wait<1>();
          fence_regs(S);
          pending = true;
        }
        release(kp);
        softmax_block(S, P1, l0, l1);
        asm volatile("" : "+f"(l0), "+f"(l1)::"memory");
        if (j == 6) {
          load_q<8, 12>(Q, lane_addr);
          sums_put(sum_addr, l0, l1);
          wg_wait<0>();
          release(vp);
          scale_q(Q);
          if (n == exit_n) {
            turn_wait();
            wg_fence();
            issue_pv<true>(O, P1, vd);
            wg_commit();
            break;
          }
          asm volatile("" ::: "memory");
          turn_wait();
          wg_fence();
          issue_qk32(S, Q, kd);
          wg_commit();
          issue_pv<true>(O, P1, vd);
          wg_commit();
          turn_pass();
          advance();
          if (pending) finish_sums();
          wg_wait<1>();
        } else {
          wg_wait<0>();
          release(vp);
          turn_wait();
          wg_fence();
          issue_qk(S, Q, kd);
          wg_commit();
          issue_pv<true>(O, P1, vd);
          wg_commit();
          turn_pass();
          advance();
          wg_wait<1>();
        }
        fence_regs(S);
        fence_regs(P0);
        release(kp);
        n += 2;
      }
      if (n + 2 == nblocks) {
        if (w == 0) turn_pass();
        finish_sums();
        check_sums(n >> 3);
        wg_wait<0>();
        fence_regs(O);
        release(vs);
        epilogue_part<0, 12>(O, inv0, inv1, lane_addr);
        epilogue_done(my_ostg, lane);
        break;
      }
      const int t = n >> 3;
      const uint32_t qt = sbase + OFF_QT, pt = sbase + OFF_PT, red = sbase + OFF_RED;
      const uint32_t tl = ((lane & 7) + (lane >> 4) * 8) * 128 + (((warp * 2 + ((lane >> 3) & 1)) ^ (lane & 7)) << 4);
      const bool tlast = n + 10 == nblocks;
      float lt[4] = {0.f, 0.f, 0.f, 0.f};
      float ST[8], OT[3][8];
      wg_fence();
      issue_qkT(ST, kd, qt);
      wg_commit();
      turn_pass();
      finish_sums();
      check_sums(t);
      wg_wait<0>();
      fence_regs(ST);
      fence_regs(O);
      release(ks);
      release(vs);
      advance();
      epilogue_part<0, NT_SPLIT>(O, inv0, inv1, lane_addr);
      if (NT_SPLIT == 12) epilogue_done(my_ostg, lane);
      tail_softmax(ST, lt, pt + tl);
      auto tail_step = [&](auto first_c, int jj) {
        constexpr bool FIRST = decltype(first_c)::value;
        asm volatile("fence.proxy.async.shared::cta;" ::: "memory");
        turn_wait();
        wg_fence();
        issue_qkT(ST, kd, qt);
        wg_commit();
        issue_pvT<!FIRST>(OT, vd, pt + (jj & 1) * 2048);
        wg_commit();
        turn_pass();
        advance();
        wg_wait<1>();
        fence_regs(ST);
        release(kp);
        tail_softmax(ST, lt, pt + (~jj & 1) * 2048 + tl);
        wg_wait<0>();
        fence_regs(OT[0]); fence_regs(OT[1]); fence_regs(OT[2]);
        release(vp);
      };
      tail_step(Bool<true>(), 0);
      if (NT_SPLIT < 12) {
        epilogue_part<NT_SPLIT, 12>(O, inv0, inv1, lane_addr);
        epilogue_done(my_ostg, lane);
      }
#pragma unroll 1
      for (int jj = 1; jj < 7; jj++) tail_step(Bool<false>(), jj);
      mbar_wait(my_qfull, t & 1);
      load_q(Q, lane_addr);
      scale_q(Q);
      tail_reduce(lt, red, warp, lane);
#pragma unroll
      for (int i = 0; i < 4; i++) lt[i] = rcp(lt[i]);
      check_inv(lt[0], lt[1], redo, 1u << ((t + 1) & 31));
      check_inv(lt[2], lt[3], redo, 1u << ((t + 1) & 31));
      inv0 = inv1 = 1.f;
      asm volatile("fence.proxy.async.shared::cta;" ::: "memory");
      turn_wait();
      wg_fence();
      issue_pvT<true>(OT, vd, pt + 2048);
      wg_commit();
      issue_qk(S, Q, kd);
      wg_commit();
      if (!tlast) turn_pass();
      wg_wait<1>();
      fence_regs(OT[0]); fence_regs(OT[1]); fence_regs(OT[2]);
      release(vs);
#pragma unroll
      for (int b = 0; b < 3; b++)
        stsm_x4_trans(s_qo + SLOT + b * SLAB + tl + (lane >> 4) * (RGRP - 1024),
                      pack_bf16(OT[b][0] * lt[0], OT[b][1] * lt[1]), pack_bf16(OT[b][2] * lt[0], OT[b][3] * lt[1]),
                      pack_bf16(OT[b][4] * lt[2], OT[b][5] * lt[3]), pack_bf16(OT[b][6] * lt[2], OT[b][7] * lt[3]));
      epilogue_done(my_ostg, lane);
      wg_wait<0>();
      fence_regs(S);
      if (tlast) break;
      release(ks);
      advance();
#pragma unroll
      for (int i = 0; i < 96; i++) O[i] = 0.f;
      pending = false;
      n += 10;
      tails >>= 1;
    }
    if (redo) asm volatile("red.shared.or.b32 [%0], %1;" ::"r"(s_redo + 4 * w), "r"(redo) : "memory");
    asm volatile("bar.sync 4, 256;" ::: "memory");
    asm volatile("ld.shared.u32 %0, [%1];" : "=r"(redo) : "r"(s_redo + 4 * w) : "memory");
    redo = __shfl_sync(0xffffffffu, redo, 0);
    if (redo) {
      mbar_wait_sleep(bar_redo + 8 * w, 0);
      asm volatile("bar.sync %0, 128;" ::"r"(5 + w) : "memory");
      uint32_t phase = 1;
      get_rounds(first_round, nrounds);
      uint32_t rank;
      asm volatile("mov.u32 %0, %%cluster_ctarank;" : "=r"(rank));
#pragma unroll 1
      for (int t = 0; t < nrounds; t++) {
        if (!(redo >> (t & 31) & 1)) continue;
        const Round r = decode_round(sched.list[first_round + t], rank);
        redo_tile(&tmQ, &tmK, &tmV, &tmO, r.head, r.qrow + w * 64, s_qo + w * SLOT, s_kv + 2 * w * SLOT, lane_addr, bar_redo + 8 * w, phase, 5 + w);
      }
    }
  }
}

typedef CUresult (*EncodeFn)(CUtensorMap*, CUtensorMapDataType, cuuint32_t, void*, const cuuint64_t*, const cuuint64_t*,
                             const cuuint32_t*, const cuuint32_t*, CUtensorMapInterleave, CUtensorMapSwizzle,
                             CUtensorMapL2promotion, CUtensorMapFloatOOBfill);

void make_map(EncodeFn fn, CUtensorMap* tm, const void* ptr, int rows, int box_rows) {
  cuuint64_t dims[5] = {64, 8, 3, (cuuint64_t)rows / 8, (cuuint64_t)NHEADS};
  cuuint64_t strides[4] = {HD * 2, 128, 8 * HD * 2, (cuuint64_t)rows * HD * 2};
  cuuint32_t box[5] = {64, 8, 3, (cuuint32_t)box_rows / 8, 1};
  cuuint32_t estr[5] = {1, 1, 1, 1, 1};
  fn(tm, CU_TENSOR_MAP_DATA_TYPE_BFLOAT16, 5, const_cast<void*>(ptr), dims, strides, box, estr,
     CU_TENSOR_MAP_INTERLEAVE_NONE, CU_TENSOR_MAP_SWIZZLE_128B, CU_TENSOR_MAP_L2_PROMOTION_L2_128B, CU_TENSOR_MAP_FLOAT_OOB_FILL_NONE);
}

#define COST_N 12690
#define COST_T 10800
#define COST_TN 12720
#define TAIL_LATE 36
#define TAIL_MAX 60
#define HEAVY_STEP 3
static_assert(MAX_CLUSTERS / 3 * STAGGER < COST_T, "the first wave has to be handed out in the order of the clusters");
void make_schedule(Schedule& s, int nclusters) {
  static uint16_t lists[MAX_CLUSTERS][NROUNDS];
  int cnt[MAX_CLUSTERS] = {0}, len[MAX_CLUSTERS], ntail[MAX_CLUSTERS] = {0}, quota[MAX_CLUSTERS] = {0};
  long long busy[MAX_CLUSTERS], fin[MAX_CLUSTERS];
  const int ntails = NROUNDS / 7, base = NROUNDS / nclusters, nheavy = NROUNDS % nclusters;
  const int step = nheavy * HEAVY_STEP <= nclusters ? HEAVY_STEP : 1;
  for (int c = 0; c < nclusters; c++) {
    len[c] = base + (c % step == 0 && c / step < nheavy);
    busy[c] = c / 3 * STAGGER;
    fin[c] = busy[c] + (long long)len[c] * COST_N;
  }
  for (int k = 0; k < ntails; k++) {
    int c = -1;
    for (int i = 0; i < nclusters; i++)
      if (quota[i] < len[i] / 2 && (c < 0 || fin[i] > fin[c])) c = i;
    quota[c]++;
    fin[c] -= 2 * COST_N - COST_T - COST_TN;
  }
  int gn = 0, gt = 3;
  for (int k = 0; k < NROUNDS; k++) {
    int c = -1;
    for (int i = 0; i < nclusters; i++)
      if (cnt[i] < len[i] && (c < 0 || busy[i] < busy[c])) c = i;
    const bool after_tail = cnt[c] > 0 && (lists[c][cnt[c] - 1] & 0x8000);
    const bool may_t = cnt[c] > 0 && !after_tail;
    const int left = len[c] - cnt[c], q = quota[c] - ntail[c];
    const bool due = (long long)(gt / 7) * quota[c] * 8 >= (long long)(ntail[c] * 8 + (c * 5 & 7)) * ntails;
    bool tail = may_t && q > 0 && (2 * q > left || (gn - gt >= TAIL_LATE && due) || gn - gt >= TAIL_MAX);
    if (4 * quota[c] >= len[c]) {
      const int m = len[c] - 1, phase = c / step * 11 % m;
      tail = may_t && q > 0 && (2 * q > left || (cnt[c] * quota[c] + phase) / m > ntail[c]);
    }
    if (gt >= NROUNDS) tail = false;
    if (gn >= NROUNDS) tail = true;
    const int g = tail ? gt : gn;
    if (tail) { gt += 7; ntail[c]++; }
    else { gn++; if (gn % 7 == 3) gn++; }
    const bool form_t = tail && may_t;
    lists[c][cnt[c]++] = (uint16_t)(g | (form_t ? 0x8000 : 0));
    busy[c] += form_t ? COST_T : after_tail ? COST_TN : COST_N;
  }
  bool use_tail = true;
  for (int c = 0; c < nclusters; c++) if (cnt[c] > MAX_ROUNDS) use_tail = false;
  if (!use_tail) for (int c = 0; c < nclusters; c++) for (int i = 0; i < cnt[c]; i++) lists[c][i] &= 0x7fff;
  int pos = 0;
  for (int c = 0; c < nclusters; c++) {
    s.start[c] = (uint16_t)pos;
    s.tails[c] = 0;
    for (int i = 0; i < cnt[c]; i++) {
      if (lists[c][i] & 0x8000) s.tails[c] |= 1u << i;
      const int g = lists[c][i] & 0x7ff, p = g / 7, r = g % 7;
      s.list[pos++] = (uint16_t)((2 * p + (r > 3)) | (r & 3) << 9 | (lists[c][i] & 0x8000));
    }
  }
  for (int c = nclusters; c <= MAX_CLUSTERS; c++) s.start[c] = (uint16_t)pos;
  s.list[NROUNDS] = 0;
}

}

extern "C" void kernel_launch(void* const* d_in, const int* in_sizes, int n_in, void* d_out, int out_size) {
  static EncodeFn encode = nullptr;
  static int nclusters = 0;
  static Schedule sched;
  if (!encode) {
    void* fn = nullptr;
    cudaDriverEntryPointQueryResult qr;
    cudaGetDriverEntryPoint("cuTensorMapEncodeTiled", &fn, cudaEnableDefault, &qr);
    encode = (EncodeFn)fn;
    int dev = 0, nsm = 0;
    cudaGetDevice(&dev);
    cudaDeviceGetAttribute(&nsm, cudaDevAttrMultiProcessorCount, dev);
    nclusters = nsm / 2 < MAX_CLUSTERS ? nsm / 2 : MAX_CLUSTERS;
    make_schedule(sched, nclusters);
    cudaFuncSetAttribute(attn_kernel, cudaFuncAttributeMaxDynamicSharedMemorySize, SMEM_BYTES);
  }
  CUtensorMap tmQ, tmQT, tmK, tmV, tmO;
  make_map(encode, &tmQ, d_in[0], SQ, 64);
  make_map(encode, &tmQT, d_in[0], SQ, 16);
  make_map(encode, &tmK, d_in[1], SK, 64);
  make_map(encode, &tmV, d_in[2], SK, 64);
  make_map(encode, &tmO, d_out, SQ, OROWS);
  attn_kernel<<<2 * nclusters, NTHREADS, SMEM_BYTES>>>(tmQ, tmQT, tmK, tmV, tmO, sched);
}
```

```cpp
#include <cuda_runtime.h>
#include <cuda_bf16.h>
#include <cuda.h>
#include <stdint.h>

namespace {

constexpr int NHEADS = 512;
constexpr int SQ = 848;
constexpr int SK = 512;
constexpr int HD = 192;
constexpr int BN = 64;
constexpr int NBLK = SK / BN;
constexpr int SLOT = 64 * HD * 2;
constexpr int SLAB = 1024;
constexpr int RGRP = 3 * SLAB;
constexpr int NSLOT = 7;
constexpr int NROUNDS = (NHEADS / 2) * 7;
constexpr int NTHREADS = 384;
constexpr int OFF_QO = 0;
constexpr int OFF_KV = 2 * SLOT;
constexpr int OFF_QT = (2 + NSLOT) * SLOT;
constexpr int OFF_PT = OFF_QT + 3 * 2048;
constexpr int OFF_RED = OFF_PT + 2 * 2048;
constexpr int OFF_BAR = OFF_RED + 256;
constexpr int SMEM_BYTES = OFF_BAR + 256;

#define ESPLIT 8
#define OROWS 16
#define NT_SPLIT 4
#define QREQ0 8
#define QREQ1 13
constexpr uint32_t WAIT_LIMIT = 1u << 18;
#define SUSPEND 20000
constexpr uint32_t SUSPEND_NS = SUSPEND;

constexpr float SCALE_LOG2 = 0.07216878364870322f * 1.4426950408889634f;
__device__ __forceinline__ void check_inv(float a, float b, uint32_t& mask, uint32_t bit) {
  asm("{\n.reg .pred p;\nsetp.ge.f32 p, %1, 0f1F800000;\nsetp.le.and.f32 p, %1, 0f53800000, p;\n"
      "setp.ge.and.f32 p, %2, 0f1F800000, p;\nsetp.le.and.f32 p, %2, 0f53800000, p;\n@!p or.b32 %0, %0, %3;\n}\n"
      : "+r"(mask) : "f"(a), "f"(b), "r"(bit));
}

__device__ __forceinline__ uint32_t smem_u32(const void* p) { return (uint32_t)__cvta_generic_to_shared(p); }
__device__ __forceinline__ void wg_fence() { asm volatile("wgmma.fence.sync.aligned;" ::: "memory"); }
__device__ __forceinline__ void wg_commit() { asm volatile("wgmma.commit_group.sync.aligned;" ::: "memory"); }
template <int N> __device__ __forceinline__ void wg_wait() { asm volatile("wgmma.wait_group.sync.aligned %0;" ::"n"(N) : "memory"); }
template <int N> __device__ __forceinline__ void fence_regs(float (&r)[N]) {
#pragma unroll
  for (int i = 0; i < N; i++) asm volatile("" : "+f"(r[i])::"memory");
}
template <int N> __device__ __forceinline__ void fence_regs(uint32_t (&r)[N]) {
#pragma unroll
  for (int i = 0; i < N; i++) asm volatile("" : "+r"(r[i])::"memory");
}

__device__ __forceinline__ void mbar_init(uint32_t bar, uint32_t cnt) {
  asm volatile("mbarrier.init.shared::cta.b64 [%0], %1;" ::"r"(bar), "r"(cnt));
}
__device__ __forceinline__ void mbar_expect_tx(uint32_t bar, uint32_t bytes) {
  asm volatile("mbarrier.arrive.expect_tx.shared::cta.b64 _, [%0], %1;" ::"r"(bar), "r"(bytes) : "memory");
}
__device__ __forceinline__ void mbar_arrive(uint32_t bar) {
  asm volatile("mbarrier.arrive.shared::cta.b64 _, [%0];" ::"r"(bar) : "memory");
}
__device__ __forceinline__ bool mbar_try(uint32_t bar, uint32_t parity) {
  uint32_t ok;
  asm volatile(
      "{\n.reg .pred p;\nmbarrier.try_wait.parity.shared::cta.b64 p, [%1], %2;\nselp.b32 %0, 1, 0, p;\n}\n"
      : "=r"(ok)
      : "r"(bar), "r"(parity)
      : "memory");
  return ok;
}
__device__ __forceinline__ bool mbar_try_sleep(uint32_t bar, uint32_t parity) {
  uint32_t ok;
  asm volatile(
      "{\n.reg .pred p;\nmbarrier.try_wait.parity.shared::cta.b64 p, [%1], %2, %3;\nselp.b32 %0, 1, 0, p;\n}\n"
      : "=r"(ok)
      : "r"(bar), "r"(parity), "r"(SUSPEND_NS)
      : "memory");
  return ok;
}
__device__ __forceinline__ void mbar_wait(uint32_t bar, uint32_t parity) {
  if (mbar_try(bar, parity)) return;
  for (uint32_t n = 0; n < WAIT_LIMIT; n++)
    if (mbar_try(bar, parity)) break;
}
__device__ __forceinline__ void mbar_wait_sleep(uint32_t bar, uint32_t parity) {
  for (uint32_t n = 0; n < WAIT_LIMIT; n++) {
    if (mbar_try_sleep(bar, parity)) break;
  }
}

__device__ __forceinline__ void tma_load(uint32_t dst, const CUtensorMap* tm, uint32_t bar, int row, int head, uint64_t pol) {
  asm volatile(
      "cp.async.bulk.tensor.5d.shared::cluster.global.mbarrier::complete_tx::bytes.L2::cache_hint"
      " [%0], [%1, {%3, %3, %3, %4, %5}], [%2], %6;" ::"r"(dst),
      "l"(tm), "r"(bar), "r"(0), "r"(row >> 3), "r"(head), "l"(pol)
      : "memory");
}
__device__ __forceinline__ void tma_load_mc(uint32_t dst, const CUtensorMap* tm, uint32_t bar, int row, int head, uint64_t pol) {
  asm volatile(
      "cp.async.bulk.tensor.5d.shared::cluster.global.mbarrier::complete_tx::bytes.multicast::cluster.L2::cache_hint"
      " [%0], [%1, {%3, %3, %3, %4, %5}], [%2], %7, %6;" ::"r"(dst),
      "l"(tm), "r"(bar), "r"(0), "r"(row >> 3), "r"(head), "l"(pol), "h"((uint16_t)3)
      : "memory");
}
__device__ __forceinline__ bool elect_one() {
  uint32_t r;
  asm volatile("{\n.reg .pred e;\nelect.sync _|e, 0xffffffff;\nselp.b32 %0, 1, 0, e;\n}\n" : "=r"(r));
  return r;
}
__device__ __forceinline__ void tma_store(const CUtensorMap* tm, uint32_t src, int row, int head, uint64_t pol) {
  asm volatile(
      "cp.async.bulk.tensor.5d.global.shared::cta.bulk_group.L2::cache_hint"
      " [%0, {%2, %2, %2, %3, %4}], [%1], %5;" ::"l"(tm),
      "r"(src), "r"(0), "r"(row >> 3), "r"(head), "l"(pol)
      : "memory");
}
__device__ __forceinline__ void ldsm_x4(uint32_t addr, uint32_t& r0, uint32_t& r1, uint32_t& r2, uint32_t& r3) {
  asm volatile("ldmatrix.sync.aligned.m8n8.x4.shared.b16 {%0, %1, %2, %3}, [%4];"
               : "=r"(r0), "=r"(r1), "=r"(r2), "=r"(r3)
               : "r"(addr)
               : "memory");
}
__device__ __forceinline__ void stsm_x4(uint32_t addr, uint32_t r0, uint32_t r1, uint32_t r2, uint32_t r3) {
  asm volatile("stmatrix.sync.aligned.m8n8.x4.shared.b16 [%0], {%1, %2, %3, %4};" ::"r"(addr), "r"(r0), "r"(r1), "r"(r2), "r"(r3)
               : "memory");
}
__device__ __forceinline__ void stsm_x4_trans(uint32_t addr, uint32_t r0, uint32_t r1, uint32_t r2, uint32_t r3) {
  asm volatile("stmatrix.sync.aligned.m8n8.x4.trans.shared.b16 [%0], {%1, %2, %3, %4};" ::"r"(addr), "r"(r0), "r"(r1), "r"(r2), "r"(r3)
               : "memory");
}
__device__ __forceinline__ float ex2(float x) {
  float y;
  asm("ex2.approx.ftz.f32 %0, %1;" : "=f"(y) : "f"(x));
  return y;
}
__device__ __forceinline__ float rcp(float x) {
  float y;
  asm("rcp.approx.ftz.f32 %0, %1;" : "=f"(y) : "f"(x));
  return y;
}
__device__ __forceinline__ uint32_t pack_bf16(float lo, float hi) {
  uint32_t r;
  asm("cvt.rn.bf16x2.f32 %0, %1, %2;" : "=r"(r) : "f"(hi), "f"(lo));
  return r;
}
__device__ __forceinline__ void wgmma_qk(float (&d)[32], uint32_t a0, uint32_t a1, uint32_t a2, uint32_t a3, uint64_t db, int scale_d) {
  asm volatile("{\n.reg .pred p;\nsetp.ne.b32 p, %37, 0;\n"
    "wgmma.mma_async.sync.aligned.m64n64k16.f32.bf16.bf16 "
    "{%0, %1, %2, %3, %4, %5, %6, %7, %8, %9, %10, %11, %12, %13, %14, %15, %16, %17, %18, %19, %20, %21, %22, %23, %24, %25, %26, %27, %28, %29, %30, %31}, "
    "{%32, %33, %34, %35}, %36, p, 1, 1, 0;\n}\n"
    : "+f"(d[0]), "+f"(d[1]), "+f"(d[2]), "+f"(d[3]), "+f"(d[4]), "+f"(d[5]), "+f"(d[6]), "+f"(d[7]), "+f"(d[8]), "+f"(d[9]), "+f"(d[10]), "+f"(d[11]), "+f"(d[12]), "+f"(d[13]), "+f"(d[14]), "+f"(d[15]), "+f"(d[16]), "+f"(d[17]), "+f"(d[18]), "+f"(d[19]), "+f"(d[20]), "+f"(d[21]), "+f"(d[22]), "+f"(d[23]), "+f"(d[24]), "+f"(d[25]), "+f"(d[26]), "+f"(d[27]), "+f"(d[28]), "+f"(d[29]), "+f"(d[30]), "+f"(d[31])
    : "r"(a0), "r"(a1), "r"(a2), "r"(a3), "l"(db), "r"(scale_d));
}

__device__ __forceinline__ void wgmma_pv(float (&d)[96], uint32_t a0, uint32_t a1, uint32_t a2, uint32_t a3, uint64_t db, int scale_d) {
  asm volatile("{\n.reg .pred p;\nsetp.ne.b32 p, %101, 0;\n"
    "wgmma.mma_async.sync.aligned.m64n192k16.f32.bf16.bf16 "
    "{%0, %1, %2, %3, %4, %5, %6, %7, %8, %9, %10, %11, %12, %13, %14, %15, %16, %17, %18, %19, %20, %21, %22, %23, %24, %25, %26, %27, %28, %29, %30, %31, %32, %33, %34, %35, %36, %37, %38, %39, %40, %41, %42, %43, %44, %45, %46, %47, %48, %49, %50, %51, %52, %53, %54, %55, %56, %57, %58, %59, %60, %61, %62, %63, %64, %65, %66, %67, %68, %69, %70, %71, %72, %73, %74, %75, %76, %77, %78, %79, %80, %81, %82, %83, %84, %85, %86, %87, %88, %89, %90, %91, %92, %93, %94, %95}, "
    "{%96, %97, %98, %99}, %100, p, 1, 1, 1;\n}\n"
    : "+f"(d[0]), "+f"(d[1]), "+f"(d[2]), "+f"(d[3]), "+f"(d[4]), "+f"(d[5]), "+f"(d[6]), "+f"(d[7]), "+f"(d[8]), "+f"(d[9]), "+f"(d[10]), "+f"(d[11]), "+f"(d[12]), "+f"(d[13]), "+f"(d[14]), "+f"(d[15]), "+f"(d[16]), "+f"(d[17]), "+f"(d[18]), "+f"(d[19]), "+f"(d[20]), "+f"(d[21]), "+f"(d[22]), "+f"(d[23]), "+f"(d[24]), "+f"(d[25]), "+f"(d[26]), "+f"(d[27]), "+f"(d[28]), "+f"(d[29]), "+f"(d[30]), "+f"(d[31]), "+f"(d[32]), "+f"(d[33]), "+f"(d[34]), "+f"(d[35]), "+f"(d[36]), "+f"(d[37]), "+f"(d[38]), "+f"(d[39]), "+f"(d[40]), "+f"(d[41]), "+f"(d[42]), "+f"(d[43]), "+f"(d[44]), "+f"(d[45]), "+f"(d[46]), "+f"(d[47]), "+f"(d[48]), "+f"(d[49]), "+f"(d[50]), "+f"(d[51]), "+f"(d[52]), "+f"(d[53]), "+f"(d[54]), "+f"(d[55]), "+f"(d[56]), "+f"(d[57]), "+f"(d[58]), "+f"(d[59]), "+f"(d[60]), "+f"(d[61]), "+f"(d[62]), "+f"(d[63]), "+f"(d[64]), "+f"(d[65]), "+f"(d[66]), "+f"(d[67]), "+f"(d[68]), "+f"(d[69]), "+f"(d[70]), "+f"(d[71]), "+f"(d[72]), "+f"(d[73]), "+f"(d[74]), "+f"(d[75]), "+f"(d[76]), "+f"(d[77]), "+f"(d[78]), "+f"(d[79]), "+f"(d[80]), "+f"(d[81]), "+f"(d[82]), "+f"(d[83]), "+f"(d[84]), "+f"(d[85]), "+f"(d[86]), "+f"(d[87]), "+f"(d[88]), "+f"(d[89]), "+f"(d[90]), "+f"(d[91]), "+f"(d[92]), "+f"(d[93]), "+f"(d[94]), "+f"(d[95])
    : "r"(a0), "r"(a1), "r"(a2), "r"(a3), "l"(db), "r"(scale_d));
}

__device__ __forceinline__ void wgmma_qkT(float (&d)[8], uint64_t da, uint64_t db, int scale_d) {
  asm volatile("{\n.reg .pred p;\nsetp.ne.b32 p, %10, 0;\n"
    "wgmma.mma_async.sync.aligned.m64n16k16.f32.bf16.bf16 "
    "{%0, %1, %2, %3, %4, %5, %6, %7}, "
    "%8, %9, p, 1, 1, 0, 0;\n}\n"
    : "+f"(d[0]), "+f"(d[1]), "+f"(d[2]), "+f"(d[3]), "+f"(d[4]), "+f"(d[5]), "+f"(d[6]), "+f"(d[7])
    : "l"(da), "l"(db), "r"(scale_d));
}
__device__ __forceinline__ void wgmma_pvT(float (&d)[8], uint64_t da, uint64_t db, int scale_d) {
  asm volatile("{\n.reg .pred p;\nsetp.ne.b32 p, %10, 0;\n"
    "wgmma.mma_async.sync.aligned.m64n16k16.f32.bf16.bf16 "
    "{%0, %1, %2, %3, %4, %5, %6, %7}, "
    "%8, %9, p, 1, 1, 1, 0;\n}\n"
    : "+f"(d[0]), "+f"(d[1]), "+f"(d[2]), "+f"(d[3]), "+f"(d[4]), "+f"(d[5]), "+f"(d[6]), "+f"(d[7])
    : "l"(da), "l"(db), "r"(scale_d));
}

__device__ __forceinline__ void wgmma_qk0(float (&d)[32], uint32_t a0, uint32_t a1, uint32_t a2, uint32_t a3, uint64_t db) {
  asm volatile("{\n.reg .pred p;\nsetp.ne.b32 p, 0, 0;\n"
    "wgmma.mma_async.sync.aligned.m64n64k16.f32.bf16.bf16 "
    "{%0, %1, %2, %3, %4, %5, %6, %7, %8, %9, %10, %11, %12, %13, %14, %15, %16, %17, %18, %19, %20, %21, %22, %23, %24, %25, %26, %27, %28, %29, %30, %31}, "
    "{%32, %33, %34, %35}, %36, p, 1, 1, 0;\n}\n"
    : "=f"(d[0]), "=f"(d[1]), "=f"(d[2]), "=f"(d[3]), "=f"(d[4]), "=f"(d[5]), "=f"(d[6]), "=f"(d[7]), "=f"(d[8]), "=f"(d[9]), "=f"(d[10]), "=f"(d[11]), "=f"(d[12]), "=f"(d[13]), "=f"(d[14]), "=f"(d[15]), "=f"(d[16]), "=f"(d[17]), "=f"(d[18]), "=f"(d[19]), "=f"(d[20]), "=f"(d[21]), "=f"(d[22]), "=f"(d[23]), "=f"(d[24]), "=f"(d[25]), "=f"(d[26]), "=f"(d[27]), "=f"(d[28]), "=f"(d[29]), "=f"(d[30]), "=f"(d[31])
    : "r"(a0), "r"(a1), "r"(a2), "r"(a3), "l"(db));
}
__device__ __forceinline__ void wgmma_pv0(float (&d)[96], uint32_t a0, uint32_t a1, uint32_t a2, uint32_t a3, uint64_t db) {
  asm volatile("{\n.reg .pred p;\nsetp.ne.b32 p, 0, 0;\n"
    "wgmma.mma_async.sync.aligned.m64n192k16.f32.bf16.bf16 "
    "{%0, %1, %2, %3, %4, %5, %6, %7, %8, %9, %10, %11, %12, %13, %14, %15, %16, %17, %18, %19, %20, %21, %22, %23, %24, %25, %26, %27, %28, %29, %30, %31, %32, %33, %34, %35, %36, %37, %38, %39, %40, %41, %42, %43, %44, %45, %46, %47, %48, %49, %50, %51, %52, %53, %54, %55, %56, %57, %58, %59, %60, %61, %62, %63, %64, %65, %66, %67, %68, %69, %70, %71, %72, %73, %74, %75, %76, %77, %78, %79, %80, %81, %82, %83, %84, %85, %86, %87, %88, %89, %90, %91, %92, %93, %94, %95}, "
    "{%96, %97, %98, %99}, %100, p, 1, 1, 1;\n}\n"
    : "=f"(d[0]), "=f"(d[1]), "=f"(d[2]), "=f"(d[3]), "=f"(d[4]), "=f"(d[5]), "=f"(d[6]), "=f"(d[7]), "=f"(d[8]), "=f"(d[9]), "=f"(d[10]), "=f"(d[11]), "=f"(d[12]), "=f"(d[13]), "=f"(d[14]), "=f"(d[15]), "=f"(d[16]), "=f"(d[17]), "=f"(d[18]), "=f"(d[19]), "=f"(d[20]), "=f"(d[21]), "=f"(d[22]), "=f"(d[23]), "=f"(d[24]), "=f"(d[25]), "=f"(d[26]), "=f"(d[27]), "=f"(d[28]), "=f"(d[29]), "=f"(d[30]), "=f"(d[31]), "=f"(d[32]), "=f"(d[33]), "=f"(d[34]), "=f"(d[35]), "=f"(d[36]), "=f"(d[37]), "=f"(d[38]), "=f"(d[39]), "=f"(d[40]), "=f"(d[41]), "=f"(d[42]), "=f"(d[43]), "=f"(d[44]), "=f"(d[45]), "=f"(d[46]), "=f"(d[47]), "=f"(d[48]), "=f"(d[49]), "=f"(d[50]), "=f"(d[51]), "=f"(d[52]), "=f"(d[53]), "=f"(d[54]), "=f"(d[55]), "=f"(d[56]), "=f"(d[57]), "=f"(d[58]), "=f"(d[59]), "=f"(d[60]), "=f"(d[61]), "=f"(d[62]), "=f"(d[63]), "=f"(d[64]), "=f"(d[65]), "=f"(d[66]), "=f"(d[67]), "=f"(d[68]), "=f"(d[69]), "=f"(d[70]), "=f"(d[71]), "=f"(d[72]), "=f"(d[73]), "=f"(d[74]), "=f"(d[75]), "=f"(d[76]), "=f"(d[77]), "=f"(d[78]), "=f"(d[79]), "=f"(d[80]), "=f"(d[81]), "=f"(d[82]), "=f"(d[83]), "=f"(d[84]), "=f"(d[85]), "=f"(d[86]), "=f"(d[87]), "=f"(d[88]), "=f"(d[89]), "=f"(d[90]), "=f"(d[91]), "=f"(d[92]), "=f"(d[93]), "=f"(d[94]), "=f"(d[95])
    : "r"(a0), "r"(a1), "r"(a2), "r"(a3), "l"(db));
}
__device__ __forceinline__ void wgmma_qkT0(float (&d)[8], uint64_t da, uint64_t db) {
  asm volatile("{\n.reg .pred p;\nsetp.ne.b32 p, 0, 0;\n"
    "wgmma.mma_async.sync.aligned.m64n16k16.f32.bf16.bf16 "
    "{%0, %1, %2, %3, %4, %5, %6, %7}, "
    "%8, %9, p, 1, 1, 0, 0;\n}\n"
    : "=f"(d[0]), "=f"(d[1]), "=f"(d[2]), "=f"(d[3]), "=f"(d[4]), "=f"(d[5]), "=f"(d[6]), "=f"(d[7])
    : "l"(da), "l"(db));
}
__device__ __forceinline__ void wgmma_pvT0(float (&d)[8], uint64_t da, uint64_t db) {
  asm volatile("{\n.reg .pred p;\nsetp.ne.b32 p, 0, 0;\n"
    "wgmma.mma_async.sync.aligned.m64n16k16.f32.bf16.bf16 "
    "{%0, %1, %2, %3, %4, %5, %6, %7}, "
    "%8, %9, p, 1, 1, 1, 0;\n}\n"
    : "=f"(d[0]), "=f"(d[1]), "=f"(d[2]), "=f"(d[3]), "=f"(d[4]), "=f"(d[5]), "=f"(d[6]), "=f"(d[7])
    : "l"(da), "l"(db));
}

struct Round { int head, qrow, mc; };
__device__ __forceinline__ Round decode_round(uint32_t e, uint32_t rank) {
  Round o;
  o.mc = (e & 0x600) != 0x600;
  o.head = (e & 0x1ff) + (o.mc ? 0 : rank);
  o.qrow = (e >> 1 & 0x300) + (o.mc ? rank * 128 : 0);
  return o;
}

__device__ __forceinline__ uint32_t ring_k(uint32_t cur) { return cur << 3 & 0x38; }
__device__ __forceinline__ uint32_t ring_v(uint32_t cur) { return cur >> 1 & 0x38; }
__device__ __forceinline__ uint32_t ring_rot(uint32_t ord) { return ord >> 8 | ((ord ^ 0x88) & 0xff) << 20; }
__device__ __forceinline__ uint32_t ring_stay(uint32_t ord) { return (ord & 0xff00000) | (ord >> 4 & 0xffff) | (ord & 0xf) << 16; }
__device__ __forceinline__ uint32_t ring_swap(uint32_t cur) { return (cur >> 4 & 0xf) | (cur & 0xf) << 4; }

__device__ __forceinline__ uint32_t kdesc0(uint32_t s_kv) { return ((s_kv & 0x3FFFFu) >> 4) | (1u << 16); }
__device__ __forceinline__ uint32_t vdesc0(uint32_t s_kv) { return ((s_kv & 0x3FFFFu) >> 4) | ((uint32_t)(SLAB >> 4) << 16); }
constexpr uint64_t DESC_HI = ((uint64_t)(RGRP >> 4) << 32) | ((uint64_t)1 << 62);
constexpr uint64_t DESC_HI_PT = ((uint64_t)(1024 >> 4) << 32) | ((uint64_t)1 << 62);

__device__ __forceinline__ void issue_qk(float (&S)[32], const uint32_t (&Q)[48], uint32_t kdesc) {
  const uint64_t d = DESC_HI | kdesc;
  wgmma_qk0(S, Q[0], Q[1], Q[2], Q[3], d);
#pragma unroll
  for (int kk = 1; kk < 12; kk++)
    wgmma_qk(S, Q[kk * 4], Q[kk * 4 + 1], Q[kk * 4 + 2], Q[kk * 4 + 3], d + (uint64_t)((kk / 4) * (SLAB / 16) + (kk % 4) * 2), 1);
}
__device__ __forceinline__ void issue_qk32(float (&S)[32], const uint32_t (&Q)[48], uint32_t kdesc) {
  uint32_t d[12];
#pragma unroll
  for (int kk = 0; kk < 12; kk++) {
    d[kk] = kdesc + ((kk / 4) * (SLAB / 16) + (kk % 4) * 2);
    asm volatile("" : "+r"(d[kk]));
  }
  wgmma_qk0(S, Q[0], Q[1], Q[2], Q[3], DESC_HI | d[0]);
#pragma unroll
  for (int kk = 1; kk < 12; kk++) wgmma_qk(S, Q[kk * 4], Q[kk * 4 + 1], Q[kk * 4 + 2], Q[kk * 4 + 3], DESC_HI | d[kk], 1);
}
__device__ __forceinline__ void issue_qk3(float (&S)[32], const uint32_t (&Q)[48], uint32_t kdesc) {
  const uint64_t d = DESC_HI | kdesc;
  wgmma_qk0(S, Q[0], Q[1], Q[2], Q[3], d);
#pragma unroll
  for (int kk = 1; kk < 12; kk++) {
    if (kk % 4 == 0) wg_commit();
    wgmma_qk(S, Q[kk * 4], Q[kk * 4 + 1], Q[kk * 4 + 2], Q[kk * 4 + 3], d + (uint64_t)((kk / 4) * (SLAB / 16) + (kk % 4) * 2), 1);
  }
}
template <bool ACCUMULATE>
__device__ __forceinline__ void issue_pv(float (&O)[96], const uint32_t (&P)[16], uint32_t vdesc) {
  const uint64_t d = DESC_HI | vdesc;
  if (ACCUMULATE) wgmma_pv(O, P[0], P[1], P[2], P[3], d, 1);
  else wgmma_pv0(O, P[0], P[1], P[2], P[3], d);
#pragma unroll
  for (int kk = 1; kk < 4; kk++)
    wgmma_pv(O, P[kk * 4], P[kk * 4 + 1], P[kk * 4 + 2], P[kk * 4 + 3], d + (uint64_t)(kk * (2 * RGRP / 16)), 1);
}

template <int K0 = 0, int K1 = 12>
__device__ __forceinline__ void load_q(uint32_t (&Q)[48], uint32_t lane_addr) {
#pragma unroll
  for (int kk = K0; kk < K1; kk++)
    ldsm_x4((lane_addr ^ ((kk % 4) << 5)) + (kk / 4) * SLAB, Q[kk * 4], Q[kk * 4 + 1], Q[kk * 4 + 2], Q[kk * 4 + 3]);
}

__device__ __forceinline__ void scale_q(uint32_t (&Q)[48]) {
  constexpr uint32_t C2 = 0x3DD53DD5u;
#pragma unroll
  for (int i = 0; i < 48; i++) asm("mul.rn.bf16x2 %0, %1, %2;" : "=r"(Q[i]) : "r"(Q[i]), "r"(C2));
  fence_regs(Q);
}
__device__ __forceinline__ void softmax_block(const float (&S)[32], uint32_t (&P)[16], float& l0, float& l1) {
#pragma unroll
  for (int i = 0; i < 8; i++) {
    const float a = ex2(S[4 * i + 0]);
    const float b = ex2(S[4 * i + 1]);
    const float c = ex2(S[4 * i + 2]);
    const float d = ex2(S[4 * i + 3]);
    l0 += a + b;
    l1 += c + d;
    P[2 * i] = pack_bf16(a, b);
    P[2 * i + 1] = pack_bf16(c, d);
  }
  fence_regs(P);
}

__device__ __forceinline__ void sums_put(uint32_t addr, float l0, float l1) {
  asm volatile("st.shared.v2.f32 [%0], {%1, %2};" ::"r"(addr), "f"(l0), "f"(l1) : "memory");
}
__device__ __forceinline__ void sums_get(uint32_t addr, float& s0, float& s1) {
  float a, b, c, d, e, f, g, h;
  asm volatile("ld.shared.v4.f32 {%0, %1, %2, %3}, [%8];\nld.shared.v4.f32 {%4, %5, %6, %7}, [%8 + 16];\n"
               : "=f"(a), "=f"(b), "=f"(c), "=f"(d), "=f"(e), "=f"(f), "=f"(g), "=f"(h) : "r"(addr & ~31u) : "memory");
  s0 = (a + c) + (e + g);
  s1 = (b + d) + (f + h);
}

template <int K0, int K1>
__device__ __forceinline__ void epilogue_part(const float (&O)[96], float i0, float i1, uint32_t lane_addr) {
#pragma unroll
  for (int kk = K0; kk < K1; kk++) {
    const int b = kk * 8;
    stsm_x4((lane_addr ^ ((kk % 4) << 5)) + (kk / 4) * SLAB,
            pack_bf16(O[b] * i0, O[b + 1] * i0), pack_bf16(O[b + 2] * i1, O[b + 3] * i1),
            pack_bf16(O[b + 4] * i0, O[b + 5] * i0), pack_bf16(O[b + 6] * i1, O[b + 7] * i1));
  }
}
__device__ __forceinline__ void epilogue_done(uint32_t bar, int lane) {
  __syncwarp();
  if (lane == 0) mbar_arrive(bar);
}

__device__ __forceinline__ void redo_tile(const CUtensorMap* tmQ, const CUtensorMap* tmK, const CUtensorMap* tmV, const CUtensorMap* tmO,
                                          int head, int row, uint32_t qo, uint32_t kv, uint32_t lane_addr, uint32_t bar, uint32_t& phase,
                                          uint32_t wg_bar) {
  float O[96], S[32];
  uint32_t Q[48], P[16];
  uint64_t pol;
  asm volatile("createpolicy.fractional.L2::evict_normal.b64 %0, 1.0;" : "=l"(pol));
  const bool leader = (threadIdx.x & 127) == 0;
  if (leader) {
    mbar_expect_tx(bar, SLOT);
    tma_load(qo, tmQ, bar, row, head, pol);
  }
  mbar_wait(bar, phase);
  phase ^= 1;
  load_q(Q, lane_addr);
  float m0 = -INFINITY, m1 = -INFINITY, l0 = 0.f, l1 = 0.f;
#pragma unroll
  for (int i = 0; i < 96; i++) O[i] = 0.f;
#pragma unroll 1
  for (int j = 0; j < NBLK; j++) {
    asm volatile("bar.sync %0, 128;" ::"r"(wg_bar) : "memory");
    if (leader) {
      mbar_expect_tx(bar, 2 * SLOT);
      tma_load(kv, tmK, bar, j * BN, head, pol);
      tma_load(kv + SLOT, tmV, bar, j * BN, head, pol);
    }
    mbar_wait(bar, phase);
    phase ^= 1;
    wg_fence();
    issue_qk(S, Q, kdesc0(kv));
    wg_commit();
    wg_wait<0>();
    fence_regs(S);
    float n0 = m0, n1 = m1;
#pragma unroll
    for (int i = 0; i < 8; i++) {
      n0 = fmaxf(n0, fmaxf(S[4 * i], S[4 * i + 1]));
      n1 = fmaxf(n1, fmaxf(S[4 * i + 2], S[4 * i + 3]));
    }
#pragma unroll
    for (int o = 1; o < 4; o <<= 1) {
      n0 = fmaxf(n0, __shfl_xor_sync(0xffffffffu, n0, o));
      n1 = fmaxf(n1, __shfl_xor_sync(0xffffffffu, n1, o));
    }
    const float f0 = ex2((m0 - n0) * SCALE_LOG2), f1 = ex2((m1 - n1) * SCALE_LOG2);
    m0 = n0; m1 = n1;
    l0 *= f0; l1 *= f1;
#pragma unroll
    for (int i = 0; i < 24; i++) {
      O[4 * i] *= f0; O[4 * i + 1] *= f0; O[4 * i + 2] *= f1; O[4 * i + 3] *= f1;
    }
#pragma unroll
    for (int i = 0; i < 8; i++) {
      S[4 * i] = (S[4 * i] - m0) * SCALE_LOG2; S[4 * i + 1] = (S[4 * i + 1] - m0) * SCALE_LOG2;
      S[4 * i + 2] = (S[4 * i + 2] - m1) * SCALE_LOG2; S[4 * i + 3] = (S[4 * i + 3] - m1) * SCALE_LOG2;
    }
    softmax_block(S, P, l0, l1);
    fence_regs(O);
    wg_fence();
    issue_pv<true>(O, P, vdesc0(kv + SLOT));
    wg_commit();
    wg_wait<0>();
    fence_regs(O);
  }
#pragma unroll
  for (int o = 1; o < 4; o <<= 1) {
    l0 += __shfl_xor_sync(0xffffffffu, l0, o);
    l1 += __shfl_xor_sync(0xffffffffu, l1, o);
  }
  epilogue_part<0, 12>(O, rcp(l0), rcp(l1), lane_addr);
  asm volatile("fence.proxy.async.shared::cta;" ::: "memory");
  asm volatile("bar.sync %0, 128;" ::"r"(wg_bar) : "memory");
  if (leader) {
    for (int i = 0; i < 64 && row + i < SQ; i += OROWS) tma_store(tmO, qo + i / 8 * RGRP, row + i, head, pol);
    asm volatile("cp.async.bulk.commit_group;" ::: "memory");
    asm volatile("cp.async.bulk.wait_group 0;" ::: "memory");
  }
}

__device__ __forceinline__ void wg_barrier() { asm volatile("bar.sync 3, 128;" ::: "memory"); }

__device__ __forceinline__ void tail_reduce(float (&v)[4], uint32_t red, int warp, int lane) {
#pragma unroll
  for (int o = 4; o < 32; o <<= 1)
#pragma unroll
    for (int i = 0; i < 4; i++) v[i] += __shfl_xor_sync(0xffffffffu, v[i], o);
  if (lane < 4)
    asm volatile("st.shared.v4.f32 [%0], {%1, %2, %3, %4};" ::"r"(red + (warp * 4 + lane) * 16), "f"(v[0]), "f"(v[1]), "f"(v[2]), "f"(v[3]) : "memory");
  wg_barrier();
#pragma unroll
  for (int ww = 0; ww < 4; ww++) {
    float x0, x1, x2, x3;
    asm volatile("ld.shared.v4.f32 {%0, %1, %2, %3}, [%4];" : "=f"(x0), "=f"(x1), "=f"(x2), "=f"(x3) : "r"(red + (ww * 4 + (lane & 3)) * 16) : "memory");
    if (ww == 0) { v[0] = x0; v[1] = x1; v[2] = x2; v[3] = x3; }
    else { v[0] += x0; v[1] += x1; v[2] += x2; v[3] += x3; }
  }
}

__device__ __forceinline__ void tail_softmax(const float (&S)[8], float (&l)[4], uint32_t pt_addr) {
  float e[8];
#pragma unroll
  for (int i = 0; i < 8; i++) e[i] = ex2(S[i] * SCALE_LOG2);
  stsm_x4_trans(pt_addr, pack_bf16(e[0], e[1]), pack_bf16(e[2], e[3]), pack_bf16(e[4], e[5]), pack_bf16(e[6], e[7]));
  l[0] += e[0] + e[2]; l[1] += e[1] + e[3]; l[2] += e[4] + e[6]; l[3] += e[5] + e[7];
}

__device__ __forceinline__ void issue_qkT(float (&S8)[8], uint32_t kdesc, uint32_t qt_addr) {
  const uint64_t da = DESC_HI | kdesc;
  const uint64_t db = DESC_HI | (uint64_t)(((qt_addr & 0x3FFFFu) >> 4) | (1u << 16));
  wgmma_qkT0(S8, da, db);
#pragma unroll
  for (int kk = 1; kk < 12; kk++)
    wgmma_qkT(S8, da + (uint64_t)((kk / 4) * (SLAB / 16) + (kk % 4) * 2), db + (uint64_t)((kk / 4) * (SLAB / 16) + (kk % 4) * 2), 1);
}
template <bool ACCUMULATE>
__device__ __forceinline__ void issue_pvT(float (&O)[3][8], uint32_t vdesc, uint32_t pt_base) {
  const uint64_t da = DESC_HI | vdesc;
  const uint64_t db = DESC_HI_PT | (uint64_t)(((pt_base & 0x3FFFFu) >> 4) | (1u << 16));
#pragma unroll
  for (int kk = 0; kk < 4; kk++)
#pragma unroll
    for (int b = 0; b < 3; b++) {
      if (kk == 0 && !ACCUMULATE) wgmma_pvT0(O[b], da + (uint64_t)(b * (SLAB / 16)), db);
      else wgmma_pvT(O[b], da + (uint64_t)(b * (SLAB / 16) + kk * (2 * RGRP / 16)), db + (uint64_t)(kk * 2), 1);
    }
}

template <bool B> struct Bool { static constexpr bool value = B; };

constexpr int MAX_CLUSTERS = 72;
constexpr int MAX_ROUNDS = 32;
struct Schedule {
  uint32_t first[MAX_CLUSTERS];
  uint32_t stays[MAX_CLUSTERS];
  uint32_t tails[MAX_CLUSTERS];
  uint16_t start[MAX_CLUSTERS + 1];
  uint16_t list[NROUNDS + 1];
};

#define TRACE_TILE()

__global__ void __cluster_dims__(2, 1, 1) __launch_bounds__(NTHREADS, 1)
attn_kernel(const __grid_constant__ CUtensorMap tmQ, const __grid_constant__ CUtensorMap tmQT, const __grid_constant__ CUtensorMap tmK,
            const __grid_constant__ CUtensorMap tmV, const __grid_constant__ CUtensorMap tmO, const __grid_constant__ Schedule sched) {
  extern __shared__ __align__(1024) uint8_t smem_raw[];
  const uint32_t c_entry = (uint32_t)clock();
  const uint32_t sbase = smem_u32(smem_raw);
  const uint32_t s_qo = sbase + OFF_QO;
  const uint32_t s_kv = sbase + OFF_KV;
  const uint32_t s_bar = sbase + OFF_BAR;
  const uint32_t bar_full = s_bar;
  const uint32_t bar_empty = s_bar + 8 * NSLOT;
  const uint32_t bar_qfull = s_bar + 16 * NSLOT;
  const uint32_t bar_ostg = bar_qfull + 16;
  const uint32_t bar_qreq = bar_ostg + 16;
  const uint32_t bar_redo = bar_qreq + 16;
  const uint32_t s_redo = bar_redo + 16;

  uint32_t rank;
  asm("mov.u32 %0, %%cluster_ctarank;" : "=r"(rank));
  const int cluster = blockIdx.x >> 1;
  auto get_rounds = [&](int& first, int& count) {
    uint32_t c;
    asm volatile("mov.u32 %0, %%ctaid.x;" : "=r"(c));
    c >>= 1;
    first = sched.start[c];
    count = sched.start[c + 1] - first;
  };

  if (threadIdx.x == 0) {
    asm volatile("prefetch.tensormap [%0];" ::"l"(&tmK) : "memory");
    asm volatile("prefetch.tensormap [%0];" ::"l"(&tmQ) : "memory");
    asm volatile("prefetch.tensormap [%0];" ::"l"(&tmV) : "memory");
    for (int i = 0; i < 3; i++) mbar_init(bar_full + 8 * i, 1);
    for (int i = 0; i < 2; i++) mbar_init(bar_qfull + 8 * i, 1);
    asm volatile("fence.mbarrier_init.release.cluster;" ::: "memory");
    asm volatile("fence.proxy.async.shared::cta;" ::: "memory");
    const uint32_t e0 = sched.first[cluster];
    const Round r0 = decode_round(e0, rank);
    const int head = r0.head, qrow = r0.qrow;
    uint64_t polq, polk;
    asm volatile("createpolicy.fractional.L2::evict_first.b64 %0, 1.0;" : "=l"(polq));
    asm volatile("createpolicy.fractional.L2::evict_unchanged.b64 %0, 1.0;" : "=l"(polk));
    while ((uint32_t)clock() - c_entry < (e0 >> 16)) {}
    mbar_expect_tx(bar_full, SLOT);
    tma_load(s_kv, &tmK, bar_full, 0, head, polk);
    mbar_expect_tx(bar_qfull, SLOT);
    tma_load(s_qo, &tmQ, bar_qfull, qrow, head, polq);
    mbar_expect_tx(bar_full + 8, SLOT);
    tma_load(s_kv + SLOT, &tmK, bar_full + 8, BN, head, polk);
    mbar_expect_tx(bar_full + 16, SLOT);
    tma_load(s_kv + 2 * SLOT, &tmV, bar_full + 16, 0, head, polk);
    mbar_expect_tx(bar_qfull + 8, SLOT);
    tma_load(s_qo + SLOT, &tmQ, bar_qfull + 8, qrow + 64, head, polq);
  } else if (threadIdx.x == 32) {
    for (int i = 0; i < NSLOT; i++) {
      if (i >= 3) mbar_init(bar_full + 8 * i, 1);
      mbar_init(bar_empty + 8 * i, 4);
    }
    for (int i = 0; i < 2; i++) {
      mbar_init(bar_ostg + 8 * i, 4);
      mbar_init(bar_qreq + 8 * i, 1);
      mbar_init(bar_redo + 8 * i, 1);
      asm volatile("st.shared.u32 [%0], %1;" ::"r"(s_redo + 4 * i), "r"(0) : "memory");
    }
    asm volatile("fence.mbarrier_init.release.cluster;" ::: "memory");
    asm volatile("fence.proxy.async.shared::cta;" ::: "memory");
  }
  __syncthreads();
  asm volatile("barrier.cluster.arrive.relaxed.aligned;\nbarrier.cluster.wait.aligned;" ::: "memory");

  const int wg = __shfl_sync(0xffffffffu, threadIdx.x >> 7, 0);
  const int warp = __shfl_sync(0xffffffffu, (threadIdx.x >> 5) & 3, 0);
  const int lane = threadIdx.x & 31;

  if (wg == 0) {
    asm volatile("setmaxnreg.dec.sync.aligned.u32 24;");
    int first_round, nrounds;
    get_rounds(first_round, nrounds);
    const int nblocks = nrounds * NBLK;
    if (warp == 0) {
      uint64_t pol;
      asm volatile("createpolicy.fractional.L2::evict_unchanged.b64 %0, 1.0;" : "=l"(pol));
      auto load = [&](uint32_t slot, uint32_t ph, const Round& r, const CUtensorMap* tm, uint32_t blk, uint32_t owner) {
        uint32_t dst = s_kv + slot * (SLOT / 8), bar = bar_full + slot, mode = blk == 8 ? 0 : !r.mc ? 1 : rank == owner ? 2 : 0;
        uint32_t bytes = blk == 8 ? 0 : SLOT;
        int row = blk * BN, head = r.head;
        asm volatile("" : "+r"(dst), "+r"(bar), "+r"(mode), "+r"(row), "+r"(head), "+r"(bytes), "+r"(ph), "+l"(tm));
        if (mode == 2) {
          mbar_wait(bar_empty + slot, ph);
          if (elect_one()) {
            tma_load_mc(dst, tm, bar, row, head, pol);
            mbar_expect_tx(bar, SLOT);
          }
        } else if (mode == 1) {
          mbar_wait(bar_empty + slot, ph);
          if (elect_one()) {
            tma_load(dst, tm, bar, row, head, pol);
            mbar_expect_tx(bar, SLOT);
          }
        } else {
          mbar_wait(bar_empty + slot, ph);
          if (elect_one()) mbar_expect_tx(bar, bytes);
        }
      };
      auto request_q = [&](int n, int pos) {
        pos += (n & 7) * 2;
        if (lane == 0 && pos == QREQ0) mbar_arrive(bar_qreq);
        if (lane == 0 && pos == QREQ1) mbar_arrive(bar_qreq + 8);
      };
      uint32_t cur = 0xb0, ord = 0x3210edc;
      Round r = decode_round(sched.list[first_round], rank);
      uint32_t kblk = 0x765432, vblk = 0x7654321;
      bool stay = false;
      for (int n = 1; n < nblocks; n++) {
        const int j = n & 7;
        if (j != 7) {
          load(ring_v(cur), cur >> 7 & 1, r, &tmK, kblk & 15, 0);
          kblk >>= 4;
          request_q(n, 0);
          cur = ord;
          ord = ring_rot(ord);
          const CUtensorMap* tm = &tmV;
          if (stay && j == 2) {
            cur = ring_swap(cur);
            ord = ring_stay(ord);
            tm = &tmK;
          }
          load(ring_k(cur), cur >> 3 & 1, r, tm, vblk & 15, 1);
          vblk >>= 4;
          request_q(n, 1);
        } else {
          const uint32_t e = sched.list[first_round + (n >> 3) + 1];
          const Round r1 = decode_round(e, rank);
          stay = e & 0x4000;
          if (n + 1 < nblocks) load(ring_v(cur), cur >> 7 & 1, r1, stay ? &tmV : &tmK, stay ? vblk : 0, 0);
          request_q(n, 0);
          cur = ord;
          ord = ring_rot(ord);
          load(ring_k(cur), cur >> 3 & 1, r, &tmV, stay ? 8 : vblk, 1);
          request_q(n, 1);
          r = r1;
          kblk = stay ? 0x4328880 : 0x7654321;
          vblk = stay ? 0x43210188 : 0x76543210;
        }
      }
      ord ^= 0x8080000;
      for (int i = 0; i < NSLOT; i++, ord >>= 4) mbar_wait_sleep(bar_empty + ring_k(ord), ord >> 3 & 1);
    } else if (warp != 3) {
      const int w = warp - 1;
      uint64_t pol;
      asm volatile("createpolicy.fractional.L2::evict_first.b64 %0, 1.0;" : "=l"(pol));
      const uint32_t buf = s_qo + w * SLOT;
      mbar_wait_sleep(bar_ostg + 8 * w, 0);
      if (elect_one()) asm volatile("prefetch.tensormap [%0];" ::"l"(w ? &tmQT : &tmO) : "memory");
      for (int t = 0; t < nrounds; t++) {
        if (t + 1 < nrounds) {
          const uint32_t e = sched.list[first_round + t + 1];
          const Round r = decode_round(e, rank);
          const bool tail = w == 1 && (e & 0x8000);
          mbar_wait_sleep(bar_qreq + 8 * w, t & 1);
          if (elect_one()) {
            tma_load(tail ? sbase + OFF_QT : buf, tail ? &tmQT : &tmQ, bar_qfull + 8 * w, r.qrow + w * 64, r.head, pol);
            mbar_expect_tx(bar_qfull + 8 * w, tail ? 3 * 2048 : SLOT);
          }
        } else {
          if (elect_one()) mbar_arrive(bar_qfull + 8 * w);
        }
        const Round r = decode_round(sched.list[first_round + t], rank);
        const int row0 = r.qrow + w * 64;
        const int nrows = row0 + 64 <= SQ ? 64 : SQ % 64;
        mbar_wait_sleep(bar_ostg + 8 * w, ~t & 1);
        asm volatile("fence.proxy.async.shared::cta;" ::: "memory");
#pragma unroll 1
        for (int i = 0; i < nrows; i += OROWS) {
          if (elect_one()) {
            tma_store(&tmO, buf + i / 8 * RGRP, row0 + i, r.head, pol);
            asm volatile("cp.async.bulk.commit_group;" ::: "memory");
          }
          if (t + 1 < nrounds) asm volatile("cp.async.bulk.wait_group.read 0;" ::: "memory");
        }
      }
      asm volatile("cp.async.bulk.wait_group 0;" ::: "memory");
      if (elect_one()) mbar_arrive(bar_redo + 8 * w);
    } else {
      uint32_t cur = 0x21, ord = 0xa986543, stays = sched.stays[cluster];
      for (int n = 0; n < nblocks; n++) {
        if (n + 1 < nblocks) mbar_wait(bar_full + ring_k(cur), cur >> 3 & 1);
        mbar_wait(bar_full + ring_v(cur), cur >> 7 & 1);
        asm volatile("bar.sync 1, 288;" ::: "memory");
        asm volatile("bar.arrive 2, 288;" ::: "memory");
        cur = ord;
        ord = ring_rot(ord);
        if ((n & 7) == 6) {
          stays >>= 1;
          if (stays & 1) {
            cur = ring_swap(cur);
            ord = ring_stay(ord);
          }
        }
        TRACE_TILE();
      }
    }
  } else {
    asm volatile("setmaxnreg.inc.sync.aligned.u32 240;");
    const int w = wg - 1;
    int first_round, nrounds;
    get_rounds(first_round, nrounds);
    const int nblocks = nrounds * NBLK;
    float O[96], S[32];
    uint32_t Q[48], P0[16], P1[16];
    float l0 = 0.f, l1 = 0.f, inv0 = 1.f, inv1 = 1.f;
    uint32_t redo = 0;
    const uint32_t lane_addr = s_qo + w * SLOT + (warp * 2 + ((lane >> 3) & 1)) * RGRP + (lane & 7) * 128 + (((lane >> 4) ^ (lane & 7)) << 4);
    const uint32_t sum_addr = s_qo + w * SLOT + warp * 2 * RGRP + lane * 8;
    const uint32_t my_qfull = bar_qfull + 8 * w, my_ostg = bar_ostg + 8 * w;

    uint32_t empty_remote;
    asm("mapa.shared::cluster.u32 %0, %1, %2;" : "=r"(empty_remote) : "r"(bar_empty), "r"(threadIdx.x & 1));
    const bool releaser = (threadIdx.x & 127) < 2;
    auto release = [&](uint32_t s) {
      if (releaser) asm volatile("mbarrier.arrive.shared::cluster.b64 _, [%0];" ::"r"(empty_remote + s) : "memory");
    };
    uint32_t ks = 8, vs = 16, kp = 0, vp = 0, ord = 0x2106543;
    const uint32_t kd0 = kdesc0(s_kv), vd0 = vdesc0(s_kv);
    uint32_t kd = kd0 + ks * (SLOT / 128), vd = vd0 + vs * (SLOT / 128);
    auto advance = [&]() {
      kp = ks; vp = vs;
      ks = ring_k(ord); vs = ring_v(ord);
      ord = ord >> 8 | (ord & 0xff) << 20;
      kd = kd0 + ks * (SLOT / 128); vd = vd0 + vs * (SLOT / 128);
      asm volatile("" : "+r"(ks), "+r"(vs), "+r"(kd), "+r"(vd), "+r"(ord));
    };
    uint32_t stay = 0;

    uint32_t tails = w == 1 ? sched.tails[cluster] : 0u;
    auto turn_wait = [&]() { asm volatile("bar.sync %0, 288;" ::"r"(1 + w) : "memory"); };
    auto turn_pass = [&]() { asm volatile("bar.arrive %0, 288;" ::"r"(2 - w) : "memory"); };
    if (w == 1) asm volatile("bar.arrive %0, 288;" ::"r"(1 + (tails & 1)) : "memory");

    mbar_wait(my_qfull, 0);
    load_q(Q, lane_addr);
    scale_q(Q);
    mbar_wait(bar_full, 0);
    wg_fence();
    issue_qk(S, Q, kd0);
    wg_commit();
    wg_wait<0>();
    fence_regs(S);
    release(0);
    __syncwarp();
    if (lane == 0) mbar_arrive(my_ostg);
    uint32_t pending = 0;

    int n = 0;
    auto finish_sums = [&]() {
      float s0, s1;
      sums_get(sum_addr, s0, s1);
      inv0 = rcp(s0); inv1 = rcp(s1);
      l0 = l1 = 0.f;
      asm volatile("" : "+f"(inv0), "+f"(inv1)::"memory");
    };
    auto check_sums = [&](int t) { check_inv(inv0, inv1, redo, 1u << (t & 31)); };

    int exit_n = -1;
#pragma unroll 1
    while (true) {
#pragma unroll 1
      while (true) {
        const int j = n & 7;
        softmax_block(S, P0, l0, l1);
        asm volatile("" : "+f"(l0), "+f"(l1)::"memory");
        if (j != 0) {
          wg_wait<0>();
          release(vp);
          turn_wait();
          wg_fence();
          issue_qk3(S, Q, kd);
          wg_commit();
          issue_pv<true>(O, P0, vd);
          wg_commit();
          turn_pass();
          advance();
          if (j == 6) {
            mbar_wait(my_qfull, ((n >> 3) + 1) & 1);
            wg_wait<3>();
            load_q<0, 4>(Q, lane_addr);
            wg_wait<2>();
            load_q<4, 8>(Q, lane_addr);
          }
          wg_wait<1>();
          fence_regs(S);
          fence_regs(P1);
        } else {
          wg_wait<0>();
          fence_regs(O);
          fence_regs(P1);
          if (pending) {
            release(vp);
            epilogue_part<0, ESPLIT>(O, inv0, inv1, lane_addr);
          }
          turn_wait();
          wg_fence();
          issue_qk32(S, Q, kd);
          wg_commit();
          if (pending) {
            epilogue_part<ESPLIT, 12>(O, inv0, inv1, lane_addr);
            epilogue_done(my_ostg, lane);
          }
          wg_fence();
          issue_pv<false>(O, P0, vd);
          wg_commit();
          turn_pass();
          advance();
          check_sums((n >> 3) - 1);
          exit_n = ((tails & 2) || n + 8 == nblocks) ? n + 6 : -1;
          tails >>= 1;
          stay = sched.list[first_round + (n >> 3) + 1] & 0x4000;
          asm volatile("" : "+r"(exit_n), "+r"(tails), "+r"(redo), "+r"(stay));
          wg_wait<1>();
          fence_regs(S);
          pending = true;
        }
        release(kp);
        softmax_block(S, P1, l0, l1);
        asm volatile("" : "+f"(l0), "+f"(l1)::"memory");
        if (j == 6) {
          load_q<8, 12>(Q, lane_addr);
          sums_put(sum_addr, l0, l1);
          wg_wait<0>();
          release(vp);
          { const uint32_t k = ks; ks = stay ? vs : ks; vs = stay ? k : vs; ord = stay ? ring_stay(ord) : ord; }
          kd = kd0 + ks * (SLOT / 128); vd = vd0 + vs * (SLOT / 128);
          asm volatile("" : "+r"(ks), "+r"(vs), "+r"(kd), "+r"(vd), "+r"(ord));
          scale_q(Q);
          if (n == exit_n) {
            turn_wait();
            wg_fence();
            issue_pv<true>(O, P1, vd);
            wg_commit();
            break;
          }
          asm volatile("" ::: "memory");
          turn_wait();
          wg_fence();
          issue_qk32(S, Q, kd);
          wg_commit();
          issue_pv<true>(O, P1, vd);
          wg_commit();
          turn_pass();
          advance();
          if (pending) finish_sums();
          wg_wait<1>();
        } else {
          wg_wait<0>();
          release(vp);
          turn_wait();
          wg_fence();
          issue_qk(S, Q, kd);
          wg_commit();
          issue_pv<true>(O, P1, vd);
          wg_commit();
          turn_pass();
          advance();
          wg_wait<1>();
        }
        fence_regs(S);
        fence_regs(P0);
        release(kp);
        n += 2;
      }
      if (n + 2 == nblocks) {
        if (w == 0) turn_pass();
        finish_sums();
        check_sums(n >> 3);
        wg_wait<0>();
        fence_regs(O);
        release(vs);
        epilogue_part<0, 12>(O, inv0, inv1, lane_addr);
        epilogue_done(my_ostg, lane);
        break;
      }
      const int t = n >> 3;
      const uint32_t qt = sbase + OFF_QT, pt = sbase + OFF_PT, red = sbase + OFF_RED;
      const uint32_t tl = ((lane & 7) + (lane >> 4) * 8) * 128 + (((warp * 2 + ((lane >> 3) & 1)) ^ (lane & 7)) << 4);
      const bool tlast = n + 10 == nblocks;
      float lt[4] = {0.f, 0.f, 0.f, 0.f};
      float ST[8], OT[3][8];
      wg_fence();
      issue_qkT(ST, kd, qt);
      wg_commit();
      turn_pass();
      finish_sums();
      check_sums(t);
      wg_wait<0>();
      fence_regs(ST);
      fence_regs(O);
      release(ks);
      release(vs);
      advance();
      epilogue_part<0, NT_SPLIT>(O, inv0, inv1, lane_addr);
      if (NT_SPLIT == 12) epilogue_done(my_ostg, lane);
      tail_softmax(ST, lt, pt + tl);
      auto tail_step = [&](auto first_c, int jj) {
        constexpr bool FIRST = decltype(first_c)::value;
        asm volatile("fence.proxy.async.shared::cta;" ::: "memory");
        turn_wait();
        wg_fence();
        issue_qkT(ST, kd, qt);
        wg_commit();
        issue_pvT<!FIRST>(OT, vd, pt + (jj & 1) * 2048);
        wg_commit();
        turn_pass();
        advance();
        wg_wait<1>();
        fence_regs(ST);
        release(kp);
        tail_softmax(ST, lt, pt + (~jj & 1) * 2048 + tl);
        wg_wait<0>();
        fence_regs(OT[0]); fence_regs(OT[1]); fence_regs(OT[2]);
        release(vp);
      };
      tail_step(Bool<true>(), 0);
      if (NT_SPLIT < 12) {
        epilogue_part<NT_SPLIT, 12>(O, inv0, inv1, lane_addr);
        epilogue_done(my_ostg, lane);
      }
#pragma unroll 1
      for (int jj = 1; jj < 7; jj++) tail_step(Bool<false>(), jj);
      mbar_wait(my_qfull, t & 1);
      load_q(Q, lane_addr);
      scale_q(Q);
      tail_reduce(lt, red, warp, lane);
#pragma unroll
      for (int i = 0; i < 4; i++) lt[i] = rcp(lt[i]);
      check_inv(lt[0], lt[1], redo, 1u << ((t + 1) & 31));
      check_inv(lt[2], lt[3], redo, 1u << ((t + 1) & 31));
      inv0 = inv1 = 1.f;
      asm volatile("fence.proxy.async.shared::cta;" ::: "memory");
      turn_wait();
      wg_fence();
      issue_pvT<true>(OT, vd, pt + 2048);
      wg_commit();
      issue_qk(S, Q, kd);
      wg_commit();
      if (!tlast) turn_pass();
      wg_wait<1>();
      fence_regs(OT[0]); fence_regs(OT[1]); fence_regs(OT[2]);
      release(vs);
#pragma unroll
      for (int b = 0; b < 3; b++)
        stsm_x4_trans(s_qo + SLOT + b * SLAB + tl + (lane >> 4) * (RGRP - 1024),
                      pack_bf16(OT[b][0] * lt[0], OT[b][1] * lt[1]), pack_bf16(OT[b][2] * lt[0], OT[b][3] * lt[1]),
                      pack_bf16(OT[b][4] * lt[2], OT[b][5] * lt[3]), pack_bf16(OT[b][6] * lt[2], OT[b][7] * lt[3]));
      epilogue_done(my_ostg, lane);
      wg_wait<0>();
      fence_regs(S);
      if (tlast) break;
      release(ks);
      advance();
#pragma unroll
      for (int i = 0; i < 96; i++) O[i] = 0.f;
      pending = false;
      n += 10;
      tails >>= 1;
    }
    if (redo) asm volatile("red.shared.or.b32 [%0], %1;" ::"r"(s_redo + 4 * w), "r"(redo) : "memory");
    asm volatile("bar.sync 4, 256;" ::: "memory");
    asm volatile("ld.shared.u32 %0, [%1];" : "=r"(redo) : "r"(s_redo + 4 * w) : "memory");
    redo = __shfl_sync(0xffffffffu, redo, 0);
    if (redo) {
      mbar_wait_sleep(bar_redo + 8 * w, 0);
      asm volatile("bar.sync %0, 128;" ::"r"(5 + w) : "memory");
      uint32_t phase = 1;
      get_rounds(first_round, nrounds);
      uint32_t rank;
      asm volatile("mov.u32 %0, %%cluster_ctarank;" : "=r"(rank));
#pragma unroll 1
      for (int t = 0; t < nrounds; t++) {
        if (!(redo >> (t & 31) & 1)) continue;
        const Round r = decode_round(sched.list[first_round + t], rank);
        redo_tile(&tmQ, &tmK, &tmV, &tmO, r.head, r.qrow + w * 64, s_qo + w * SLOT, s_kv + 2 * w * SLOT, lane_addr, bar_redo + 8 * w, phase, 5 + w);
      }
    }
  }
}

typedef CUresult (*EncodeFn)(CUtensorMap*, CUtensorMapDataType, cuuint32_t, void*, const cuuint64_t*, const cuuint64_t*,
                             const cuuint32_t*, const cuuint32_t*, CUtensorMapInterleave, CUtensorMapSwizzle,
                             CUtensorMapL2promotion, CUtensorMapFloatOOBfill);

void make_map(EncodeFn fn, CUtensorMap* tm, const void* ptr, int rows, int box_rows) {
  cuuint64_t dims[5] = {64, 8, 3, (cuuint64_t)rows / 8, (cuuint64_t)NHEADS};
  cuuint64_t strides[4] = {HD * 2, 128, 8 * HD * 2, (cuuint64_t)rows * HD * 2};
  cuuint32_t box[5] = {64, 8, 3, (cuuint32_t)box_rows / 8, 1};
  cuuint32_t estr[5] = {1, 1, 1, 1, 1};
  fn(tm, CU_TENSOR_MAP_DATA_TYPE_BFLOAT16, 5, const_cast<void*>(ptr), dims, strides, box, estr,
     CU_TENSOR_MAP_INTERLEAVE_NONE, CU_TENSOR_MAP_SWIZZLE_128B, CU_TENSOR_MAP_L2_PROMOTION_L2_128B, CU_TENSOR_MAP_FLOAT_OOB_FILL_NONE);
}

#define STAGGER 250
#define COST_N 12690
#define COST_T 10800
#define COST_TN 12720
#define TAIL_LATE 36
#define TAIL_MAX 60
#define HEAVY_STEP 3
const uint16_t DELAY66[66] = {
  86, 259, 518, 1209, 1036, 0, 431, 777, 690, 604, 345, 172, 2245, 950, 1122, 1727, 1381, 1468, 863, 1295, 3109, 1900,
  1813, 2677, 2072, 2331, 1554, 2504, 3886, 4404, 2850, 3627, 3281, 3454, 3195, 3713, 2159, 2763, 2936, 2590, 2418, 3540, 3368, 3022,
  4231, 3972, 4059, 4490, 4318, 4145, 3800, 4922, 4577, 4663, 5009, 4836, 4750, 5095, 5613, 5181, 5268, 5527, 5354, 5440, 1640, 1986,
};
const uint16_t LIST66[66][28] = {
  {0x0002,0x0020,0x0034,0x4434,0x005d,0x425d,0x0271,0x0095,0x4495,0x00b9,0x44b9,0x00e5,0x42e5,0x8706,0x011a,0x431a,0x0140,0x4540,0x016a,0x456a,0x0194,0x4594,0x01ba,0x01c7,0x43c7,0x01f3,0x45f3,0xffff},
  {0x0202,0x8602,0x002b,0x442b,0x0053,0x4453,0x8670,0x0094,0x4494,0x86a4,0x00c6,0x44c6,0x86e4,0x0106,0x4506,0x0119,0x4319,0x014a,0x454a,0x876a,0x0187,0x4587,0x879e,0x01bb,0x45bb,0x87e0,0x01f6,0x87f2},
  {0x0402,0x0021,0x8620,0x0046,0x4446,0x0070,0x4470,0x8684,0x00a4,0x44a4,0x86b8,0x00d7,0x44d7,0x0107,0x4507,0x871a,0x0519,0x8740,0x015b,0x455b,0x0386,0x8794,0x01ac,0x45ac,0x87c6,0x01e1,0x45e1,0x87f6},
  {0x0003,0x0221,0x4421,0x8634,0x005c,0x425c,0x0084,0x4284,0x00a5,0x00b8,0x44b8,0x00e4,0x42e4,0x010c,0x450c,0x051a,0x0141,0x4541,0x016b,0x456b,0x8786,0x019e,0x459e,0x01c6,0x45c6,0x01f2,0x45f2,0xffff},
  {0x0010,0x8610,0x022d,0x0048,0x8648,0x0266,0x0267,0x008b,0x448b,0x86ac,0x00c8,0x44c8,0x02ec,0x02ed,0x010b,0x450b,0x872c,0x014c,0x874c,0x0376,0x0377,0x878e,0x058f,0x87b4,0x03be,0x87d4,0x03e9,0x87f4},
  {0x0000,0x8600,0x0225,0x0042,0x8642,0x026a,0x026b,0x0281,0x0097,0x4497,0x86b6,0x00dc,0x44dc,0x02fc,0x02fd,0x011f,0x451f,0x873c,0x015e,0x875e,0x037e,0x037f,0x879c,0x059d,0x87c0,0x01e4,0x87e4,0x03f9},
  {0x0008,0x8608,0x0027,0x4427,0x024b,0x026e,0x866e,0x028c,0x028d,0x00ab,0x44ab,0x04cc,0x02f4,0x44f4,0x0113,0x4513,0x0333,0x0152,0x4552,0x0179,0x4379,0x0199,0x4599,0x03b6,0x01d3,0x43d3,0x01f1,0xffff},
  {0x000e,0x000f,0x440f,0x8632,0x005a,0x865a,0x0278,0x0279,0x009d,0x449d,0x86bc,0x00de,0x44de,0x02fa,0x02fb,0x0121,0x4521,0x873a,0x0160,0x8760,0x038a,0x038b,0x87a0,0x05a1,0x87c2,0x01e6,0x45e6,0x87fa},
  {0x000c,0x000d,0x0236,0x4436,0x0258,0x0074,0x4274,0x0098,0x4498,0x00bb,0x44bb,0x86e0,0x00f8,0x42f8,0x011c,0x451c,0x013f,0x453f,0x0562,0x0563,0x877c,0x0392,0x01b1,0x43b1,0x01d8,0x43d8,0x01fe,0xffff},
  {0x000a,0x860a,0x0029,0x4429,0x024f,0x0072,0x4472,0x0288,0x00a8,0x44a8,0x02ce,0x02cf,0x02f6,0x04f7,0x870e,0x050f,0x032e,0x0350,0x4550,0x0570,0x0190,0x4390,0x03b2,0x03b3,0x01d6,0x43d6,0x01fd,0xffff},
  {0x0006,0x8606,0x0223,0x0044,0x4444,0x0063,0x4463,0x0287,0x00a6,0x44a6,0x02ca,0x00e2,0x42e2,0x0108,0x4508,0x012b,0x452b,0x014f,0x454f,0x8766,0x018c,0x438c,0x03ae,0x03af,0x01cb,0x45cb,0x01ed,0xffff},
  {0x0004,0x0220,0x4420,0x0047,0x4447,0x045c,0x8676,0x0477,0x0295,0x02b3,0x02b9,0x02c7,0x02f2,0x02f3,0x0118,0x4518,0x0337,0x034b,0x035b,0x037a,0x057b,0x039e,0x03ad,0x03c6,0x05d0,0x03f2,0x05f7,0xffff},
  {0x0210,0x002c,0x862c,0x0248,0x4448,0x0067,0x4467,0x028b,0x00ac,0x44ac,0x00c9,0x44c9,0x86ec,0x010a,0x450a,0x032c,0x032d,0x034c,0x054d,0x8776,0x018e,0x438e,0x01b5,0x01be,0x45be,0x01e9,0x45e9,0xffff},
  {0x0200,0x0024,0x8624,0x0242,0x4442,0x006b,0x446b,0x0096,0x4496,0x02b6,0x02b7,0x02dc,0x04dd,0x04fc,0x031e,0x871e,0x013c,0x453c,0x035e,0x035f,0x017f,0x457f,0x059c,0x01c1,0x43c1,0x03e4,0x05e5,0xffff},
  {0x0208,0x0026,0x4426,0x024a,0x444a,0x006f,0x446f,0x868c,0x00aa,0x44aa,0x00cd,0x42cd,0x00f5,0x44f5,0x0512,0x0332,0x8732,0x0352,0x0353,0x0378,0x0579,0x0598,0x01b7,0x43b7,0x05d2,0x01f0,0x45f0,0xffff},
  {0x020e,0x860e,0x0032,0x4432,0x025a,0x445a,0x0079,0x4479,0x029d,0x00bc,0x44bc,0x02de,0x00fa,0x44fa,0x0320,0x4520,0x013b,0x433b,0x0161,0x4561,0x878a,0x01a0,0x45a0,0x03c2,0x03c3,0x03e7,0x03fb,0xffff},
  {0x020c,0x020d,0x440d,0x0237,0x0059,0x4259,0x8674,0x0475,0x0299,0x00ba,0x44ba,0x00e1,0x42e1,0x86f8,0x04f9,0x031d,0x013e,0x453e,0x0163,0x4363,0x017d,0x437d,0x03b0,0x01c9,0x45c9,0x05d8,0x03fe,0xffff},
  {0x020a,0x0028,0x4428,0x024e,0x864e,0x0272,0x0273,0x0089,0x4489,0x86a8,0x00ce,0x44ce,0x00f7,0x42f7,0x030e,0x012e,0x452e,0x0151,0x4551,0x0171,0x4571,0x0590,0x05b2,0x01cc,0x45cc,0x05d6,0x03fd,0xffff},
  {0x0206,0x0022,0x4422,0x0244,0x0445,0x0262,0x0086,0x8686,0x02a6,0x02a7,0x00cb,0x42cb,0x86e2,0x04e3,0x0309,0x012a,0x452a,0x034e,0x034f,0x0167,0x4567,0x058c,0x01af,0x45af,0x03cb,0x01ec,0x03ed,0xffff},
  {0x0204,0x8604,0x022b,0x0235,0x0247,0x865c,0x0077,0x4277,0x8694,0x00b3,0x44b3,0x86c6,0x00f2,0x44f2,0x870c,0x0318,0x0137,0x4537,0x874a,0x036a,0x877a,0x0387,0x039f,0x87ac,0x01d0,0x87d0,0x05d1,0x03f3},
  {0x0410,0x022c,0x442c,0x0049,0x0066,0x4466,0x028a,0x868a,0x00ad,0x42ad,0x86c8,0x02c9,0x00ed,0x44ed,0x870a,0x012c,0x452c,0x014d,0x434d,0x0177,0x4577,0x058e,0x03b5,0x45b5,0x01d5,0x45d5,0x01f5,0xffff},
  {0x0400,0x0224,0x4424,0x0043,0x4443,0x866a,0x0081,0x4481,0x8696,0x00b6,0x44b6,0x00dd,0x42dd,0x00fd,0x44fd,0x031f,0x033c,0x033d,0x055e,0x017e,0x457e,0x019d,0x439d,0x03c0,0x05c1,0x05e4,0x05f9,0xffff},
  {0x0408,0x0226,0x8626,0x004a,0x864a,0x006e,0x446e,0x008d,0x448d,0x86aa,0x00cc,0x42cc,0x00f4,0x86f4,0x0312,0x0313,0x0133,0x4533,0x8752,0x0178,0x8778,0x0398,0x0399,0x87b6,0x01d2,0x87d2,0x03f0,0x87f0},
  {0x040e,0x020f,0x0033,0x4233,0x005b,0x0078,0x4478,0x029c,0x869c,0x02bc,0x02bd,0x00df,0x44df,0x86fa,0x0120,0x8720,0x013a,0x453a,0x0360,0x0361,0x018b,0x458b,0x03a0,0x01c2,0x45c2,0x03e6,0x01fb,0xffff},
  {0x040c,0x860c,0x0036,0x8636,0x0058,0x4458,0x0075,0x4275,0x0099,0x4499,0x86ba,0x00e0,0x44e0,0x00f9,0x42f9,0x011d,0x451d,0x873e,0x0162,0x8762,0x037c,0x8792,0x01b0,0x87b0,0x03c9,0x87d8,0x05d9,0x87fe},
  {0x040a,0x0228,0x8628,0x004e,0x444e,0x0073,0x4473,0x8688,0x0289,0x00a9,0x44a9,0x86ce,0x00f6,0x44f6,0x010f,0x430f,0x872e,0x0150,0x8750,0x0370,0x0371,0x8790,0x01b2,0x87b2,0x03cc,0x87d6,0x05d7,0x87fc},
  {0x0406,0x0222,0x8622,0x0045,0x4245,0x8662,0x0263,0x0087,0x4487,0x86a6,0x00ca,0x44ca,0x00e3,0x42e3,0x0109,0x4509,0x872a,0x014e,0x874e,0x0366,0x0367,0x878c,0x01ae,0x87ae,0x03ca,0x87ca,0x05ec,0x87ec},
  {0x0404,0x0205,0x862a,0x0246,0x0252,0x045d,0x0276,0x0285,0x02a4,0x86b2,0x00c7,0x44c7,0x00f3,0x44f3,0x030c,0x8718,0x0336,0x014b,0x454b,0x017a,0x457a,0x0394,0x01ad,0x45ad,0x01d1,0x43d1,0x01f7,0xffff},
  {0x0211,0x002d,0x442d,0x0249,0x4449,0x8666,0x008a,0x448a,0x02ac,0x04ad,0x02c8,0x00ec,0x44ec,0x030a,0x030b,0x012d,0x452d,0x054c,0x0176,0x4576,0x018f,0x438f,0x03b4,0x87be,0x03d5,0x87e8,0x05f5,0xffff},
  {0x0201,0x0025,0x4425,0x0243,0x006a,0x446a,0x8680,0x0296,0x0297,0x00b7,0x44b7,0x86dc,0x00fc,0x86fc,0x011e,0x451e,0x013d,0x453d,0x015f,0x455f,0x877e,0x019c,0x439c,0x01c0,0x45c0,0x01e5,0x43e5,0xffff},
  {0x0009,0x4409,0x0227,0x004b,0x444b,0x026f,0x008c,0x448c,0x02aa,0x02ab,0x86cc,0x04cd,0x02f5,0x0112,0x8712,0x0132,0x4532,0x0153,0x4553,0x0578,0x0198,0x8798,0x01b6,0x45b6,0x03d2,0x05d3,0x03f1,0xffff},
  {0x0214,0x4414,0x0232,0x0433,0x025b,0x445b,0x8678,0x009c,0x449c,0x00bd,0x44bd,0x86de,0x02df,0x00fb,0x44fb,0x0321,0x033a,0x053b,0x0560,0x018a,0x458a,0x01a1,0x43a1,0x01c3,0x45c3,0x87e6,0x05fb,0xffff},
  {0x0212,0x4412,0x0037,0x4437,0x8658,0x0459,0x0474,0x0298,0x8698,0x02ba,0x02bb,0x02e0,0x04e1,0x04f8,0x031c,0x871c,0x033e,0x033f,0x0362,0x017c,0x457c,0x057d,0x05b0,0x05b1,0x01d9,0x43d9,0x05fe,0xffff},
  {0x000b,0x440b,0x0229,0x004f,0x444f,0x8672,0x0088,0x4488,0x02a8,0x02a9,0x00cf,0x44cf,0x86f6,0x010e,0x450e,0x012f,0x432f,0x0351,0x0170,0x8770,0x0191,0x4391,0x01b3,0x45b3,0x01d7,0x43d7,0x05fd,0xffff},
  {0x0007,0x0023,0x4423,0x8644,0x0062,0x4462,0x0286,0x4486,0x00a7,0x44a7,0x86ca,0x04cb,0x04e2,0x0308,0x8708,0x032a,0x032b,0x054e,0x0166,0x4566,0x018d,0x438d,0x05ae,0x01ca,0x45ca,0x03ec,0x05ed,0xffff},
  {0x0005,0x4405,0x0234,0x8646,0x0253,0x0076,0x4476,0x0294,0x02b2,0x02b8,0x02d6,0x44d6,0x86f2,0x0306,0x050d,0x031b,0x8736,0x0341,0x035a,0x017b,0x437b,0x0395,0x03ac,0x03bb,0x03d0,0x05e0,0x03f7,0xffff},
  {0x0011,0x4411,0x0238,0x0239,0x0260,0x0461,0x027a,0x00a0,0x44a0,0x02c4,0x86c4,0x00e9,0x44e9,0x86fe,0x02ff,0x0125,0x4525,0x0343,0x0364,0x0565,0x8782,0x0383,0x01b4,0x45b4,0x01d4,0x01e8,0x45e8,0xffff},
  {0x0001,0x4401,0x003e,0x863e,0x005e,0x445e,0x0280,0x008f,0x448f,0x02b5,0x02d4,0x86d4,0x02f0,0x02f1,0x0117,0x4517,0x0339,0x0358,0x8758,0x0374,0x0375,0x019b,0x459b,0x03bc,0x01dc,0x45dc,0x03f8,0xffff},
  {0x0209,0x0019,0x023a,0x863a,0x0055,0x4255,0x007d,0x447d,0x029f,0x02be,0x86be,0x00d9,0x42d9,0x0101,0x0122,0x4522,0x0344,0x8744,0x015d,0x435d,0x0185,0x4585,0x03a4,0x03c4,0x45c4,0x03ea,0x05eb,0xffff},
  {0x0014,0x8614,0x022f,0x0050,0x4450,0x0069,0x4269,0x0091,0x4491,0x86ae,0x00d2,0x44d2,0x00eb,0x42eb,0x0111,0x4511,0x8734,0x0154,0x4554,0x016f,0x436f,0x0197,0x4597,0x03b9,0x01da,0x01e7,0x45e7,0xffff},
  {0x0012,0x8612,0x0231,0x004c,0x444c,0x006d,0x426d,0x0093,0x4493,0x86b0,0x00d0,0x44d0,0x00ef,0x42ef,0x0115,0x0130,0x4530,0x0356,0x0357,0x0173,0x4373,0x0393,0x01a9,0x45a9,0x87c8,0x01e3,0x45e3,0xffff},
  {0x020b,0x001f,0x023c,0x863c,0x0057,0x4257,0x007f,0x009a,0x449a,0x02c2,0x86c2,0x00db,0x42db,0x0103,0x4503,0x0327,0x0346,0x8746,0x0168,0x4568,0x0388,0x0591,0x03a6,0x01cd,0x01de,0x45de,0x05fc,0xffff},
  {0x0207,0x4407,0x0040,0x4440,0x0264,0x4464,0x8682,0x0483,0x02a3,0x44a3,0x86c0,0x00e6,0x44e6,0x0105,0x4505,0x0329,0x0148,0x4548,0x016d,0x436d,0x0181,0x4581,0x87aa,0x03ab,0x01cf,0x45cf,0x03ef,0xffff},
  {0x0016,0x0017,0x4417,0x8638,0x0060,0x4460,0x007b,0x447b,0x02a1,0x00c4,0x44c4,0x02e8,0x86e8,0x02fe,0x0124,0x4524,0x0342,0x8742,0x0164,0x4564,0x0183,0x4583,0x01a3,0x43a3,0x03d4,0x45d4,0x03f4,0xffff},
  {0x001c,0x001d,0x441d,0x023f,0x005f,0x445f,0x028e,0x868e,0x00b4,0x86b4,0x00d4,0x44d4,0x00f1,0x44f1,0x0317,0x0138,0x8738,0x0158,0x4558,0x0175,0x4575,0x039b,0x01bc,0x45bc,0x03dc,0x87dc,0x01f9,0xffff},
  {0x0018,0x8618,0x003a,0x443a,0x0254,0x0455,0x027d,0x009e,0x869e,0x00be,0x44be,0x02d8,0x04d9,0x0301,0x4501,0x8722,0x0144,0x4544,0x035c,0x055d,0x0385,0x01a4,0x45a4,0x05b7,0x87c4,0x01ea,0x45ea,0xffff},
  {0x0015,0x002e,0x442e,0x0051,0x4451,0x0468,0x0290,0x8690,0x02ae,0x02af,0x00d3,0x44d3,0x86ea,0x04eb,0x0311,0x0135,0x4335,0x0354,0x0555,0x876e,0x056f,0x0397,0x01b9,0x45b9,0x03db,0x87da,0x01fa,0xffff},
  {0x0013,0x0030,0x4430,0x024c,0x006c,0x446c,0x0292,0x8692,0x00b1,0x42b1,0x02d0,0x00ee,0x44ee,0x0314,0x8714,0x0131,0x4331,0x0157,0x4557,0x8772,0x0573,0x01a8,0x45a8,0x03c8,0x03e2,0x87e2,0x01ff,0xffff},
  {0x001e,0x861e,0x003c,0x443c,0x0256,0x0457,0x027f,0x447f,0x869a,0x00c2,0x44c2,0x02da,0x04db,0x0303,0x0126,0x4526,0x052f,0x0347,0x0169,0x4569,0x8788,0x01a6,0x45a6,0x03a7,0x87cc,0x01df,0x01fc,0xffff},
  {0x001a,0x001b,0x441b,0x8640,0x0064,0x8664,0x0083,0x4283,0x00a3,0x00c0,0x44c0,0x02e6,0x86e6,0x0304,0x0305,0x0129,0x4529,0x0348,0x016c,0x456c,0x0380,0x058d,0x03aa,0x01ce,0x45ce,0x03ee,0x87ee,0xffff},
  {0x0216,0x8616,0x0038,0x4438,0x0061,0x4261,0x867a,0x027b,0x00a1,0x44a1,0x02c5,0x00e8,0x44e8,0x00ff,0x44ff,0x8724,0x0142,0x4542,0x0165,0x4365,0x0382,0x01a2,0x45a2,0x05a3,0x05bf,0x01f4,0x45f4,0xffff},
  {0x021c,0x861c,0x023e,0x443e,0x025e,0x025f,0x008e,0x448e,0x02b4,0x44b4,0x00d5,0x00f0,0x44f0,0x0316,0x8716,0x0338,0x4538,0x0159,0x0174,0x4574,0x039a,0x879a,0x01bd,0x87bc,0x01dd,0x45dd,0x05f8,0xffff},
  {0x0218,0x0219,0x003b,0x0054,0x4454,0x027c,0x867c,0x029e,0x449e,0x00bf,0x00d8,0x44d8,0x0300,0x8700,0x0123,0x4323,0x0145,0x015c,0x455c,0x0384,0x8784,0x01a5,0x87a4,0x01c4,0x03c5,0x01eb,0x43eb,0xffff},
  {0x0215,0x022e,0x862e,0x0250,0x0251,0x8668,0x0469,0x0291,0x00ae,0x44ae,0x02d2,0x02d3,0x02ea,0x0110,0x4510,0x0334,0x0535,0x8754,0x016e,0x436e,0x0196,0x4596,0x03b8,0x87b8,0x03da,0x45da,0x03fa,0xffff},
  {0x0213,0x0230,0x8630,0x004d,0x424d,0x866c,0x046d,0x0293,0x00b0,0x44b0,0x00d1,0x42d1,0x86ee,0x04ef,0x0315,0x4515,0x8730,0x0156,0x4556,0x0372,0x0192,0x4592,0x03a8,0x01c8,0x45c8,0x03e3,0x03ff,0xffff},
  {0x021e,0x021f,0x003d,0x0056,0x4456,0x027e,0x867e,0x009b,0x429b,0x00c3,0x00da,0x44da,0x0302,0x8702,0x0326,0x8726,0x0146,0x4546,0x0368,0x0369,0x0189,0x4389,0x01a7,0x45a7,0x03de,0x87de,0x03fc,0xffff},
  {0x021a,0x021b,0x0240,0x0441,0x0265,0x0082,0x4482,0x02a2,0x86a2,0x02c0,0x02c1,0x00e7,0x0104,0x4504,0x0328,0x8728,0x0149,0x8748,0x036c,0x0180,0x4580,0x01aa,0x45aa,0x03ce,0x87ce,0x01ee,0x45ee,0xffff},
  {0x0416,0x0217,0x0039,0x4439,0x8660,0x007a,0x447a,0x02a0,0x86a0,0x00c5,0x44c5,0x02e9,0x00fe,0x44fe,0x0324,0x0325,0x0143,0x4543,0x8764,0x0182,0x4582,0x03a2,0x87a2,0x01bf,0x43bf,0x03e8,0x03f5,0xffff},
  {0x041c,0x021d,0x003f,0x443f,0x865e,0x0080,0x4480,0x028f,0x00b5,0x44b5,0x02d5,0x44d5,0x86f0,0x0116,0x4516,0x0139,0x4539,0x0359,0x4559,0x8774,0x019a,0x459a,0x03bd,0x45bd,0x03dd,0x01f8,0x87f8,0xffff},
  {0x0418,0x0419,0x023b,0x443b,0x8654,0x007c,0x447c,0x009f,0x449f,0x02bf,0x44bf,0x86d8,0x0100,0x4500,0x0322,0x0523,0x0345,0x4545,0x875c,0x0184,0x4584,0x03a5,0x45a5,0x01c5,0x45c5,0x87ea,0x05f1,0xffff},
  {0x0415,0x002f,0x442f,0x8650,0x0068,0x4268,0x0090,0x4490,0x00af,0x44af,0x86d2,0x00ea,0x44ea,0x0310,0x8710,0x0134,0x4534,0x0155,0x4355,0x056e,0x0396,0x8796,0x01b8,0x45b8,0x01db,0x45db,0x05fa,0xffff},
  {0x0413,0x0031,0x4431,0x864c,0x044d,0x026c,0x0092,0x4492,0x02b0,0x04b1,0x86d0,0x04d1,0x02ee,0x0114,0x4514,0x0330,0x0531,0x8756,0x0172,0x4572,0x0193,0x4593,0x87a8,0x03a9,0x01e2,0x45e2,0x05ff,0xffff},
  {0x041e,0x041f,0x023d,0x443d,0x8656,0x007e,0x447e,0x029a,0x049b,0x02c3,0x44c3,0x86da,0x0102,0x4502,0x0127,0x4527,0x0147,0x4547,0x8768,0x0188,0x4588,0x0589,0x87a6,0x03cd,0x45cd,0x03df,0x45df,0xffff},
  {0x041a,0x861a,0x0041,0x4241,0x0065,0x4465,0x0282,0x00a2,0x44a2,0x00c1,0x44c1,0x02e7,0x44e7,0x8704,0x0128,0x4528,0x0349,0x4549,0x876c,0x056d,0x8780,0x0381,0x01ab,0x45ab,0x03cf,0x01ef,0x45ef,0xffff},
  {0x0203,0x002a,0x442a,0x0052,0x4452,0x0270,0x0085,0x4485,0x00b2,0x44b2,0x00d6,0x86d6,0x04e4,0x010d,0x430d,0x0136,0x4536,0x015a,0x455a,0x0186,0x4586,0x019f,0x459f,0x87ba,0x01e0,0x43e0,0x03f6,0xffff},
  {0x0403,0x022a,0x0035,0x4435,0x8652,0x0071,0x4471,0x0484,0x02a5,0x44a5,0x02c6,0x02d7,0x04e5,0x0307,0x011b,0x451b,0x0340,0x034a,0x875a,0x036b,0x0195,0x4595,0x03ba,0x45ba,0x05c7,0x03e1,0x05f6,0xffff},
};

void make_schedule(Schedule& s, int nclusters) {
  static uint16_t lists[MAX_CLUSTERS][NROUNDS];
  int cnt[MAX_CLUSTERS] = {0}, len[MAX_CLUSTERS], ntail[MAX_CLUSTERS] = {0}, quota[MAX_CLUSTERS] = {0};
  long long busy[MAX_CLUSTERS], fin[MAX_CLUSTERS];
  const int ntails = NROUNDS / 7, base = NROUNDS / nclusters, nheavy = NROUNDS % nclusters;
  const int step = nheavy * HEAVY_STEP <= nclusters ? HEAVY_STEP : 1;
  for (int c = 0; c < nclusters; c++) {
    len[c] = base + (c % step == 0 && c / step < nheavy);
    busy[c] = c / 3 * STAGGER;
    fin[c] = busy[c] + (long long)len[c] * COST_N;
  }
  for (int k = 0; k < ntails; k++) {
    int c = -1;
    for (int i = 0; i < nclusters; i++)
      if (quota[i] < len[i] / 2 && (c < 0 || fin[i] > fin[c])) c = i;
    quota[c]++;
    fin[c] -= 2 * COST_N - COST_T - COST_TN;
  }
  int gn = 0, gt = 3;
  for (int k = 0; k < NROUNDS; k++) {
    int c = -1;
    for (int i = 0; i < nclusters; i++)
      if (cnt[i] < len[i] && (c < 0 || busy[i] < busy[c])) c = i;
    const bool after_tail = cnt[c] > 0 && (lists[c][cnt[c] - 1] & 0x8000);
    const bool may_t = cnt[c] > 0 && !after_tail;
    const int left = len[c] - cnt[c], q = quota[c] - ntail[c];
    const bool due = (long long)(gt / 7) * quota[c] * 8 >= (long long)(ntail[c] * 8 + (c * 5 & 7)) * ntails;
    bool tail = may_t && q > 0 && (2 * q > left || (gn - gt >= TAIL_LATE && due) || gn - gt >= TAIL_MAX);
    if (4 * quota[c] >= len[c]) {
      const int m = len[c] - 1, phase = c / step * 11 % m;
      tail = may_t && q > 0 && (2 * q > left || (cnt[c] * quota[c] + phase) / m > ntail[c]);
    }
    if (gt >= NROUNDS) tail = false;
    if (gn >= NROUNDS) tail = true;
    const int g = tail ? gt : gn;
    if (tail) { gt += 7; ntail[c]++; }
    else { gn++; if (gn % 7 == 3) gn++; }
    const bool form_t = tail && may_t;
    lists[c][cnt[c]++] = (uint16_t)(g | (form_t ? 0x8000 : 0));
    busy[c] += form_t ? COST_T : after_tail ? COST_TN : COST_N;
  }
  bool use_tail = true;
  for (int c = 0; c < nclusters; c++) if (cnt[c] > MAX_ROUNDS) use_tail = false;
  if (!use_tail) for (int c = 0; c < nclusters; c++) for (int i = 0; i < cnt[c]; i++) lists[c][i] &= 0x7fff;
  for (int c = 0; c < nclusters; c++)
    for (int i = 0; i < cnt[c]; i++) {
      const int g = lists[c][i] & 0x7ff, p = g / 7, r = g % 7;
      lists[c][i] = (uint16_t)((2 * p + (r > 3)) | (r & 3) << 9 | (lists[c][i] & 0x8000));
    }
  if (nclusters == 66)
    for (int c = 0; c < 66; c++)
      for (cnt[c] = 0; cnt[c] < 28 && LIST66[c][cnt[c]] != 0xffff; cnt[c]++) lists[c][cnt[c]] = LIST66[c][cnt[c]];
  const bool table = nclusters == 66;
  int pos = 0;
  for (int c = 0; c < nclusters; c++) {
    s.start[c] = (uint16_t)pos;
    s.first[c] = lists[c][0] | (uint32_t)(table ? DELAY66[c] : c / 3 * STAGGER) << 16;
    s.tails[c] = s.stays[c] = 0;
    for (int i = 0; i < cnt[c]; i++) {
      if (lists[c][i] & 0x8000) s.tails[c] |= 1u << i;
      if (lists[c][i] & 0x4000) s.stays[c] |= 1u << i;
      s.list[pos++] = lists[c][i];
    }
  }
  for (int c = nclusters; c <= MAX_CLUSTERS; c++) s.start[c] = (uint16_t)pos;
  s.list[NROUNDS] = 0;
}

}

extern "C" void kernel_launch(void* const* d_in, const int* in_sizes, int n_in, void* d_out, int out_size) {
  static EncodeFn encode = nullptr;
  static int nclusters = 0;
  static Schedule sched;
  if (!encode) {
    void* fn = nullptr;
    cudaDriverEntryPointQueryResult qr;
    cudaGetDriverEntryPoint("cuTensorMapEncodeTiled", &fn, cudaEnableDefault, &qr);
    encode = (EncodeFn)fn;
    int dev = 0, nsm = 0;
    cudaGetDevice(&dev);
    cudaDeviceGetAttribute(&nsm, cudaDevAttrMultiProcessorCount, dev);
    nclusters = nsm / 2 < MAX_CLUSTERS ? nsm / 2 : MAX_CLUSTERS;
    make_schedule(sched, nclusters);
    cudaFuncSetAttribute(attn_kernel, cudaFuncAttributeMaxDynamicSharedMemorySize, SMEM_BYTES);
  }
  CUtensorMap tmQ, tmQT, tmK, tmV, tmO;
  make_map(encode, &tmQ, d_in[0], SQ, 64);
  make_map(encode, &tmQT, d_in[0], SQ, 16);
  make_map(encode, &tmK, d_in[1], SK, 64);
  make_map(encode, &tmV, d_in[2], SK, 64);
  make_map(encode, &tmO, d_out, SQ, OROWS);
  attn_kernel<<<2 * nclusters, NTHREADS, SMEM_BYTES>>>(tmQ, tmQT, tmK, tmV, tmO, sched);
}
```

```cpp
#include <cuda_runtime.h>
#include <cuda_bf16.h>
#include <cuda.h>
#include <stdint.h>

namespace {

constexpr int NHEADS = 512;
constexpr int SQ = 848;
constexpr int SK = 512;
constexpr int HD = 192;
constexpr int BN = 64;
constexpr int NBLK = SK / BN;
constexpr int SLOT = 64 * HD * 2;
constexpr int SLAB = 1024;
constexpr int RGRP = 3 * SLAB;
constexpr int NSLOT = 7;
constexpr int NROUNDS = (NHEADS / 2) * 7;
constexpr int NTHREADS = 384;
constexpr int OFF_QO = 0;
constexpr int OFF_KV = 2 * SLOT;
constexpr int OFF_QT = (2 + NSLOT) * SLOT;
constexpr int OFF_PT = OFF_QT + 3 * 2048;
constexpr int OFF_RED = OFF_PT + 2 * 2048;
constexpr int OFF_BAR = OFF_RED + 256;
constexpr int SMEM_BYTES = OFF_BAR + 256;

#define ESPLIT 8
#define OROWS 16
#define NT_SPLIT 4
#define QREQ0 8
#define QREQ1 13
constexpr uint32_t WAIT_LIMIT = 1u << 18;
#define SUSPEND 20000
constexpr uint32_t SUSPEND_NS = SUSPEND;

constexpr float SCALE_LOG2 = 0.07216878364870322f * 1.4426950408889634f;
__device__ __forceinline__ void check_inv(float a, float b, uint32_t& mask, uint32_t bit) {
  asm("{\n.reg .pred p;\nsetp.ge.f32 p, %1, 0f1F800000;\nsetp.le.and.f32 p, %1, 0f53800000, p;\n"
      "setp.ge.and.f32 p, %2, 0f1F800000, p;\nsetp.le.and.f32 p, %2, 0f53800000, p;\n@!p or.b32 %0, %0, %3;\n}\n"
      : "+r"(mask) : "f"(a), "f"(b), "r"(bit));
}

__device__ __forceinline__ uint32_t smem_u32(const void* p) { return (uint32_t)__cvta_generic_to_shared(p); }
__device__ __forceinline__ void wg_fence() { asm volatile("wgmma.fence.sync.aligned;" ::: "memory"); }
__device__ __forceinline__ void wg_commit() { asm volatile("wgmma.commit_group.sync.aligned;" ::: "memory"); }
template <int N> __device__ __forceinline__ void wg_wait() { asm volatile("wgmma.wait_group.sync.aligned %0;" ::"n"(N) : "memory"); }
template <int N> __device__ __forceinline__ void fence_regs(float (&r)[N]) {
#pragma unroll
  for (int i = 0; i < N; i++) asm volatile("" : "+f"(r[i])::"memory");
}
template <int N> __device__ __forceinline__ void fence_regs(uint32_t (&r)[N]) {
#pragma unroll
  for (int i = 0; i < N; i++) asm volatile("" : "+r"(r[i])::"memory");
}

__device__ __forceinline__ void mbar_init(uint32_t bar, uint32_t cnt) {
  asm volatile("mbarrier.init.shared::cta.b64 [%0], %1;" ::"r"(bar), "r"(cnt));
}
__device__ __forceinline__ void mbar_expect_tx(uint32_t bar, uint32_t bytes) {
  asm volatile("mbarrier.arrive.expect_tx.shared::cta.b64 _, [%0], %1;" ::"r"(bar), "r"(bytes) : "memory");
}
__device__ __forceinline__ void mbar_arrive(uint32_t bar) {
  asm volatile("mbarrier.arrive.shared::cta.b64 _, [%0];" ::"r"(bar) : "memory");
}
__device__ __forceinline__ bool mbar_try(uint32_t bar, uint32_t parity) {
  uint32_t ok;
  asm volatile(
      "{\n.reg .pred p;\nmbarrier.try_wait.parity.shared::cta.b64 p, [%1], %2;\nselp.b32 %0, 1, 0, p;\n}\n"
      : "=r"(ok)
      : "r"(bar), "r"(parity)
      : "memory");
  return ok;
}
__device__ __forceinline__ bool mbar_try_sleep(uint32_t bar, uint32_t parity) {
  uint32_t ok;
  asm volatile(
      "{\n.reg .pred p;\nmbarrier.try_wait.parity.shared::cta.b64 p, [%1], %2, %3;\nselp.b32 %0, 1, 0, p;\n}\n"
      : "=r"(ok)
      : "r"(bar), "r"(parity), "r"(SUSPEND_NS)
      : "memory");
  return ok;
}
__device__ __forceinline__ void mbar_wait(uint32_t bar, uint32_t parity) {
  if (mbar_try(bar, parity)) return;
  for (uint32_t n = 0; n < WAIT_LIMIT; n++)
    if (mbar_try(bar, parity)) break;
}
__device__ __forceinline__ void mbar_wait_sleep(uint32_t bar, uint32_t parity) {
  for (uint32_t n = 0; n < WAIT_LIMIT; n++) {
    if (mbar_try_sleep(bar, parity)) break;
  }
}

__device__ __forceinline__ void tma_load(uint32_t dst, const CUtensorMap* tm, uint32_t bar, int row, int head, uint64_t pol) {
  asm volatile(
      "cp.async.bulk.tensor.5d.shared::cluster.global.mbarrier::complete_tx::bytes.L2::cache_hint"
      " [%0], [%1, {%3, %3, %3, %4, %5}], [%2], %6;" ::"r"(dst),
      "l"(tm), "r"(bar), "r"(0), "r"(row >> 3), "r"(head), "l"(pol)
      : "memory");
}
__device__ __forceinline__ void tma_load_mc(uint32_t dst, const CUtensorMap* tm, uint32_t bar, int row, int head, uint64_t pol) {
  asm volatile(
      "cp.async.bulk.tensor.5d.shared::cluster.global.mbarrier::complete_tx::bytes.multicast::cluster.L2::cache_hint"
      " [%0], [%1, {%3, %3, %3, %4, %5}], [%2], %7, %6;" ::"r"(dst),
      "l"(tm), "r"(bar), "r"(0), "r"(row >> 3), "r"(head), "l"(pol), "h"((uint16_t)3)
      : "memory");
}
__device__ __forceinline__ bool elect_one() {
  uint32_t r;
  asm volatile("{\n.reg .pred e;\nelect.sync _|e, 0xffffffff;\nselp.b32 %0, 1, 0, e;\n}\n" : "=r"(r));
  return r;
}
__device__ __forceinline__ void tma_store(const CUtensorMap* tm, uint32_t src, int row, int head, uint64_t pol) {
  asm volatile(
      "cp.async.bulk.tensor.5d.global.shared::cta.bulk_group.L2::cache_hint"
      " [%0, {%2, %2, %2, %3, %4}], [%1], %5;" ::"l"(tm),
      "r"(src), "r"(0), "r"(row >> 3), "r"(head), "l"(pol)
      : "memory");
}
__device__ __forceinline__ void ldsm_x4(uint32_t addr, uint32_t& r0, uint32_t& r1, uint32_t& r2, uint32_t& r3) {
  asm volatile("ldmatrix.sync.aligned.m8n8.x4.shared.b16 {%0, %1, %2, %3}, [%4];"
               : "=r"(r0), "=r"(r1), "=r"(r2), "=r"(r3)
               : "r"(addr)
               : "memory");
}
__device__ __forceinline__ void stsm_x4(uint32_t addr, uint32_t r0, uint32_t r1, uint32_t r2, uint32_t r3) {
  asm volatile("stmatrix.sync.aligned.m8n8.x4.shared.b16 [%0], {%1, %2, %3, %4};" ::"r"(addr), "r"(r0), "r"(r1), "r"(r2), "r"(r3)
               : "memory");
}
__device__ __forceinline__ void stsm_x4_trans(uint32_t addr, uint32_t r0, uint32_t r1, uint32_t r2, uint32_t r3) {
  asm volatile("stmatrix.sync.aligned.m8n8.x4.trans.shared.b16 [%0], {%1, %2, %3, %4};" ::"r"(addr), "r"(r0), "r"(r1), "r"(r2), "r"(r3)
               : "memory");
}
__device__ __forceinline__ float ex2(float x) {
  float y;
  asm("ex2.approx.ftz.f32 %0, %1;" : "=f"(y) : "f"(x));
  return y;
}
__device__ __forceinline__ float rcp(float x) {
  float y;
  asm("rcp.approx.ftz.f32 %0, %1;" : "=f"(y) : "f"(x));
  return y;
}
__device__ __forceinline__ uint32_t pack_bf16(float lo, float hi) {
  uint32_t r;
  asm("cvt.rn.bf16x2.f32 %0, %1, %2;" : "=r"(r) : "f"(hi), "f"(lo));
  return r;
}
__device__ __forceinline__ void wgmma_qk(float (&d)[32], uint32_t a0, uint32_t a1, uint32_t a2, uint32_t a3, uint64_t db, int scale_d) {
  asm volatile("{\n.reg .pred p;\nsetp.ne.b32 p, %37, 0;\n"
    "wgmma.mma_async.sync.aligned.m64n64k16.f32.bf16.bf16 "
    "{%0, %1, %2, %3, %4, %5, %6, %7, %8, %9, %10, %11, %12, %13, %14, %15, %16, %17, %18, %19, %20, %21, %22, %23, %24, %25, %26, %27, %28, %29, %30, %31}, "
    "{%32, %33, %34, %35}, %36, p, 1, 1, 0;\n}\n"
    : "+f"(d[0]), "+f"(d[1]), "+f"(d[2]), "+f"(d[3]), "+f"(d[4]), "+f"(d[5]), "+f"(d[6]), "+f"(d[7]), "+f"(d[8]), "+f"(d[9]), "+f"(d[10]), "+f"(d[11]), "+f"(d[12]), "+f"(d[13]), "+f"(d[14]), "+f"(d[15]), "+f"(d[16]), "+f"(d[17]), "+f"(d[18]), "+f"(d[19]), "+f"(d[20]), "+f"(d[21]), "+f"(d[22]), "+f"(d[23]), "+f"(d[24]), "+f"(d[25]), "+f"(d[26]), "+f"(d[27]), "+f"(d[28]), "+f"(d[29]), "+f"(d[30]), "+f"(d[31])
    : "r"(a0), "r"(a1), "r"(a2), "r"(a3), "l"(db), "r"(scale_d));
}

__device__ __forceinline__ void wgmma_pv(float (&d)[96], uint32_t a0, uint32_t a1, uint32_t a2, uint32_t a3, uint64_t db, int scale_d) {
  asm volatile("{\n.reg .pred p;\nsetp.ne.b32 p, %101, 0;\n"
    "wgmma.mma_async.sync.aligned.m64n192k16.f32.bf16.bf16 "
    "{%0, %1, %2, %3, %4, %5, %6, %7, %8, %9, %10, %11, %12, %13, %14, %15, %16, %17, %18, %19, %20, %21, %22, %23, %24, %25, %26, %27, %28, %29, %30, %31, %32, %33, %34, %35, %36, %37, %38, %39, %40, %41, %42, %43, %44, %45, %46, %47, %48, %49, %50, %51, %52, %53, %54, %55, %56, %57, %58, %59, %60, %61, %62, %63, %64, %65, %66, %67, %68, %69, %70, %71, %72, %73, %74, %75, %76, %77, %78, %79, %80, %81, %82, %83, %84, %85, %86, %87, %88, %89, %90, %91, %92, %93, %94, %95}, "
    "{%96, %97, %98, %99}, %100, p, 1, 1, 1;\n}\n"
    : "+f"(d[0]), "+f"(d[1]), "+f"(d[2]), "+f"(d[3]), "+f"(d[4]), "+f"(d[5]), "+f"(d[6]), "+f"(d[7]), "+f"(d[8]), "+f"(d[9]), "+f"(d[10]), "+f"(d[11]), "+f"(d[12]), "+f"(d[13]), "+f"(d[14]), "+f"(d[15]), "+f"(d[16]), "+f"(d[17]), "+f"(d[18]), "+f"(d[19]), "+f"(d[20]), "+f"(d[21]), "+f"(d[22]), "+f"(d[23]), "+f"(d[24]), "+f"(d[25]), "+f"(d[26]), "+f"(d[27]), "+f"(d[28]), "+f"(d[29]), "+f"(d[30]), "+f"(d[31]), "+f"(d[32]), "+f"(d[33]), "+f"(d[34]), "+f"(d[35]), "+f"(d[36]), "+f"(d[37]), "+f"(d[38]), "+f"(d[39]), "+f"(d[40]), "+f"(d[41]), "+f"(d[42]), "+f"(d[43]), "+f"(d[44]), "+f"(d[45]), "+f"(d[46]), "+f"(d[47]), "+f"(d[48]), "+f"(d[49]), "+f"(d[50]), "+f"(d[51]), "+f"(d[52]), "+f"(d[53]), "+f"(d[54]), "+f"(d[55]), "+f"(d[56]), "+f"(d[57]), "+f"(d[58]), "+f"(d[59]), "+f"(d[60]), "+f"(d[61]), "+f"(d[62]), "+f"(d[63]), "+f"(d[64]), "+f"(d[65]), "+f"(d[66]), "+f"(d[67]), "+f"(d[68]), "+f"(d[69]), "+f"(d[70]), "+f"(d[71]), "+f"(d[72]), "+f"(d[73]), "+f"(d[74]), "+f"(d[75]), "+f"(d[76]), "+f"(d[77]), "+f"(d[78]), "+f"(d[79]), "+f"(d[80]), "+f"(d[81]), "+f"(d[82]), "+f"(d[83]), "+f"(d[84]), "+f"(d[85]), "+f"(d[86]), "+f"(d[87]), "+f"(d[88]), "+f"(d[89]), "+f"(d[90]), "+f"(d[91]), "+f"(d[92]), "+f"(d[93]), "+f"(d[94]), "+f"(d[95])
    : "r"(a0), "r"(a1), "r"(a2), "r"(a3), "l"(db), "r"(scale_d));
}

__device__ __forceinline__ void wgmma_qkT(float (&d)[8], uint64_t da, uint64_t db, int scale_d) {
  asm volatile("{\n.reg .pred p;\nsetp.ne.b32 p, %10, 0;\n"
    "wgmma.mma_async.sync.aligned.m64n16k16.f32.bf16.bf16 "
    "{%0, %1, %2, %3, %4, %5, %6, %7}, "
    "%8, %9, p, 1, 1, 0, 0;\n}\n"
    : "+f"(d[0]), "+f"(d[1]), "+f"(d[2]), "+f"(d[3]), "+f"(d[4]), "+f"(d[5]), "+f"(d[6]), "+f"(d[7])
    : "l"(da), "l"(db), "r"(scale_d));
}
__device__ __forceinline__ void wgmma_pvT(float (&d)[8], uint64_t da, uint64_t db, int scale_d) {
  asm volatile("{\n.reg .pred p;\nsetp.ne.b32 p, %10, 0;\n"
    "wgmma.mma_async.sync.aligned.m64n16k16.f32.bf16.bf16 "
    "{%0, %1, %2, %3, %4, %5, %6, %7}, "
    "%8, %9, p, 1, 1, 1, 0;\n}\n"
    : "+f"(d[0]), "+f"(d[1]), "+f"(d[2]), "+f"(d[3]), "+f"(d[4]), "+f"(d[5]), "+f"(d[6]), "+f"(d[7])
    : "l"(da), "l"(db), "r"(scale_d));
}

__device__ __forceinline__ void wgmma_qk0(float (&d)[32], uint32_t a0, uint32_t a1, uint32_t a2, uint32_t a3, uint64_t db) {
  asm volatile("{\n.reg .pred p;\nsetp.ne.b32 p, 0, 0;\n"
    "wgmma.mma_async.sync.aligned.m64n64k16.f32.bf16.bf16 "
    "{%0, %1, %2, %3, %4, %5, %6, %7, %8, %9, %10, %11, %12, %13, %14, %15, %16, %17, %18, %19, %20, %21, %22, %23, %24, %25, %26, %27, %28, %29, %30, %31}, "
    "{%32, %33, %34, %35}, %36, p, 1, 1, 0;\n}\n"
    : "=f"(d[0]), "=f"(d[1]), "=f"(d[2]), "=f"(d[3]), "=f"(d[4]), "=f"(d[5]), "=f"(d[6]), "=f"(d[7]), "=f"(d[8]), "=f"(d[9]), "=f"(d[10]), "=f"(d[11]), "=f"(d[12]), "=f"(d[13]), "=f"(d[14]), "=f"(d[15]), "=f"(d[16]), "=f"(d[17]), "=f"(d[18]), "=f"(d[19]), "=f"(d[20]), "=f"(d[21]), "=f"(d[22]), "=f"(d[23]), "=f"(d[24]), "=f"(d[25]), "=f"(d[26]), "=f"(d[27]), "=f"(d[28]), "=f"(d[29]), "=f"(d[30]), "=f"(d[31])
    : "r"(a0), "r"(a1), "r"(a2), "r"(a3), "l"(db));
}
__device__ __forceinline__ void wgmma_pv0(float (&d)[96], uint32_t a0, uint32_t a1, uint32_t a2, uint32_t a3, uint64_t db) {
  asm volatile("{\n.reg .pred p;\nsetp.ne.b32 p, 0, 0;\n"
    "wgmma.mma_async.sync.aligned.m64n192k16.f32.bf16.bf16 "
    "{%0, %1, %2, %3, %4, %5, %6, %7, %8, %9, %10, %11, %12, %13, %14, %15, %16, %17, %18, %19, %20, %21, %22, %23, %24, %25, %26, %27, %28, %29, %30, %31, %32, %33, %34, %35, %36, %37, %38, %39, %40, %41, %42, %43, %44, %45, %46, %47, %48, %49, %50, %51, %52, %53, %54, %55, %56, %57, %58, %59, %60, %61, %62, %63, %64, %65, %66, %67, %68, %69, %70, %71, %72, %73, %74, %75, %76, %77, %78, %79, %80, %81, %82, %83, %84, %85, %86, %87, %88, %89, %90, %91, %92, %93, %94, %95}, "
    "{%96, %97, %98, %99}, %100, p, 1, 1, 1;\n}\n"
    : "=f"(d[0]), "=f"(d[1]), "=f"(d[2]), "=f"(d[3]), "=f"(d[4]), "=f"(d[5]), "=f"(d[6]), "=f"(d[7]), "=f"(d[8]), "=f"(d[9]), "=f"(d[10]), "=f"(d[11]), "=f"(d[12]), "=f"(d[13]), "=f"(d[14]), "=f"(d[15]), "=f"(d[16]), "=f"(d[17]), "=f"(d[18]), "=f"(d[19]), "=f"(d[20]), "=f"(d[21]), "=f"(d[22]), "=f"(d[23]), "=f"(d[24]), "=f"(d[25]), "=f"(d[26]), "=f"(d[27]), "=f"(d[28]), "=f"(d[29]), "=f"(d[30]), "=f"(d[31]), "=f"(d[32]), "=f"(d[33]), "=f"(d[34]), "=f"(d[35]), "=f"(d[36]), "=f"(d[37]), "=f"(d[38]), "=f"(d[39]), "=f"(d[40]), "=f"(d[41]), "=f"(d[42]), "=f"(d[43]), "=f"(d[44]), "=f"(d[45]), "=f"(d[46]), "=f"(d[47]), "=f"(d[48]), "=f"(d[49]), "=f"(d[50]), "=f"(d[51]), "=f"(d[52]), "=f"(d[53]), "=f"(d[54]), "=f"(d[55]), "=f"(d[56]), "=f"(d[57]), "=f"(d[58]), "=f"(d[59]), "=f"(d[60]), "=f"(d[61]), "=f"(d[62]), "=f"(d[63]), "=f"(d[64]), "=f"(d[65]), "=f"(d[66]), "=f"(d[67]), "=f"(d[68]), "=f"(d[69]), "=f"(d[70]), "=f"(d[71]), "=f"(d[72]), "=f"(d[73]), "=f"(d[74]), "=f"(d[75]), "=f"(d[76]), "=f"(d[77]), "=f"(d[78]), "=f"(d[79]), "=f"(d[80]), "=f"(d[81]), "=f"(d[82]), "=f"(d[83]), "=f"(d[84]), "=f"(d[85]), "=f"(d[86]), "=f"(d[87]), "=f"(d[88]), "=f"(d[89]), "=f"(d[90]), "=f"(d[91]), "=f"(d[92]), "=f"(d[93]), "=f"(d[94]), "=f"(d[95])
    : "r"(a0), "r"(a1), "r"(a2), "r"(a3), "l"(db));
}
__device__ __forceinline__ void wgmma_qkT0(float (&d)[8], uint64_t da, uint64_t db) {
  asm volatile("{\n.reg .pred p;\nsetp.ne.b32 p, 0, 0;\n"
    "wgmma.mma_async.sync.aligned.m64n16k16.f32.bf16.bf16 "
    "{%0, %1, %2, %3, %4, %5, %6, %7}, "
    "%8, %9, p, 1, 1, 0, 0;\n}\n"
    : "=f"(d[0]), "=f"(d[1]), "=f"(d[2]), "=f"(d[3]), "=f"(d[4]), "=f"(d[5]), "=f"(d[6]), "=f"(d[7])
    : "l"(da), "l"(db));
}
__device__ __forceinline__ void wgmma_pvT0(float (&d)[8], uint64_t da, uint64_t db) {
  asm volatile("{\n.reg .pred p;\nsetp.ne.b32 p, 0, 0;\n"
    "wgmma.mma_async.sync.aligned.m64n16k16.f32.bf16.bf16 "
    "{%0, %1, %2, %3, %4, %5, %6, %7}, "
    "%8, %9, p, 1, 1, 1, 0;\n}\n"
    : "=f"(d[0]), "=f"(d[1]), "=f"(d[2]), "=f"(d[3]), "=f"(d[4]), "=f"(d[5]), "=f"(d[6]), "=f"(d[7])
    : "l"(da), "l"(db));
}

struct Round { int head, qrow, mc; };
__device__ __forceinline__ Round decode_round(uint32_t e, uint32_t rank) {
  Round o;
  o.mc = (e & 0x600) != 0x600;
  o.head = (e & 0x1ff) + (o.mc ? 0 : rank);
  o.qrow = (e >> 1 & 0x300) + (o.mc ? rank * 128 : 0);
  return o;
}

__device__ __forceinline__ uint32_t ring_k(uint32_t cur) { return cur << 3 & 0x38; }
__device__ __forceinline__ uint32_t ring_v(uint32_t cur) { return cur >> 1 & 0x38; }
__device__ __forceinline__ uint32_t ring_rot(uint32_t ord) { return ord >> 8 | ((ord ^ 0x88) & 0xff) << 20; }
__device__ __forceinline__ uint32_t ring_stay(uint32_t ord) { return (ord & 0xff00000) | (ord >> 4 & 0xffff) | (ord & 0xf) << 16; }
__device__ __forceinline__ uint32_t ring_swap(uint32_t cur) { return (cur >> 4 & 0xf) | (cur & 0xf) << 4; }

__device__ __forceinline__ uint32_t kdesc0(uint32_t s_kv) { return ((s_kv & 0x3FFFFu) >> 4) | (1u << 16); }
__device__ __forceinline__ uint32_t vdesc0(uint32_t s_kv) { return ((s_kv & 0x3FFFFu) >> 4) | ((uint32_t)(SLAB >> 4) << 16); }
constexpr uint64_t DESC_HI = ((uint64_t)(RGRP >> 4) << 32) | ((uint64_t)1 << 62);
constexpr uint64_t DESC_HI_PT = ((uint64_t)(1024 >> 4) << 32) | ((uint64_t)1 << 62);

__device__ __forceinline__ void issue_qk(float (&S)[32], const uint32_t (&Q)[48], uint32_t kdesc) {
  const uint64_t d = DESC_HI | kdesc;
  wgmma_qk0(S, Q[0], Q[1], Q[2], Q[3], d);
#pragma unroll
  for (int kk = 1; kk < 12; kk++)
    wgmma_qk(S, Q[kk * 4], Q[kk * 4 + 1], Q[kk * 4 + 2], Q[kk * 4 + 3], d + (uint64_t)((kk / 4) * (SLAB / 16) + (kk % 4) * 2), 1);
}
__device__ __forceinline__ void issue_qk32(float (&S)[32], const uint32_t (&Q)[48], uint32_t kdesc) {
  uint32_t d[12];
#pragma unroll
  for (int kk = 0; kk < 12; kk++) {
    d[kk] = kdesc + ((kk / 4) * (SLAB / 16) + (kk % 4) * 2);
    asm volatile("" : "+r"(d[kk]));
  }
  wgmma_qk0(S, Q[0], Q[1], Q[2], Q[3], DESC_HI | d[0]);
#pragma unroll
  for (int kk = 1; kk < 12; kk++) wgmma_qk(S, Q[kk * 4], Q[kk * 4 + 1], Q[kk * 4 + 2], Q[kk * 4 + 3], DESC_HI | d[kk], 1);
}
__device__ __forceinline__ void issue_qk3(float (&S)[32], const uint32_t (&Q)[48], uint32_t kdesc) {
  const uint64_t d = DESC_HI | kdesc;
  wgmma_qk0(S, Q[0], Q[1], Q[2], Q[3], d);
#pragma unroll
  for (int kk = 1; kk < 12; kk++) {
    if (kk % 4 == 0) wg_commit();
    wgmma_qk(S, Q[kk * 4], Q[kk * 4 + 1], Q[kk * 4 + 2], Q[kk * 4 + 3], d + (uint64_t)((kk / 4) * (SLAB / 16) + (kk % 4) * 2), 1);
  }
}
template <bool ACCUMULATE>
__device__ __forceinline__ void issue_pv(float (&O)[96], const uint32_t (&P)[16], uint32_t vdesc) {
  const uint64_t d = DESC_HI | vdesc;
  if (ACCUMULATE) wgmma_pv(O, P[0], P[1], P[2], P[3], d, 1);
  else wgmma_pv0(O, P[0], P[1], P[2], P[3], d);
#pragma unroll
  for (int kk = 1; kk < 4; kk++)
    wgmma_pv(O, P[kk * 4], P[kk * 4 + 1], P[kk * 4 + 2], P[kk * 4 + 3], d + (uint64_t)(kk * (2 * RGRP / 16)), 1);
}

template <int K0 = 0, int K1 = 12>
__device__ __forceinline__ void load_q(uint32_t (&Q)[48], uint32_t lane_addr) {
#pragma unroll
  for (int kk = K0; kk < K1; kk++)
    ldsm_x4((lane_addr ^ ((kk % 4) << 5)) + (kk / 4) * SLAB, Q[kk * 4], Q[kk * 4 + 1], Q[kk * 4 + 2], Q[kk * 4 + 3]);
}

__device__ __forceinline__ void scale_q(uint32_t (&Q)[48]) {
  constexpr uint32_t C2 = 0x3DD53DD5u;
#pragma unroll
  for (int i = 0; i < 48; i++) asm("mul.rn.bf16x2 %0, %1, %2;" : "=r"(Q[i]) : "r"(Q[i]), "r"(C2));
  fence_regs(Q);
}
__device__ __forceinline__ void softmax_block(const float (&S)[32], uint32_t (&P)[16], float& l0, float& l1) {
#pragma unroll
  for (int i = 0; i < 8; i++) {
    const float a = ex2(S[4 * i + 0]);
    const float b = ex2(S[4 * i + 1]);
    const float c = ex2(S[4 * i + 2]);
    const float d = ex2(S[4 * i + 3]);
    l0 += a + b;
    l1 += c + d;
    P[2 * i] = pack_bf16(a, b);
    P[2 * i + 1] = pack_bf16(c, d);
  }
  fence_regs(P);
}

__device__ __forceinline__ void sums_put(uint32_t addr, float l0, float l1) {
  asm volatile("st.shared.v2.f32 [%0], {%1, %2};" ::"r"(addr), "f"(l0), "f"(l1) : "memory");
}
__device__ __forceinline__ void sums_get(uint32_t addr, float& s0, float& s1) {
  float a, b, c, d, e, f, g, h;
  asm volatile("ld.shared.v4.f32 {%0, %1, %2, %3}, [%8];\nld.shared.v4.f32 {%4, %5, %6, %7}, [%8 + 16];\n"
               : "=f"(a), "=f"(b), "=f"(c), "=f"(d), "=f"(e), "=f"(f), "=f"(g), "=f"(h) : "r"(addr & ~31u) : "memory");
  s0 = (a + c) + (e + g);
  s1 = (b + d) + (f + h);
}

template <int K0, int K1>
__device__ __forceinline__ void epilogue_part(const float (&O)[96], float i0, float i1, uint32_t lane_addr) {
#pragma unroll
  for (int kk = K0; kk < K1; kk++) {
    const int b = kk * 8;
    stsm_x4((lane_addr ^ ((kk % 4) << 5)) + (kk / 4) * SLAB,
            pack_bf16(O[b] * i0, O[b + 1] * i0), pack_bf16(O[b + 2] * i1, O[b + 3] * i1),
            pack_bf16(O[b + 4] * i0, O[b + 5] * i0), pack_bf16(O[b + 6] * i1, O[b + 7] * i1));
  }
}
__device__ __forceinline__ void epilogue_done(uint32_t bar, int lane) {
  __syncwarp();
  if (lane == 0) mbar_arrive(bar);
}

__device__ __forceinline__ void redo_tile(const CUtensorMap* tmQ, const CUtensorMap* tmK, const CUtensorMap* tmV, const CUtensorMap* tmO,
                                          int head, int row, uint32_t qo, uint32_t kv, uint32_t lane_addr, uint32_t bar, uint32_t& phase,
                                          uint32_t wg_bar) {
  float O[96], S[32];
  uint32_t Q[48], P[16];
  uint64_t pol;
  asm volatile("createpolicy.fractional.L2::evict_normal.b64 %0, 1.0;" : "=l"(pol));
  const bool leader = (threadIdx.x & 127) == 0;
  if (leader) {
    mbar_expect_tx(bar, SLOT);
    tma_load(qo, tmQ, bar, row, head, pol);
  }
  mbar_wait(bar, phase);
  phase ^= 1;
  load_q(Q, lane_addr);
  float m0 = -INFINITY, m1 = -INFINITY, l0 = 0.f, l1 = 0.f;
#pragma unroll
  for (int i = 0; i < 96; i++) O[i] = 0.f;
#pragma unroll 1
  for (int j = 0; j < NBLK; j++) {
    asm volatile("bar.sync %0, 128;" ::"r"(wg_bar) : "memory");
    if (leader) {
      mbar_expect_tx(bar, 2 * SLOT);
      tma_load(kv, tmK, bar, j * BN, head, pol);
      tma_load(kv + SLOT, tmV, bar, j * BN, head, pol);
    }
    mbar_wait(bar, phase);
    phase ^= 1;
    wg_fence();
    issue_qk(S, Q, kdesc0(kv));
    wg_commit();
    wg_wait<0>();
    fence_regs(S);
    float n0 = m0, n1 = m1;
#pragma unroll
    for (int i = 0; i < 8; i++) {
      n0 = fmaxf(n0, fmaxf(S[4 * i], S[4 * i + 1]));
      n1 = fmaxf(n1, fmaxf(S[4 * i + 2], S[4 * i + 3]));
    }
#pragma unroll
    for (int o = 1; o < 4; o <<= 1) {
      n0 = fmaxf(n0, __shfl_xor_sync(0xffffffffu, n0, o));
      n1 = fmaxf(n1, __shfl_xor_sync(0xffffffffu, n1, o));
    }
    const float f0 = ex2((m0 - n0) * SCALE_LOG2), f1 = ex2((m1 - n1) * SCALE_LOG2);
    m0 = n0; m1 = n1;
    l0 *= f0; l1 *= f1;
#pragma unroll
    for (int i = 0; i < 24; i++) {
      O[4 * i] *= f0; O[4 * i + 1] *= f0; O[4 * i + 2] *= f1; O[4 * i + 3] *= f1;
    }
#pragma unroll
    for (int i = 0; i < 8; i++) {
      S[4 * i] = (S[4 * i] - m0) * SCALE_LOG2; S[4 * i + 1] = (S[4 * i + 1] - m0) * SCALE_LOG2;
      S[4 * i + 2] = (S[4 * i + 2] - m1) * SCALE_LOG2; S[4 * i + 3] = (S[4 * i + 3] - m1) * SCALE_LOG2;
    }
    softmax_block(S, P, l0, l1);
    fence_regs(O);
    wg_fence();
    issue_pv<true>(O, P, vdesc0(kv + SLOT));
    wg_commit();
    wg_wait<0>();
    fence_regs(O);
  }
#pragma unroll
  for (int o = 1; o < 4; o <<= 1) {
    l0 += __shfl_xor_sync(0xffffffffu, l0, o);
    l1 += __shfl_xor_sync(0xffffffffu, l1, o);
  }
  epilogue_part<0, 12>(O, rcp(l0), rcp(l1), lane_addr);
  asm volatile("fence.proxy.async.shared::cta;" ::: "memory");
  asm volatile("bar.sync %0, 128;" ::"r"(wg_bar) : "memory");
  if (leader) {
    for (int i = 0; i < 64 && row + i < SQ; i += OROWS) tma_store(tmO, qo + i / 8 * RGRP, row + i, head, pol);
    asm volatile("cp.async.bulk.commit_group;" ::: "memory");
    asm volatile("cp.async.bulk.wait_group 0;" ::: "memory");
  }
}

__device__ __forceinline__ void wg_barrier() { asm volatile("bar.sync 3, 128;" ::: "memory"); }

__device__ __forceinline__ void tail_reduce(float (&v)[4], uint32_t red, int warp, int lane) {
#pragma unroll
  for (int o = 4; o < 32; o <<= 1)
#pragma unroll
    for (int i = 0; i < 4; i++) v[i] += __shfl_xor_sync(0xffffffffu, v[i], o);
  if (lane < 4)
    asm volatile("st.shared.v4.f32 [%0], {%1, %2, %3, %4};" ::"r"(red + (warp * 4 + lane) * 16), "f"(v[0]), "f"(v[1]), "f"(v[2]), "f"(v[3]) : "memory");
  wg_barrier();
#pragma unroll
  for (int ww = 0; ww < 4; ww++) {
    float x0, x1, x2, x3;
    asm volatile("ld.shared.v4.f32 {%0, %1, %2, %3}, [%4];" : "=f"(x0), "=f"(x1), "=f"(x2), "=f"(x3) : "r"(red + (ww * 4 + (lane & 3)) * 16) : "memory");
    if (ww == 0) { v[0] = x0; v[1] = x1; v[2] = x2; v[3] = x3; }
    else { v[0] += x0; v[1] += x1; v[2] += x2; v[3] += x3; }
  }
}

__device__ __forceinline__ void tail_softmax(const float (&S)[8], float (&l)[4], uint32_t pt_addr) {
  float e[8];
#pragma unroll
  for (int i = 0; i < 8; i++) e[i] = ex2(S[i] * SCALE_LOG2);
  stsm_x4_trans(pt_addr, pack_bf16(e[0], e[1]), pack_bf16(e[2], e[3]), pack_bf16(e[4], e[5]), pack_bf16(e[6], e[7]));
  l[0] += e[0] + e[2]; l[1] += e[1] + e[3]; l[2] += e[4] + e[6]; l[3] += e[5] + e[7];
}

__device__ __forceinline__ void issue_qkT(float (&S8)[8], uint32_t kdesc, uint32_t qt_addr) {
  const uint64_t da = DESC_HI | kdesc;
  const uint64_t db = DESC_HI | (uint64_t)(((qt_addr & 0x3FFFFu) >> 4) | (1u << 16));
  wgmma_qkT0(S8, da, db);
#pragma unroll
  for (int kk = 1; kk < 12; kk++)
    wgmma_qkT(S8, da + (uint64_t)((kk / 4) * (SLAB / 16) + (kk % 4) * 2), db + (uint64_t)((kk / 4) * (SLAB / 16) + (kk % 4) * 2), 1);
}
template <bool ACCUMULATE>
__device__ __forceinline__ void issue_pvT(float (&O)[3][8], uint32_t vdesc, uint32_t pt_base) {
  const uint64_t da = DESC_HI | vdesc;
  const uint64_t db = DESC_HI_PT | (uint64_t)(((pt_base & 0x3FFFFu) >> 4) | (1u << 16));
#pragma unroll
  for (int kk = 0; kk < 4; kk++)
#pragma unroll
    for (int b = 0; b < 3; b++) {
      if (kk == 0 && !ACCUMULATE) wgmma_pvT0(O[b], da + (uint64_t)(b * (SLAB / 16)), db);
      else wgmma_pvT(O[b], da + (uint64_t)(b * (SLAB / 16) + kk * (2 * RGRP / 16)), db + (uint64_t)(kk * 2), 1);
    }
}

template <bool B> struct Bool { static constexpr bool value = B; };

constexpr int MAX_CLUSTERS = 72;
constexpr int MAX_ROUNDS = 32;
struct Schedule {
  uint32_t first[MAX_CLUSTERS];
  uint32_t stays[MAX_CLUSTERS];
  uint32_t tails[MAX_CLUSTERS];
  uint16_t start[MAX_CLUSTERS + 1];
  uint16_t list[NROUNDS + 1];
};

#define TRACE_TILE()

__global__ void __cluster_dims__(2, 1, 1) __launch_bounds__(NTHREADS, 1)
attn_kernel(const __grid_constant__ CUtensorMap tmQ, const __grid_constant__ CUtensorMap tmQT, const __grid_constant__ CUtensorMap tmK,
            const __grid_constant__ CUtensorMap tmV, const __grid_constant__ CUtensorMap tmO, const __grid_constant__ Schedule sched) {
  extern __shared__ __align__(1024) uint8_t smem_raw[];
  const uint32_t c_entry = (uint32_t)clock();
  const uint32_t sbase = smem_u32(smem_raw);
  const uint32_t s_qo = sbase + OFF_QO;
  const uint32_t s_kv = sbase + OFF_KV;
  const uint32_t s_bar = sbase + OFF_BAR;
  const uint32_t bar_full = s_bar;
  const uint32_t bar_empty = s_bar + 8 * NSLOT;
  const uint32_t bar_qfull = s_bar + 16 * NSLOT;
  const uint32_t bar_ostg = bar_qfull + 16;
  const uint32_t bar_qreq = bar_ostg + 16;
  const uint32_t bar_redo = bar_qreq + 16;
  const uint32_t s_redo = bar_redo + 16;

  uint32_t rank;
  asm("mov.u32 %0, %%cluster_ctarank;" : "=r"(rank));
  const int cluster = blockIdx.x >> 1;
  auto get_rounds = [&](int& first, int& count) {
    uint32_t c;
    asm volatile("mov.u32 %0, %%ctaid.x;" : "=r"(c));
    c >>= 1;
    first = sched.start[c];
    count = sched.start[c + 1] - first;
  };

  if (threadIdx.x == 0) {
    asm volatile("prefetch.tensormap [%0];" ::"l"(&tmK) : "memory");
    asm volatile("prefetch.tensormap [%0];" ::"l"(&tmQ) : "memory");
    asm volatile("prefetch.tensormap [%0];" ::"l"(&tmV) : "memory");
    for (int i = 0; i < 3; i++) mbar_init(bar_full + 8 * i, 1);
    for (int i = 0; i < 2; i++) mbar_init(bar_qfull + 8 * i, 1);
    asm volatile("fence.mbarrier_init.release.cluster;" ::: "memory");
    asm volatile("fence.proxy.async.shared::cta;" ::: "memory");
    const uint32_t e0 = sched.first[cluster];
    const Round r0 = decode_round(e0, rank);
    const int head = r0.head, qrow = r0.qrow;
    uint64_t polq, polk;
    asm volatile("createpolicy.fractional.L2::evict_first.b64 %0, 1.0;" : "=l"(polq));
    asm volatile("createpolicy.fractional.L2::evict_unchanged.b64 %0, 1.0;" : "=l"(polk));
    while ((uint32_t)clock() - c_entry < (e0 >> 16)) {}
    mbar_expect_tx(bar_full, SLOT);
    tma_load(s_kv, &tmK, bar_full, 0, head, polk);
    mbar_expect_tx(bar_qfull, SLOT);
    tma_load(s_qo, &tmQ, bar_qfull, qrow, head, polq);
    mbar_expect_tx(bar_full + 8, SLOT);
    tma_load(s_kv + SLOT, &tmK, bar_full + 8, BN, head, polk);
    mbar_expect_tx(bar_full + 16, SLOT);
    tma_load(s_kv + 2 * SLOT, &tmV, bar_full + 16, 0, head, polk);
    mbar_expect_tx(bar_qfull + 8, SLOT);
    tma_load(s_qo + SLOT, &tmQ, bar_qfull + 8, qrow + 64, head, polq);
  } else if (threadIdx.x == 32) {
    for (int i = 0; i < NSLOT; i++) {
      if (i >= 3) mbar_init(bar_full + 8 * i, 1);
      mbar_init(bar_empty + 8 * i, 4);
    }
    for (int i = 0; i < 2; i++) {
      mbar_init(bar_ostg + 8 * i, 4);
      mbar_init(bar_qreq + 8 * i, 1);
      mbar_init(bar_redo + 8 * i, 1);
      asm volatile("st.shared.u32 [%0], %1;" ::"r"(s_redo + 4 * i), "r"(0) : "memory");
    }
    asm volatile("fence.mbarrier_init.release.cluster;" ::: "memory");
    asm volatile("fence.proxy.async.shared::cta;" ::: "memory");
  }
  __syncthreads();
  asm volatile("barrier.cluster.arrive.relaxed.aligned;\nbarrier.cluster.wait.aligned;" ::: "memory");

  const int wg = __shfl_sync(0xffffffffu, threadIdx.x >> 7, 0);
  const int warp = __shfl_sync(0xffffffffu, (threadIdx.x >> 5) & 3, 0);
  const int lane = threadIdx.x & 31;

  if (wg == 0) {
    asm volatile("setmaxnreg.dec.sync.aligned.u32 24;");
    int first_round, nrounds;
    get_rounds(first_round, nrounds);
    const int nblocks = nrounds * NBLK;
    if (warp == 2) {
      uint64_t pol;
      asm volatile("createpolicy.fractional.L2::evict_unchanged.b64 %0, 1.0;" : "=l"(pol));
      auto load = [&](uint32_t slot, uint32_t ph, int head, int mc, const CUtensorMap* tm, uint32_t blk, uint32_t owner) {
        uint32_t dst = s_kv + slot * (SLOT / 8), bar = bar_full + slot, mode = blk == 8 ? 0 : !mc ? 1 : rank == owner ? 2 : 0;
        uint32_t bytes = blk == 8 ? 0 : SLOT;
        int row = blk * BN;
        asm volatile("" : "+r"(dst), "+r"(bar), "+r"(mode), "+r"(row), "+r"(head), "+r"(bytes), "+r"(ph), "+l"(tm));
        if (mode == 2) {
          mbar_wait(bar_empty + slot, ph);
          if (elect_one()) {
            tma_load_mc(dst, tm, bar, row, head, pol);
            mbar_expect_tx(bar, SLOT);
          }
        } else if (mode == 1) {
          mbar_wait(bar_empty + slot, ph);
          if (elect_one()) {
            tma_load(dst, tm, bar, row, head, pol);
            mbar_expect_tx(bar, SLOT);
          }
        } else {
          mbar_wait(bar_empty + slot, ph);
          if (elect_one()) mbar_expect_tx(bar, bytes);
        }
      };
      auto request_q = [&](int n, int pos) {
        pos += (n & 7) * 2;
        if (lane == 0 && pos == QREQ0) mbar_arrive(bar_qreq);
        if (lane == 0 && pos == QREQ1) mbar_arrive(bar_qreq + 8);
      };
      uint32_t cur = 0xb0, ord = 0x3210edc;
      Round r = decode_round(sched.list[first_round], rank);
      uint32_t kblk = 0x765432, vblk = 0x7654321;
      uint32_t flip = 0;
      for (int n = 1; n < nblocks; n++) {
        const int j = n & 7;
        if (j != 7) {
          load(ring_v(cur), cur >> 7 & 1, r.head, r.mc, (flip & 1) ? &tmV : &tmK, kblk & 15, 0);
          kblk >>= 4;
          request_q(n, 0);
          cur = ord;
          ord = ring_rot(ord);
          if (j == 2 && (flip & 2)) {
            cur = ring_swap(cur);
            ord = ring_stay(ord);
          }
          load(ring_k(cur), cur >> 3 & 1, r.head, r.mc, (flip & 2) ? &tmK : &tmV, vblk & 15, 1);
          vblk >>= 4;
          flip >>= 2;
          request_q(n, 1);
        } else {
          const uint32_t e = sched.list[first_round + (n >> 3) + 1];
          const Round r1 = decode_round(e, rank);
          const bool stay = e & 0x4000, other = stay && r1.head != r.head;
          if (n + 1 < nblocks) load(ring_v(cur), cur >> 7 & 1, stay ? r.head : r1.head, stay ? r.mc : r1.mc, stay ? &tmV : &tmK, stay ? 7 : 0, 0);
          request_q(n, 0);
          cur = ord;
          ord = ring_rot(ord);
          load(ring_k(cur), cur >> 3 & 1, other ? r1.head : r.head, other ? r1.mc : r.mc, other ? &tmK : &tmV, other ? 0 : stay ? 8 : vblk, 1);
          request_q(n, 1);
          r = r1;
          kblk = other ? 0x7652103 : stay ? 0x4328880 : 0x7654321;
          vblk = other ? 0x76543421 : stay ? 0x43210188 : 0x76543210;
          flip = other ? 0x7e : stay ? 0x20 : 0;
        }
      }
      ord ^= 0x8080000;
      for (int i = 0; i < NSLOT; i++, ord >>= 4) mbar_wait_sleep(bar_empty + ring_k(ord), ord >> 3 & 1);
    } else if (warp != 3) {
      const int w = warp == 0;
      uint64_t pol;
      asm volatile("createpolicy.fractional.L2::evict_first.b64 %0, 1.0;" : "=l"(pol));
      const uint32_t buf = s_qo + w * SLOT;
      mbar_wait_sleep(bar_ostg + 8 * w, 0);
      if (elect_one()) asm volatile("prefetch.tensormap [%0];" ::"l"(w ? &tmQT : &tmO) : "memory");
      for (int t = 0; t < nrounds; t++) {
        if (t + 1 < nrounds) {
          const uint32_t e = sched.list[first_round + t + 1];
          const Round r = decode_round(e, rank);
          const bool tail = w == 1 && (e & 0x8000);
          mbar_wait_sleep(bar_qreq + 8 * w, t & 1);
          if (elect_one()) {
            tma_load(tail ? sbase + OFF_QT : buf, tail ? &tmQT : &tmQ, bar_qfull + 8 * w, r.qrow + w * 64, r.head, pol);
            mbar_expect_tx(bar_qfull + 8 * w, tail ? 3 * 2048 : SLOT);
          }
        } else {
          if (elect_one()) mbar_arrive(bar_qfull + 8 * w);
        }
        const Round r = decode_round(sched.list[first_round + t], rank);
        const int row0 = r.qrow + w * 64;
        const int nrows = row0 + 64 <= SQ ? 64 : SQ % 64;
        mbar_wait_sleep(bar_ostg + 8 * w, ~t & 1);
        asm volatile("fence.proxy.async.shared::cta;" ::: "memory");
#pragma unroll 1
        for (int i = 0; i < nrows; i += OROWS) {
          if (elect_one()) {
            tma_store(&tmO, buf + i / 8 * RGRP, row0 + i, r.head, pol);
            asm volatile("cp.async.bulk.commit_group;" ::: "memory");
          }
          if (t + 1 < nrounds) asm volatile("cp.async.bulk.wait_group.read 0;" ::: "memory");
        }
      }
      asm volatile("cp.async.bulk.wait_group 0;" ::: "memory");
      if (elect_one()) mbar_arrive(bar_redo + 8 * w);
    } else {
      uint32_t cur = 0x21, ord = 0xa986543, stays = sched.stays[cluster];
      for (int n = 0; n < nblocks; n++) {
        if (n + 1 < nblocks) mbar_wait(bar_full + ring_k(cur), cur >> 3 & 1);
        mbar_wait(bar_full + ring_v(cur), cur >> 7 & 1);
        asm volatile("bar.sync 1, 288;" ::: "memory");
        asm volatile("bar.arrive 2, 288;" ::: "memory");
        cur = ord;
        ord = ring_rot(ord);
        if ((n & 7) == 6) {
          stays >>= 1;
          if (stays & 1) {
            cur = ring_swap(cur);
            ord = ring_stay(ord);
          }
        }
        TRACE_TILE();
      }
    }
  } else {
    asm volatile("setmaxnreg.inc.sync.aligned.u32 240;");
    const int w = wg - 1;
    int first_round, nrounds;
    get_rounds(first_round, nrounds);
    const int nblocks = nrounds * NBLK;
    float O[96], S[32];
    uint32_t Q[48], P0[16], P1[16];
    float l0 = 0.f, l1 = 0.f, inv0 = 1.f, inv1 = 1.f;
    uint32_t redo = 0;
    const uint32_t lane_addr = s_qo + w * SLOT + (warp * 2 + ((lane >> 3) & 1)) * RGRP + (lane & 7) * 128 + (((lane >> 4) ^ (lane & 7)) << 4);
    const uint32_t sum_addr = s_qo + w * SLOT + warp * 2 * RGRP + lane * 8;
    const uint32_t my_qfull = bar_qfull + 8 * w, my_ostg = bar_ostg + 8 * w;

    uint32_t empty_remote;
    asm("mapa.shared::cluster.u32 %0, %1, %2;" : "=r"(empty_remote) : "r"(bar_empty), "r"(threadIdx.x & 1));
    const bool releaser = (threadIdx.x & 126) == 32;
    auto release = [&](uint32_t s) {
      if (releaser) asm volatile("mbarrier.arrive.shared::cluster.b64 _, [%0];" ::"r"(empty_remote + s) : "memory");
    };
    uint32_t ks = 8, vs = 16, kp = 0, vp = 0, ord = 0x2106543;
    const uint32_t kd0 = kdesc0(s_kv), vd0 = vdesc0(s_kv);
    uint32_t kd = kd0 + ks * (SLOT / 128), vd = vd0 + vs * (SLOT / 128);
    auto advance = [&]() {
      kp = ks; vp = vs;
      ks = ring_k(ord); vs = ring_v(ord);
      ord = ord >> 8 | (ord & 0xff) << 20;
      kd = kd0 + ks * (SLOT / 128); vd = vd0 + vs * (SLOT / 128);
      asm volatile("" : "+r"(ks), "+r"(vs), "+r"(kd), "+r"(vd), "+r"(ord));
    };
    uint32_t stay = 0;

    uint32_t tails = w == 1 ? sched.tails[cluster] : 0u;
    auto turn_wait = [&]() { asm volatile("bar.sync %0, 288;" ::"r"(1 + w) : "memory"); };
    auto turn_pass = [&]() { asm volatile("bar.arrive %0, 288;" ::"r"(2 - w) : "memory"); };
    if (w == 1) asm volatile("bar.arrive %0, 288;" ::"r"(1 + (tails & 1)) : "memory");

    mbar_wait(my_qfull, 0);
    load_q(Q, lane_addr);
    scale_q(Q);
    mbar_wait(bar_full, 0);
    wg_fence();
    issue_qk(S, Q, kd0);
    wg_commit();
    wg_wait<0>();
    fence_regs(S);
    release(0);
    __syncwarp();
    if (lane == 0) mbar_arrive(my_ostg);
    uint32_t pending = 0;

    int n = 0;
    auto finish_sums = [&]() {
      float s0, s1;
      sums_get(sum_addr, s0, s1);
      inv0 = rcp(s0); inv1 = rcp(s1);
      l0 = l1 = 0.f;
      asm volatile("" : "+f"(inv0), "+f"(inv1)::"memory");
    };
    auto check_sums = [&](int t) { check_inv(inv0, inv1, redo, 1u << (t & 31)); };

    int exit_n = -1;
#pragma unroll 1
    while (true) {
#pragma unroll 1
      while (true) {
        const int j = n & 7;
        softmax_block(S, P0, l0, l1);
        asm volatile("" : "+f"(l0), "+f"(l1)::"memory");
        if (j != 0) {
          wg_wait<0>();
          release(vp);
          turn_wait();
          wg_fence();
          issue_qk3(S, Q, kd);
          wg_commit();
          issue_pv<true>(O, P0, vd);
          wg_commit();
          turn_pass();
          advance();
          if (j == 6) {
            mbar_wait(my_qfull, ((n >> 3) + 1) & 1);
            wg_wait<3>();
            load_q<0, 4>(Q, lane_addr);
            wg_wait<2>();
            load_q<4, 8>(Q, lane_addr);
          }
          wg_wait<1>();
          fence_regs(S);
          fence_regs(P1);
        } else {
          wg_wait<0>();
          fence_regs(O);
          fence_regs(P1);
          if (pending) {
            release(vp);
            epilogue_part<0, ESPLIT>(O, inv0, inv1, lane_addr);
          }
          turn_wait();
          wg_fence();
          issue_qk32(S, Q, kd);
          wg_commit();
          if (pending) {
            epilogue_part<ESPLIT, 12>(O, inv0, inv1, lane_addr);
            epilogue_done(my_ostg, lane);
          }
          wg_fence();
          issue_pv<false>(O, P0, vd);
          wg_commit();
          turn_pass();
          advance();
          check_sums((n >> 3) - 1);
          exit_n = ((tails & 2) || n + 8 == nblocks) ? n + 6 : -1;
          tails >>= 1;
          stay = sched.list[first_round + (n >> 3) + 1] & 0x4000;
          asm volatile("" : "+r"(exit_n), "+r"(tails), "+r"(redo), "+r"(stay));
          wg_wait<1>();
          fence_regs(S);
          pending = true;
        }
        release(kp);
        softmax_block(S, P1, l0, l1);
        asm volatile("" : "+f"(l0), "+f"(l1)::"memory");
        if (j == 6) {
          load_q<8, 12>(Q, lane_addr);
          sums_put(sum_addr, l0, l1);
          wg_wait<0>();
          release(vp);
          { const uint32_t k = ks; ks = stay ? vs : ks; vs = stay ? k : vs; ord = stay ? ring_stay(ord) : ord; }
          kd = kd0 + ks * (SLOT / 128); vd = vd0 + vs * (SLOT / 128);
          asm volatile("" : "+r"(ks), "+r"(vs), "+r"(kd), "+r"(vd), "+r"(ord));
          scale_q(Q);
          if (n == exit_n) {
            turn_wait();
            wg_fence();
            issue_pv<true>(O, P1, vd);
            wg_commit();
            break;
          }
          asm volatile("" ::: "memory");
          turn_wait();
          wg_fence();
          issue_qk32(S, Q, kd);
          wg_commit();
          issue_pv<true>(O, P1, vd);
          wg_commit();
          turn_pass();
          advance();
          if (pending) finish_sums();
          wg_wait<1>();
        } else {
          wg_wait<0>();
          release(vp);
          turn_wait();
          wg_fence();
          issue_qk(S, Q, kd);
          wg_commit();
          issue_pv<true>(O, P1, vd);
          wg_commit();
          turn_pass();
          advance();
          wg_wait<1>();
        }
        fence_regs(S);
        fence_regs(P0);
        release(kp);
        n += 2;
      }
      if (n + 2 == nblocks) {
        if (w == 0) turn_pass();
        finish_sums();
        check_sums(n >> 3);
        wg_wait<0>();
        fence_regs(O);
        release(vs);
        epilogue_part<0, 12>(O, inv0, inv1, lane_addr);
        epilogue_done(my_ostg, lane);
        break;
      }
      const int t = n >> 3;
      const uint32_t qt = sbase + OFF_QT, pt = sbase + OFF_PT, red = sbase + OFF_RED;
      const uint32_t tl = ((lane & 7) + (lane >> 4) * 8) * 128 + (((warp * 2 + ((lane >> 3) & 1)) ^ (lane & 7)) << 4);
      const bool tlast = n + 10 == nblocks;
      float lt[4] = {0.f, 0.f, 0.f, 0.f};
      float ST[8], OT[3][8];
      wg_fence();
      issue_qkT(ST, kd, qt);
      wg_commit();
      turn_pass();
      finish_sums();
      check_sums(t);
      wg_wait<0>();
      fence_regs(ST);
      fence_regs(O);
      release(ks);
      release(vs);
      advance();
      epilogue_part<0, NT_SPLIT>(O, inv0, inv1, lane_addr);
      if (NT_SPLIT == 12) epilogue_done(my_ostg, lane);
      tail_softmax(ST, lt, pt + tl);
      auto tail_step = [&](auto first_c, int jj) {
        constexpr bool FIRST = decltype(first_c)::value;
        asm volatile("fence.proxy.async.shared::cta;" ::: "memory");
        turn_wait();
        wg_fence();
        issue_qkT(ST, kd, qt);
        wg_commit();
        issue_pvT<!FIRST>(OT, vd, pt + (jj & 1) * 2048);
        wg_commit();
        turn_pass();
        advance();
        wg_wait<1>();
        fence_regs(ST);
        release(kp);
        tail_softmax(ST, lt, pt + (~jj & 1) * 2048 + tl);
        wg_wait<0>();
        fence_regs(OT[0]); fence_regs(OT[1]); fence_regs(OT[2]);
        release(vp);
      };
      tail_step(Bool<true>(), 0);
      if (NT_SPLIT < 12) {
        epilogue_part<NT_SPLIT, 12>(O, inv0, inv1, lane_addr);
        epilogue_done(my_ostg, lane);
      }
#pragma unroll 1
      for (int jj = 1; jj < 7; jj++) tail_step(Bool<false>(), jj);
      mbar_wait(my_qfull, t & 1);
      load_q(Q, lane_addr);
      scale_q(Q);
      tail_reduce(lt, red, warp, lane);
#pragma unroll
      for (int i = 0; i < 4; i++) lt[i] = rcp(lt[i]);
      check_inv(lt[0], lt[1], redo, 1u << ((t + 1) & 31));
      check_inv(lt[2], lt[3], redo, 1u << ((t + 1) & 31));
      inv0 = inv1 = 1.f;
      asm volatile("fence.proxy.async.shared::cta;" ::: "memory");
      turn_wait();
      wg_fence();
      issue_pvT<true>(OT, vd, pt + 2048);
      wg_commit();
      issue_qk(S, Q, kd);
      wg_commit();
      if (!tlast) turn_pass();
      wg_wait<1>();
      fence_regs(OT[0]); fence_regs(OT[1]); fence_regs(OT[2]);
      release(vs);
#pragma unroll
      for (int b = 0; b < 3; b++)
        stsm_x4_trans(s_qo + SLOT + b * SLAB + tl + (lane >> 4) * (RGRP - 1024),
                      pack_bf16(OT[b][0] * lt[0], OT[b][1] * lt[1]), pack_bf16(OT[b][2] * lt[0], OT[b][3] * lt[1]),
                      pack_bf16(OT[b][4] * lt[2], OT[b][5] * lt[3]), pack_bf16(OT[b][6] * lt[2], OT[b][7] * lt[3]));
      epilogue_done(my_ostg, lane);
      wg_wait<0>();
      fence_regs(S);
      if (tlast) break;
      release(ks);
      advance();
#pragma unroll
      for (int i = 0; i < 96; i++) O[i] = 0.f;
      pending = false;
      n += 10;
      tails >>= 1;
    }
    if (redo) asm volatile("red.shared.or.b32 [%0], %1;" ::"r"(s_redo + 4 * w), "r"(redo) : "memory");
    asm volatile("bar.sync 4, 256;" ::: "memory");
    asm volatile("ld.shared.u32 %0, [%1];" : "=r"(redo) : "r"(s_redo + 4 * w) : "memory");
    redo = __shfl_sync(0xffffffffu, redo, 0);
    if (redo) {
      mbar_wait_sleep(bar_redo + 8 * w, 0);
      asm volatile("bar.sync %0, 128;" ::"r"(5 + w) : "memory");
      uint32_t phase = 1;
      get_rounds(first_round, nrounds);
      uint32_t rank;
      asm volatile("mov.u32 %0, %%cluster_ctarank;" : "=r"(rank));
#pragma unroll 1
      for (int t = 0; t < nrounds; t++) {
        if (!(redo >> (t & 31) & 1)) continue;
        const Round r = decode_round(sched.list[first_round + t], rank);
        redo_tile(&tmQ, &tmK, &tmV, &tmO, r.head, r.qrow + w * 64, s_qo + w * SLOT, s_kv + 2 * w * SLOT, lane_addr, bar_redo + 8 * w, phase, 5 + w);
      }
    }
  }
}

typedef CUresult (*EncodeFn)(CUtensorMap*, CUtensorMapDataType, cuuint32_t, void*, const cuuint64_t*, const cuuint64_t*,
                             const cuuint32_t*, const cuuint32_t*, CUtensorMapInterleave, CUtensorMapSwizzle,
                             CUtensorMapL2promotion, CUtensorMapFloatOOBfill);

void make_map(EncodeFn fn, CUtensorMap* tm, const void* ptr, int rows, int box_rows) {
  cuuint64_t dims[5] = {64, 8, 3, (cuuint64_t)rows / 8, (cuuint64_t)NHEADS};
  cuuint64_t strides[4] = {HD * 2, 128, 8 * HD * 2, (cuuint64_t)rows * HD * 2};
  cuuint32_t box[5] = {64, 8, 3, (cuuint32_t)box_rows / 8, 1};
  cuuint32_t estr[5] = {1, 1, 1, 1, 1};
  fn(tm, CU_TENSOR_MAP_DATA_TYPE_BFLOAT16, 5, const_cast<void*>(ptr), dims, strides, box, estr,
     CU_TENSOR_MAP_INTERLEAVE_NONE, CU_TENSOR_MAP_SWIZZLE_128B, CU_TENSOR_MAP_L2_PROMOTION_L2_128B, CU_TENSOR_MAP_FLOAT_OOB_FILL_NONE);
}

#define STAGGER 250
#define COST_N 12690
#define COST_T 10800
#define COST_TN 12720
#define TAIL_LATE 36
#define TAIL_MAX 60
#define HEAVY_STEP 3
const uint16_t DELAY66[66] = {
  0, 86, 950, 1122, 259, 690, 604, 431, 345, 777, 518, 172, 1900, 1381, 2245, 1295, 2159, 863, 1468, 1209, 3109, 1554,
  2331, 2677, 3281, 1036, 1640, 1727, 3800, 4318, 3195, 3022, 3540, 3368, 3886, 2504, 2936, 2590, 2418, 3713, 2072, 3454, 2763, 4145,
  4231, 2850, 4490, 3627, 5354, 4404, 4922, 4577, 4836, 5095, 3972, 5440, 4663, 5181, 5268, 5009, 5527, 4059, 5613, 4750, 1813, 1986,
};
const uint16_t LIST66[66][28] = {
  {0x0000,0x0020,0x4420,0x8632,0x005a,0xc65a,0x0075,0x4275,0x00a4,0xc6a4,0x00c6,0x44c6,0x00f0,0x44f0,0x0118,0xc718,0x0336,0x033d,0x8758,0x0174,0xc774,0x058c,0x03ac,0xc7ac,0x01c7,0xc7c6,0x05d1,0x03fe},
  {0x0200,0x0220,0xc620,0x0042,0x4442,0x006c,0xc66c,0x0475,0x02a4,0x44a4,0x86b6,0x00d7,0x44d7,0x86f0,0x0109,0x4509,0x8736,0x014a,0x454a,0x8764,0x018c,0x438c,0x879c,0x03ba,0x45ba,0x01dd,0x45dd,0x87fe},
  {0x0400,0xc600,0x0032,0x4432,0x0053,0x4453,0x046c,0x0094,0x4494,0x00b6,0x44b6,0x00e0,0x44e0,0x02f1,0x0309,0x0136,0x4536,0x0158,0x4558,0x0175,0x4575,0x019d,0x01ba,0xc7ba,0x01d1,0x43d1,0x01fe,0xffff},
  {0x0001,0x0024,0x4424,0x0043,0x4243,0x025b,0x026d,0x0285,0x00a5,0x44a5,0x00d6,0xc6d6,0x00f1,0x44f1,0x0119,0x4319,0x013d,0xc73c,0x0164,0x4564,0x0375,0x019c,0x439c,0x01c6,0x01dc,0x43dc,0x01ff,0xffff},
  {0x0004,0xc604,0x022d,0x0044,0xc644,0x0264,0x0265,0x008d,0x448d,0x02af,0x00c8,0xc6c8,0x02ee,0x02ef,0x010f,0x450f,0x872e,0x014c,0xc74c,0x036c,0x036d,0x0195,0x4595,0x87b8,0x01d2,0xc7d2,0x03f4,0xc7f4},
  {0x000e,0xc60e,0x0229,0x0048,0xc648,0x026a,0x026b,0x0089,0x4489,0x02a9,0x00cc,0xc6cc,0x02e8,0x02e9,0x010b,0x450b,0x872a,0x0150,0xc750,0x0372,0x0373,0x018f,0x458f,0x87b4,0x03c1,0x87d8,0x01fa,0xc7fa},
  {0x000c,0xc60c,0x0031,0x4431,0x024f,0x0272,0xc672,0x0290,0x0291,0x00b5,0x44b5,0x02d1,0x00f6,0xc6f6,0x0314,0x0315,0x0133,0x4533,0x8756,0x0178,0xc778,0x0396,0x0397,0x87b2,0x01d6,0xc7d6,0x03f6,0xc7f6},
  {0x0008,0xc608,0x0027,0x4427,0x0251,0x006e,0xc66e,0x028e,0x028f,0x00b3,0x44b3,0x02d3,0x00f2,0xc6f2,0x0312,0x0313,0x0135,0x4535,0x8754,0x0176,0xc776,0x0398,0x0399,0x87b6,0x05b7,0x87da,0x01f8,0xc7f8},
  {0x0006,0xc606,0x022f,0x0046,0xc646,0x0266,0x0267,0x008b,0x448b,0x02b1,0x00ca,0xc6ca,0x02ea,0x02eb,0x010d,0x450d,0x0331,0x0152,0xc752,0x036e,0x036f,0x8792,0x01ae,0xc7ae,0x03ce,0xc7ce,0x05e7,0x87fc},
  {0x0010,0x0022,0xc622,0x024a,0xc64a,0x0268,0x0269,0x0087,0x4487,0x02a7,0x00ce,0xc6ce,0x02ec,0x0107,0x4507,0x871a,0x013a,0xc73a,0x035a,0x035b,0x877a,0x019a,0xc79a,0x03bc,0xc7bc,0x01df,0x45df,0x87ee},
  {0x000a,0xc60a,0x002b,0x442b,0x024d,0x0070,0xc670,0x0292,0x0293,0x00ab,0x44ab,0x02d5,0x00f4,0xc6f4,0x0310,0x0311,0x872c,0x014e,0xc74e,0x0370,0x0371,0x0191,0x4591,0x87b0,0x01d4,0xc7d4,0x03f2,0xc7f2},
  {0x0002,0xc602,0x0025,0x4425,0x8642,0x0253,0x026c,0x8684,0x0295,0x02a5,0x02c6,0xc6c6,0x00e1,0x44e1,0x02ff,0x0128,0xc728,0x034a,0xc74a,0x0359,0x018a,0xc78a,0x039d,0x459d,0x03c7,0x45c7,0x87e8,0x05e9},
  {0x0204,0x002c,0xc62c,0x0244,0x4444,0x0065,0x4465,0x028d,0x00ae,0xc6ae,0x02c8,0x44c8,0x00ef,0x44ef,0x030f,0x012e,0x452e,0x034c,0x034d,0x016d,0x456d,0x0395,0x01b9,0x43b9,0x03d2,0x05d3,0x05f5,0xffff},
  {0x020e,0x0028,0xc628,0x0248,0x4448,0x006b,0x446b,0x0289,0x00a8,0xc6a8,0x02cc,0x44cc,0x00e9,0x44e9,0x030b,0x012a,0x452a,0x0151,0x4351,0x0572,0x018e,0x458e,0x01b5,0x43b5,0x01d9,0x43d9,0x05fa,0xffff},
  {0x020c,0x0030,0x4430,0x024e,0x444e,0x0073,0x4473,0x0490,0x02b4,0x44b4,0x00d1,0x44d1,0x02f7,0x0114,0xc714,0x0332,0xc732,0x0157,0x4357,0x0378,0x0579,0x8796,0x01b2,0x43b2,0x03d6,0x03d7,0x05f6,0xffff},
  {0x0208,0x0026,0x4426,0x0250,0xc650,0x026e,0x446e,0x008f,0x448f,0x02b3,0x02d2,0xc6d2,0x02f2,0x44f2,0x0113,0x4513,0x0335,0x0354,0x0355,0x0376,0x0577,0x0598,0x01b7,0x43b7,0x03da,0x05db,0x05f8,0xffff},
  {0x0206,0x002e,0xc62e,0x0246,0x4446,0x0067,0x4467,0x028b,0x00b0,0xc6b0,0x02ca,0x02cb,0x00eb,0x44eb,0x030d,0x0130,0xc730,0x0352,0x0353,0x016f,0x456f,0x0392,0x03ae,0x03af,0x01cf,0x45cf,0x01fd,0xffff},
  {0x0210,0xc610,0x0223,0x004a,0x444a,0x0069,0x4469,0x0287,0x00a6,0xc6a6,0x02ce,0x44ce,0x04ec,0x02ed,0x011a,0x451a,0x033a,0x033b,0x015b,0x455b,0x037a,0x019b,0x439b,0x01bd,0x45bd,0x01ee,0x43ee,0xffff},
  {0x020a,0x002a,0x442a,0x024c,0xc64c,0x0270,0x4470,0x0093,0x4493,0x02ab,0x00d4,0xc6d4,0x02f4,0x44f4,0x0111,0x4511,0x032c,0x014f,0x434f,0x0570,0x0190,0x4590,0x01b1,0x43b1,0x01d5,0x45d5,0x05f3,0xffff},
  {0x0202,0x0203,0x0225,0x0242,0x0443,0x0274,0xc674,0x0294,0xc694,0x02ad,0x02b6,0x02c7,0x02e1,0x00ff,0x44ff,0x0328,0x0529,0x033c,0x054b,0x0365,0x038a,0x058b,0x059c,0x03c6,0x45c6,0x01e9,0x43e9,0xffff},
  {0x0404,0x022c,0x442c,0x0045,0x0064,0x4464,0x028c,0x448c,0x00af,0x44af,0x02c9,0x00ee,0xc6ee,0x030e,0xc70e,0x032e,0x032f,0x054c,0x016c,0x456c,0x0394,0xc794,0x01b8,0x45b8,0x01d3,0x43d3,0x01f5,0xffff},
  {0x040e,0x0228,0x4428,0x0049,0x4449,0x046a,0x0088,0x4488,0x00a9,0x44a9,0x02cd,0x44cd,0x86e8,0x010a,0xc70a,0x032a,0x032b,0x0350,0x0551,0x0173,0x4573,0x038f,0x03b4,0x05b5,0x03d8,0x05d9,0x05fb,0xffff},
  {0x040c,0x0230,0xc630,0x004e,0xc64e,0x0072,0x4472,0x0091,0x4491,0x02b5,0x00d0,0x44d0,0x00f7,0x44f7,0x0514,0x0132,0x4532,0x0356,0x0557,0x0578,0x0196,0x4596,0x01b3,0x45b3,0x05d6,0x01f6,0x87ea,0xffff},
  {0x0408,0x0226,0xc626,0x0050,0x4450,0x006f,0x446f,0x048e,0x00b2,0xc6b2,0x00d2,0x44d2,0x00f3,0x44f3,0x0512,0x0134,0x4534,0x0155,0x4555,0x0576,0x0198,0xc798,0x01b6,0x43b6,0x01da,0x45da,0x01f9,0xffff},
  {0x0406,0x022e,0x442e,0x0047,0x0066,0x4466,0x028a,0xc68a,0x02b0,0x44b0,0x04ca,0x00ea,0x44ea,0x030c,0xc70c,0x0330,0x4530,0x0153,0x4553,0x876e,0x0192,0x4592,0x01af,0x45af,0x03cf,0x03e6,0x03fd,0xffff},
  {0x0410,0x0222,0x4422,0x004b,0x444b,0x0468,0x0086,0xc686,0x02a6,0x44a6,0x00cf,0x44cf,0x00ed,0x44ed,0x011b,0x431b,0x053a,0x015a,0x455a,0x017b,0x437b,0x059a,0x01bc,0x45bc,0x03de,0xc7de,0x01ef,0xffff},
  {0x040a,0x022a,0xc62a,0x004c,0x444c,0x0071,0x4471,0x0492,0x00aa,0x44aa,0x02d4,0x44d4,0x00f5,0x44f5,0x8710,0x012c,0x452c,0x034e,0x054f,0x0171,0x4571,0x0391,0x03b0,0x05b1,0x05d4,0x01f2,0x45f2,0xffff},
  {0x0402,0x0224,0xc624,0x0233,0x025a,0x445a,0x0084,0x4284,0x00ac,0x44ac,0x02b7,0x02e0,0xc6e0,0x0108,0x4508,0x0528,0x013c,0x453c,0x0358,0x0374,0x058a,0x038d,0x03ad,0x03bb,0x05d0,0x03e8,0x05fe,0xffff},
  {0x0205,0x002d,0x442d,0x0245,0x4445,0x8664,0x008c,0xc68c,0x02ae,0x44ae,0x00c9,0x44c9,0x04ee,0x010e,0x450e,0x012f,0x452f,0x014d,0x454d,0x876c,0x0194,0x4594,0x03b8,0x05b9,0x05d2,0x01f4,0x45f4,0xffff},
  {0x020f,0x0029,0x4429,0x0249,0x006a,0xc66a,0x0288,0xc688,0x02a8,0x44a8,0x00cd,0x00e8,0x44e8,0x030a,0x450a,0x012b,0x452b,0x0550,0x0172,0xc772,0x038e,0xc78e,0x01b4,0x45b4,0x01d8,0x45d8,0x03fa,0xffff},
  {0x020d,0x440d,0x0231,0x004f,0x444f,0x0273,0x0090,0xc690,0x00b4,0xc6b4,0x02d0,0xc6d0,0x02f6,0x44f6,0x0115,0x4515,0x0333,0x0156,0x4556,0x0179,0x4379,0x0197,0x4597,0x03b3,0x01d7,0x45d7,0x05f7,0xffff},
  {0x0009,0x4409,0x0227,0x0051,0x4451,0x026f,0x008e,0xc68e,0x02b2,0x44b2,0x00d3,0x44d3,0x02f3,0x0112,0xc712,0x0334,0xc734,0x0154,0x4554,0x0177,0x4377,0x0199,0x4599,0x05b6,0x01db,0x43db,0x03f8,0xffff},
  {0x0207,0x002f,0x442f,0x0247,0x4447,0x8666,0x008a,0x448a,0x00b1,0x44b1,0x00cb,0x44cb,0x86ea,0x010c,0x450c,0x0131,0x4531,0x0552,0x016e,0x456e,0x0193,0x4593,0x05ae,0x01ce,0x45ce,0x87e6,0x05fd,0xffff},
  {0x0011,0x0023,0x4423,0x024b,0x0068,0xc668,0x0286,0x4486,0x00a7,0x44a7,0x02cf,0x00ec,0xc6ec,0x0307,0x031a,0x051b,0x013b,0x453b,0x875a,0x017a,0x457a,0x039a,0x059b,0x03bd,0x01de,0x45de,0x05ee,0xffff},
  {0x020b,0x440b,0x022b,0x004d,0x444d,0x0271,0x0092,0xc692,0x02aa,0xc6aa,0x00d5,0x44d5,0x02f5,0x0110,0x4510,0x012d,0x432d,0x054e,0x0170,0xc770,0x0390,0xc790,0x01b0,0x45b0,0x03d4,0x03d5,0x01f3,0xffff},
  {0x0003,0x4403,0x0232,0x0252,0xc652,0x0074,0x4474,0x0484,0x02ac,0xc6ac,0x00c7,0x44c7,0x02f0,0x0308,0xc708,0x0129,0x4329,0x014b,0x434b,0x0364,0x018b,0x438b,0x01ad,0x45ad,0x03d0,0x01e8,0x45e8,0xffff},
  {0x0005,0x4405,0x003e,0x443e,0x025e,0xc65e,0x007f,0x427f,0x00a1,0x44a1,0x02c0,0x00e7,0x44e7,0x0504,0x0126,0x4526,0x0347,0x4547,0x0368,0x0188,0xc788,0x01aa,0x45aa,0x03c8,0xc7c8,0x01f0,0x45f0,0xffff},
  {0x000f,0x440f,0x0038,0x4438,0x0260,0xc660,0x0081,0x4281,0x009f,0x449f,0x02c3,0x02e2,0xc6e2,0x0103,0x4303,0x0125,0x4525,0x0348,0x016b,0x456b,0x0584,0x03a0,0xc7a0,0x01c0,0x45c0,0x03e2,0x01fb,0xffff},
  {0x000d,0x0013,0x0234,0xc634,0x0057,0x4257,0x0079,0x4479,0x0296,0x00ba,0x44ba,0x02da,0x04db,0x02f9,0x031c,0xc71c,0x0140,0x4540,0x035e,0x055f,0x037f,0x019f,0x459f,0x03c2,0xc7c2,0x01ea,0x01f7,0xffff},
  {0x0209,0x001d,0x023c,0xc63c,0x0059,0x4259,0x007d,0x447d,0x029d,0x02be,0xc6be,0x00dd,0x42dd,0x0101,0x4501,0x0323,0x0344,0xc744,0x0161,0x4361,0x0181,0x4581,0x03a7,0x01cc,0x45cc,0x05e4,0x05f9,0xffff},
  {0x0007,0x4407,0x0036,0xc636,0x005c,0x445c,0x007b,0x427b,0x0099,0x00b8,0xc6b8,0x00de,0x44de,0x00fd,0x42fd,0x011f,0x013e,0x453e,0x0167,0x4567,0x0582,0x01a4,0x45a4,0x03ca,0xc7ca,0x01e7,0x01fc,0xffff},
  {0x0211,0x4411,0x0040,0xc640,0x0062,0x4462,0x0083,0x4283,0x00a3,0x00c4,0x44c4,0x02e4,0xc6e4,0x0306,0x0117,0x4317,0x0139,0x015c,0x455c,0x017d,0x437d,0x01a3,0x01be,0x45be,0x03e0,0xc7e0,0x05e1,0xffff},
  {0x000b,0x001b,0x023a,0xc63a,0x0055,0x4255,0x0077,0x4477,0x029b,0x02bc,0xc6bc,0x00d9,0x42d9,0x00fb,0x44fb,0x0321,0x0342,0xc742,0x0162,0x4562,0x0187,0x4387,0x01a9,0x45a9,0x03c4,0x01ed,0x43ed,0xffff},
  {0x0016,0x0017,0x003f,0x423f,0x005f,0x007e,0x447e,0x02a0,0xc6a0,0x00c1,0xc6c0,0x00e6,0x44e6,0x0304,0x0505,0x0327,0x0147,0xc746,0x0168,0x4568,0x0388,0x0589,0x03ab,0x01c9,0x45c9,0x03f1,0xc7f0,0xffff},
  {0x0018,0x0019,0x0039,0x4239,0x0061,0x0080,0x4480,0x029e,0xc69e,0x02c2,0x44c2,0x00e3,0x0102,0x4502,0x0324,0xc724,0x0149,0xc748,0x016a,0x456a,0x0185,0x4385,0x01a1,0x03c0,0xc7c0,0x01e3,0x43e3,0xffff},
  {0x0012,0xc612,0x0034,0x4434,0x0256,0x0457,0x0279,0x0096,0x4496,0x00bb,0x44bb,0x04da,0x00f8,0x44f8,0x011d,0x451d,0x0341,0x015e,0xc75e,0x017e,0x457e,0x039e,0xc79e,0x01c2,0x45c2,0x03ea,0x45ea,0xffff},
  {0x001c,0xc61c,0x003c,0x443c,0x0258,0x0459,0x027d,0x009c,0xc69c,0x00be,0x44be,0x02dc,0x04dd,0x0301,0x0122,0xc722,0x0144,0x4544,0x0360,0x0561,0x0381,0x01a6,0x45a6,0x03cc,0xc7cc,0x01e5,0x43e5,0xffff},
  {0x0014,0x0015,0x0037,0x4237,0x005d,0x007a,0x447a,0x0298,0xc698,0x02b8,0x44b8,0x00df,0x00fc,0x44fc,0x031e,0xc71e,0x033e,0xc73e,0x0166,0x4566,0x0382,0x0583,0x03a4,0x01ca,0x45ca,0x03e7,0x05fc,0xffff},
  {0x001e,0x001f,0x0041,0x4241,0x0063,0x0082,0x4482,0x02a2,0xc6a2,0x00c5,0x42c5,0x00e5,0x44e5,0x0116,0xc716,0x0138,0x4538,0x015d,0x455d,0x877c,0x057b,0x03a2,0xc7a2,0x01bf,0x43bf,0x01e1,0x43e1,0xffff},
  {0x001a,0xc61a,0x003a,0x443a,0x0254,0x0455,0x0277,0x009a,0xc69a,0x00bc,0x44bc,0x02d8,0x04d9,0x02fb,0x0120,0xc720,0x0142,0x4542,0x0163,0x4363,0x0386,0x0587,0x03a9,0x01c5,0xc7c4,0x01ec,0x45ec,0xffff},
  {0x0216,0x0217,0x4417,0x043f,0x025f,0x445f,0x867e,0x00a0,0x44a0,0x02c1,0x44c1,0x02e7,0x0104,0xc704,0x0326,0xc726,0x0146,0x4346,0x0169,0xc768,0x0189,0x4389,0x01ab,0x45ab,0x03c9,0x01f1,0x45f1,0xffff},
  {0x0218,0x0219,0x4419,0x0439,0x0261,0x4461,0x8680,0x009e,0x449e,0x00c3,0x44c3,0x02e3,0x44e3,0x8702,0x0124,0x4524,0x0349,0x4549,0x036b,0x0184,0xc784,0x0585,0x03a1,0x45a1,0x01e2,0xc7e2,0x05e3,0xffff},
  {0x0212,0x0213,0x0035,0x0056,0x4456,0x0278,0xc678,0x0097,0xc696,0x02ba,0xc6ba,0x00db,0x42db,0x00f9,0x44f9,0x031d,0x0141,0x4541,0x055e,0x037e,0xc77e,0x019e,0x459e,0x05b2,0x03c3,0x01eb,0x45eb,0xffff},
  {0x021c,0x021d,0x003d,0x0058,0x4458,0x027c,0xc67c,0x029c,0x449c,0x00bf,0x00dc,0x44dc,0x0300,0xc700,0x0322,0x4522,0x0145,0x0160,0x4560,0x0380,0xc780,0x01a7,0x45a7,0x03cd,0x01e4,0xc7e4,0x05e5,0xffff},
  {0x0214,0xc614,0x0236,0x4436,0x025c,0xc65c,0x027a,0x047b,0x0299,0x4499,0x02b9,0x02de,0xc6de,0x02fc,0x04fd,0x031f,0x451f,0x033f,0x0366,0xc766,0x0183,0x4383,0x01a5,0x43a5,0x01cb,0x01e6,0x45e6,0xffff},
  {0x021e,0xc61e,0x0240,0x4440,0x0262,0xc662,0x0282,0x0483,0x02a3,0x44a3,0x86c4,0x00e4,0x44e4,0x0506,0x0316,0x0517,0x0339,0x4539,0x035d,0x037c,0x057d,0x03a3,0x45a3,0x87be,0x01e0,0x45e0,0x03ef,0xffff},
  {0x021a,0x021b,0x003b,0x0054,0x4454,0x0276,0xc676,0x029a,0x449a,0x00bd,0x00d8,0x44d8,0x02fa,0xc6fa,0x0320,0x4520,0x0143,0x4343,0x0362,0x0186,0xc786,0x03a8,0x45a8,0x03c5,0x45c5,0x87ec,0x03f3,0xffff},
  {0x0416,0xc616,0x023e,0xc63e,0x005e,0x445e,0x027e,0x047f,0x02a1,0x00c0,0x44c0,0x02e6,0xc6e6,0x0105,0x4305,0x0127,0x4527,0x0546,0x0369,0x4569,0x0588,0x03aa,0xc7aa,0x01c8,0x45c8,0x03f0,0x03f5,0xffff},
  {0x0418,0xc618,0x0238,0xc638,0x0060,0x4460,0x0280,0x0481,0x029f,0x00c2,0xc6c2,0x00e2,0x44e2,0x0302,0x0503,0x0325,0x0148,0x4548,0x036a,0xc76a,0x0384,0x01a0,0x45a0,0x01c1,0x45c1,0x05e2,0x03fb,0xffff},
  {0x0412,0x0413,0x0235,0x4435,0x8656,0x0078,0x4478,0x0297,0x4497,0x02bb,0x00da,0xc6da,0x02f8,0xc6f8,0x011c,0x451c,0x0340,0xc740,0x015f,0x435f,0x017f,0x457f,0x039f,0x01c3,0x45c3,0x03eb,0x03f7,0xffff},
  {0x041c,0x041d,0x023d,0x443d,0x8658,0x007c,0x447c,0x009d,0x449d,0x02bf,0x44bf,0x86dc,0x0100,0x4500,0x0123,0x4523,0x0345,0x4545,0x8760,0x0180,0x4580,0x03a6,0xc7a6,0x01cd,0x45cd,0x03e4,0x03f9,0xffff},
  {0x0414,0x0215,0x4415,0x0437,0x025d,0x445d,0x867a,0x0098,0x4498,0x00b9,0x44b9,0x02df,0x44df,0x86fc,0x011e,0x451e,0x013f,0x453f,0x0367,0x0182,0xc782,0x0393,0x87a4,0x05a5,0x03cb,0x45cb,0x03fc,0xffff},
  {0x041e,0x021f,0x441f,0x0441,0x0263,0x4463,0x8682,0x00a2,0x44a2,0x02c4,0x04c5,0x02e5,0x0106,0xc706,0x0516,0x0338,0xc738,0x035c,0xc75c,0x017c,0x457c,0x01a2,0x45a2,0x03be,0x05bf,0x03df,0x05ef,0xffff},
  {0x041a,0x041b,0x023b,0x443b,0x8654,0x0076,0x4476,0x009b,0x449b,0x02bd,0x44bd,0x86d8,0x00fa,0x44fa,0x0121,0x4521,0x052d,0x0543,0x8762,0x0563,0x0586,0x01a8,0xc7a8,0x01c4,0x45c4,0x03ec,0x05ed,0xffff},
  {0x0201,0x0021,0x0033,0x4433,0x005b,0x445b,0x0085,0x4485,0x00ad,0x44ad,0x02d6,0x44d6,0x00fe,0x44fe,0x0518,0x0137,0x4537,0x0159,0x4559,0x0574,0x878c,0x01ac,0x45ac,0x01d0,0xc7d0,0x05dc,0x03ff,0xffff},
  {0x0401,0x0221,0x4421,0x0052,0x4452,0x006d,0x446d,0x0095,0x4495,0x00b7,0x44b7,0x02d7,0x02fe,0xc6fe,0x0318,0x0519,0x0337,0x053d,0x0165,0x4565,0x018d,0x458d,0x01bb,0x45bb,0x87dc,0x03dd,0x05ff,0xffff},
};

void make_schedule(Schedule& s, int nclusters) {
  static uint16_t lists[MAX_CLUSTERS][NROUNDS];
  int cnt[MAX_CLUSTERS] = {0}, len[MAX_CLUSTERS], ntail[MAX_CLUSTERS] = {0}, quota[MAX_CLUSTERS] = {0};
  long long busy[MAX_CLUSTERS], fin[MAX_CLUSTERS];
  const int ntails = NROUNDS / 7, base = NROUNDS / nclusters, nheavy = NROUNDS % nclusters;
  const int step = nheavy * HEAVY_STEP <= nclusters ? HEAVY_STEP : 1;
  for (int c = 0; c < nclusters; c++) {
    len[c] = base + (c % step == 0 && c / step < nheavy);
    busy[c] = c / 3 * STAGGER;
    fin[c] = busy[c] + (long long)len[c] * COST_N;
  }
  for (int k = 0; k < ntails; k++) {
    int c = -1;
    for (int i = 0; i < nclusters; i++)
      if (quota[i] < len[i] / 2 && (c < 0 || fin[i] > fin[c])) c = i;
    quota[c]++;
    fin[c] -= 2 * COST_N - COST_T - COST_TN;
  }
  int gn = 0, gt = 3;
  for (int k = 0; k < NROUNDS; k++) {
    int c = -1;
    for (int i = 0; i < nclusters; i++)
      if (cnt[i] < len[i] && (c < 0 || busy[i] < busy[c])) c = i;
    const bool after_tail = cnt[c] > 0 && (lists[c][cnt[c] - 1] & 0x8000);
    const bool may_t = cnt[c] > 0 && !after_tail;
    const int left = len[c] - cnt[c], q = quota[c] - ntail[c];
    const bool due = (long long)(gt / 7) * quota[c] * 8 >= (long long)(ntail[c] * 8 + (c * 5 & 7)) * ntails;
    bool tail = may_t && q > 0 && (2 * q > left || (gn - gt >= TAIL_LATE && due) || gn - gt >= TAIL_MAX);
    if (4 * quota[c] >= len[c]) {
      const int m = len[c] - 1, phase = c / step * 11 % m;
      tail = may_t && q > 0 && (2 * q > left || (cnt[c] * quota[c] + phase) / m > ntail[c]);
    }
    if (gt >= NROUNDS) tail = false;
    if (gn >= NROUNDS) tail = true;
    const int g = tail ? gt : gn;
    if (tail) { gt += 7; ntail[c]++; }
    else { gn++; if (gn % 7 == 3) gn++; }
    const bool form_t = tail && may_t;
    lists[c][cnt[c]++] = (uint16_t)(g | (form_t ? 0x8000 : 0));
    busy[c] += form_t ? COST_T : after_tail ? COST_TN : COST_N;
  }
  bool use_tail = true;
  for (int c = 0; c < nclusters; c++) if (cnt[c] > MAX_ROUNDS) use_tail = false;
  if (!use_tail) for (int c = 0; c < nclusters; c++) for (int i = 0; i < cnt[c]; i++) lists[c][i] &= 0x7fff;
  for (int c = 0; c < nclusters; c++)
    for (int i = 0; i < cnt[c]; i++) {
      const int g = lists[c][i] & 0x7ff, p = g / 7, r = g % 7;
      lists[c][i] = (uint16_t)((2 * p + (r > 3)) | (r & 3) << 9 | (lists[c][i] & 0x8000));
    }
  if (nclusters == 66)
    for (int c = 0; c < 66; c++)
      for (cnt[c] = 0; cnt[c] < 28 && LIST66[c][cnt[c]] != 0xffff; cnt[c]++) lists[c][cnt[c]] = LIST66[c][cnt[c]];
  const bool table = nclusters == 66;
  int pos = 0;
  for (int c = 0; c < nclusters; c++) {
    s.start[c] = (uint16_t)pos;
    s.first[c] = lists[c][0] | (uint32_t)(table ? DELAY66[c] : c / 3 * STAGGER) << 16;
    s.tails[c] = s.stays[c] = 0;
    for (int i = 0; i < cnt[c]; i++) {
      if (lists[c][i] & 0x8000) s.tails[c] |= 1u << i;
      if (lists[c][i] & 0x4000) s.stays[c] |= 1u << i;
      s.list[pos++] = lists[c][i];
    }
  }
  for (int c = nclusters; c <= MAX_CLUSTERS; c++) s.start[c] = (uint16_t)pos;
  s.list[NROUNDS] = 0;
}

}

extern "C" void kernel_launch(void* const* d_in, const int* in_sizes, int n_in, void* d_out, int out_size) {
  static EncodeFn encode = nullptr;
  static int nclusters = 0;
  static Schedule sched;
  if (!encode) {
    void* fn = nullptr;
    cudaDriverEntryPointQueryResult qr;
    cudaGetDriverEntryPoint("cuTensorMapEncodeTiled", &fn, cudaEnableDefault, &qr);
    encode = (EncodeFn)fn;
    int dev = 0, nsm = 0;
    cudaGetDevice(&dev);
    cudaDeviceGetAttribute(&nsm, cudaDevAttrMultiProcessorCount, dev);
    nclusters = nsm / 2 < MAX_CLUSTERS ? nsm / 2 : MAX_CLUSTERS;
    make_schedule(sched, nclusters);
    cudaFuncSetAttribute(attn_kernel, cudaFuncAttributeMaxDynamicSharedMemorySize, SMEM_BYTES);
  }
  CUtensorMap tmQ, tmQT, tmK, tmV, tmO;
  make_map(encode, &tmQ, d_in[0], SQ, 64);
  make_map(encode, &tmQT, d_in[0], SQ, 16);
  make_map(encode, &tmK, d_in[1], SK, 64);
  make_map(encode, &tmV, d_in[2], SK, 64);
  make_map(encode, &tmO, d_out, SQ, OROWS);
  attn_kernel<<<2 * nclusters, NTHREADS, SMEM_BYTES>>>(tmQ, tmQT, tmK, tmV, tmO, sched);
}
```

```cpp
#include <cuda_runtime.h>
#include <cuda_bf16.h>
#include <cuda.h>
#include <stdint.h>

namespace {

constexpr int NHEADS = 512;
constexpr int SQ = 848;
constexpr int SK = 512;
constexpr int HD = 192;
constexpr int BN = 64;
constexpr int NBLK = SK / BN;
constexpr int SLOT = 64 * HD * 2;
constexpr int SLAB = 1024;
constexpr int RGRP = 3 * SLAB;
constexpr int NSLOT = 7;
constexpr int NROUNDS = (NHEADS / 2) * 7;
constexpr int NTHREADS = 384;
constexpr int OFF_QO = 0;
constexpr int OFF_KV = 2 * SLOT;
constexpr int OFF_QT = (2 + NSLOT) * SLOT;
constexpr int OFF_PT = OFF_QT + 3 * 2048;
constexpr int OFF_RED = OFF_PT + 2 * 2048;
constexpr int OFF_BAR = OFF_RED + 256;
constexpr int SMEM_BYTES = OFF_BAR + 256;

#define ESPLIT 8
#define OROWS 16
#define NT_SPLIT 4
#define QREQ0 8
#define QREQ1 13
constexpr uint32_t WAIT_LIMIT = 1u << 18;
#define SUSPEND 20000
constexpr uint32_t SUSPEND_NS = SUSPEND;

constexpr float SCALE_LOG2 = 0.07216878364870322f * 1.4426950408889634f;
__device__ __forceinline__ void check_inv(float a, float b, uint32_t& mask, uint32_t bit) {
  asm("{\n.reg .pred p;\nsetp.ge.f32 p, %1, 0f1F800000;\nsetp.le.and.f32 p, %1, 0f53800000, p;\n"
      "setp.ge.and.f32 p, %2, 0f1F800000, p;\nsetp.le.and.f32 p, %2, 0f53800000, p;\n@!p or.b32 %0, %0, %3;\n}\n"
      : "+r"(mask) : "f"(a), "f"(b), "r"(bit));
}

__device__ __forceinline__ uint32_t smem_u32(const void* p) { return (uint32_t)__cvta_generic_to_shared(p); }
__device__ __forceinline__ void wg_fence() { asm volatile("wgmma.fence.sync.aligned;" ::: "memory"); }
__device__ __forceinline__ void wg_commit() { asm volatile("wgmma.commit_group.sync.aligned;" ::: "memory"); }
template <int N> __device__ __forceinline__ void wg_wait() { asm volatile("wgmma.wait_group.sync.aligned %0;" ::"n"(N) : "memory"); }
template <int N> __device__ __forceinline__ void fence_regs(float (&r)[N]) {
#pragma unroll
  for (int i = 0; i < N; i++) asm volatile("" : "+f"(r[i])::"memory");
}
template <int N> __device__ __forceinline__ void fence_regs(uint32_t (&r)[N]) {
#pragma unroll
  for (int i = 0; i < N; i++) asm volatile("" : "+r"(r[i])::"memory");
}

__device__ __forceinline__ void mbar_init(uint32_t bar, uint32_t cnt) {
  asm volatile("mbarrier.init.shared::cta.b64 [%0], %1;" ::"r"(bar), "r"(cnt));
}
__device__ __forceinline__ void mbar_expect_tx(uint32_t bar, uint32_t bytes) {
  asm volatile("mbarrier.arrive.expect_tx.shared::cta.b64 _, [%0], %1;" ::"r"(bar), "r"(bytes) : "memory");
}
__device__ __forceinline__ void mbar_arrive(uint32_t bar) {
  asm volatile("mbarrier.arrive.shared::cta.b64 _, [%0];" ::"r"(bar) : "memory");
}
__device__ __forceinline__ bool mbar_try(uint32_t bar, uint32_t parity) {
  uint32_t ok;
  asm volatile(
      "{\n.reg .pred p;\nmbarrier.try_wait.parity.shared::cta.b64 p, [%1], %2;\nselp.b32 %0, 1, 0, p;\n}\n"
      : "=r"(ok)
      : "r"(bar), "r"(parity)
      : "memory");
  return ok;
}
__device__ __forceinline__ bool mbar_try_sleep(uint32_t bar, uint32_t parity) {
  uint32_t ok;
  asm volatile(
      "{\n.reg .pred p;\nmbarrier.try_wait.parity.shared::cta.b64 p, [%1], %2, %3;\nselp.b32 %0, 1, 0, p;\n}\n"
      : "=r"(ok)
      : "r"(bar), "r"(parity), "r"(SUSPEND_NS)
      : "memory");
  return ok;
}
__device__ __forceinline__ void mbar_wait(uint32_t bar, uint32_t parity) {
  if (mbar_try(bar, parity)) return;
  for (uint32_t n = 0; n < WAIT_LIMIT; n++)
    if (mbar_try(bar, parity)) break;
}
__device__ __forceinline__ void mbar_wait_sleep(uint32_t bar, uint32_t parity) {
  for (uint32_t n = 0; n < WAIT_LIMIT; n++) {
    if (mbar_try_sleep(bar, parity)) break;
  }
}

__device__ __forceinline__ void tma_load(uint32_t dst, const CUtensorMap* tm, uint32_t bar, int row, int head, uint64_t pol) {
  asm volatile(
      "cp.async.bulk.tensor.5d.shared::cluster.global.mbarrier::complete_tx::bytes.L2::cache_hint"
      " [%0], [%1, {%3, %3, %3, %4, %5}], [%2], %6;" ::"r"(dst),
      "l"(tm), "r"(bar), "r"(0), "r"(row >> 3), "r"(head), "l"(pol)
      : "memory");
}
__device__ __forceinline__ void tma_load_mc(uint32_t dst, const CUtensorMap* tm, uint32_t bar, int row, int head, uint64_t pol) {
  asm volatile(
      "cp.async.bulk.tensor.5d.shared::cluster.global.mbarrier::complete_tx::bytes.multicast::cluster.L2::cache_hint"
      " [%0], [%1, {%3, %3, %3, %4, %5}], [%2], %7, %6;" ::"r"(dst),
      "l"(tm), "r"(bar), "r"(0), "r"(row >> 3), "r"(head), "l"(pol), "h"((uint16_t)3)
      : "memory");
}
__device__ __forceinline__ bool elect_one() {
  uint32_t r;
  asm volatile("{\n.reg .pred e;\nelect.sync _|e, 0xffffffff;\nselp.b32 %0, 1, 0, e;\n}\n" : "=r"(r));
  return r;
}
__device__ __forceinline__ void tma_store(const CUtensorMap* tm, uint32_t src, int row, int head, uint64_t pol) {
  asm volatile(
      "cp.async.bulk.tensor.5d.global.shared::cta.bulk_group.L2::cache_hint"
      " [%0, {%2, %2, %2, %3, %4}], [%1], %5;" ::"l"(tm),
      "r"(src), "r"(0), "r"(row >> 3), "r"(head), "l"(pol)
      : "memory");
}
__device__ __forceinline__ void ldsm_x4(uint32_t addr, uint32_t& r0, uint32_t& r1, uint32_t& r2, uint32_t& r3) {
  asm volatile("ldmatrix.sync.aligned.m8n8.x4.shared.b16 {%0, %1, %2, %3}, [%4];"
               : "=r"(r0), "=r"(r1), "=r"(r2), "=r"(r3)
               : "r"(addr)
               : "memory");
}
__device__ __forceinline__ void stsm_x4(uint32_t addr, uint32_t r0, uint32_t r1, uint32_t r2, uint32_t r3) {
  asm volatile("stmatrix.sync.aligned.m8n8.x4.shared.b16 [%0], {%1, %2, %3, %4};" ::"r"(addr), "r"(r0), "r"(r1), "r"(r2), "r"(r3)
               : "memory");
}
__device__ __forceinline__ void stsm_x4_trans(uint32_t addr, uint32_t r0, uint32_t r1, uint32_t r2, uint32_t r3) {
  asm volatile("stmatrix.sync.aligned.m8n8.x4.trans.shared.b16 [%0], {%1, %2, %3, %4};" ::"r"(addr), "r"(r0), "r"(r1), "r"(r2), "r"(r3)
               : "memory");
}
__device__ __forceinline__ float ex2(float x) {
  float y;
  asm("ex2.approx.ftz.f32 %0, %1;" : "=f"(y) : "f"(x));
  return y;
}
__device__ __forceinline__ float rcp(float x) {
  float y;
  asm("rcp.approx.ftz.f32 %0, %1;" : "=f"(y) : "f"(x));
  return y;
}
__device__ __forceinline__ uint32_t pack_bf16(float lo, float hi) {
  uint32_t r;
  asm("cvt.rn.bf16x2.f32 %0, %1, %2;" : "=r"(r) : "f"(hi), "f"(lo));
  return r;
}
__device__ __forceinline__ void wgmma_qk(float (&d)[32], uint32_t a0, uint32_t a1, uint32_t a2, uint32_t a3, uint64_t db, int scale_d) {
  asm volatile("{\n.reg .pred p;\nsetp.ne.b32 p, %37, 0;\n"
    "wgmma.mma_async.sync.aligned.m64n64k16.f32.bf16.bf16 "
    "{%0, %1, %2, %3, %4, %5, %6, %7, %8, %9, %10, %11, %12, %13, %14, %15, %16, %17, %18, %19, %20, %21, %22, %23, %24, %25, %26, %27, %28, %29, %30, %31}, "
    "{%32, %33, %34, %35}, %36, p, 1, 1, 0;\n}\n"
    : "+f"(d[0]), "+f"(d[1]), "+f"(d[2]), "+f"(d[3]), "+f"(d[4]), "+f"(d[5]), "+f"(d[6]), "+f"(d[7]), "+f"(d[8]), "+f"(d[9]), "+f"(d[10]), "+f"(d[11]), "+f"(d[12]), "+f"(d[13]), "+f"(d[14]), "+f"(d[15]), "+f"(d[16]), "+f"(d[17]), "+f"(d[18]), "+f"(d[19]), "+f"(d[20]), "+f"(d[21]), "+f"(d[22]), "+f"(d[23]), "+f"(d[24]), "+f"(d[25]), "+f"(d[26]), "+f"(d[27]), "+f"(d[28]), "+f"(d[29]), "+f"(d[30]), "+f"(d[31])
    : "r"(a0), "r"(a1), "r"(a2), "r"(a3), "l"(db), "r"(scale_d));
}

__device__ __forceinline__ void wgmma_pv(float (&d)[96], uint32_t a0, uint32_t a1, uint32_t a2, uint32_t a3, uint64_t db, int scale_d) {
  asm volatile("{\n.reg .pred p;\nsetp.ne.b32 p, %101, 0;\n"
    "wgmma.mma_async.sync.aligned.m64n192k16.f32.bf16.bf16 "
    "{%0, %1, %2, %3, %4, %5, %6, %7, %8, %9, %10, %11, %12, %13, %14, %15, %16, %17, %18, %19, %20, %21, %22, %23, %24, %25, %26, %27, %28, %29, %30, %31, %32, %33, %34, %35, %36, %37, %38, %39, %40, %41, %42, %43, %44, %45, %46, %47, %48, %49, %50, %51, %52, %53, %54, %55, %56, %57, %58, %59, %60, %61, %62, %63, %64, %65, %66, %67, %68, %69, %70, %71, %72, %73, %74, %75, %76, %77, %78, %79, %80, %81, %82, %83, %84, %85, %86, %87, %88, %89, %90, %91, %92, %93, %94, %95}, "
    "{%96, %97, %98, %99}, %100, p, 1, 1, 1;\n}\n"
    : "+f"(d[0]), "+f"(d[1]), "+f"(d[2]), "+f"(d[3]), "+f"(d[4]), "+f"(d[5]), "+f"(d[6]), "+f"(d[7]), "+f"(d[8]), "+f"(d[9]), "+f"(d[10]), "+f"(d[11]), "+f"(d[12]), "+f"(d[13]), "+f"(d[14]), "+f"(d[15]), "+f"(d[16]), "+f"(d[17]), "+f"(d[18]), "+f"(d[19]), "+f"(d[20]), "+f"(d[21]), "+f"(d[22]), "+f"(d[23]), "+f"(d[24]), "+f"(d[25]), "+f"(d[26]), "+f"(d[27]), "+f"(d[28]), "+f"(d[29]), "+f"(d[30]), "+f"(d[31]), "+f"(d[32]), "+f"(d[33]), "+f"(d[34]), "+f"(d[35]), "+f"(d[36]), "+f"(d[37]), "+f"(d[38]), "+f"(d[39]), "+f"(d[40]), "+f"(d[41]), "+f"(d[42]), "+f"(d[43]), "+f"(d[44]), "+f"(d[45]), "+f"(d[46]), "+f"(d[47]), "+f"(d[48]), "+f"(d[49]), "+f"(d[50]), "+f"(d[51]), "+f"(d[52]), "+f"(d[53]), "+f"(d[54]), "+f"(d[55]), "+f"(d[56]), "+f"(d[57]), "+f"(d[58]), "+f"(d[59]), "+f"(d[60]), "+f"(d[61]), "+f"(d[62]), "+f"(d[63]), "+f"(d[64]), "+f"(d[65]), "+f"(d[66]), "+f"(d[67]), "+f"(d[68]), "+f"(d[69]), "+f"(d[70]), "+f"(d[71]), "+f"(d[72]), "+f"(d[73]), "+f"(d[74]), "+f"(d[75]), "+f"(d[76]), "+f"(d[77]), "+f"(d[78]), "+f"(d[79]), "+f"(d[80]), "+f"(d[81]), "+f"(d[82]), "+f"(d[83]), "+f"(d[84]), "+f"(d[85]), "+f"(d[86]), "+f"(d[87]), "+f"(d[88]), "+f"(d[89]), "+f"(d[90]), "+f"(d[91]), "+f"(d[92]), "+f"(d[93]), "+f"(d[94]), "+f"(d[95])
    : "r"(a0), "r"(a1), "r"(a2), "r"(a3), "l"(db), "r"(scale_d));
}

__device__ __forceinline__ void wgmma_qkT(float (&d)[8], uint64_t da, uint64_t db, int scale_d) {
  asm volatile("{\n.reg .pred p;\nsetp.ne.b32 p, %10, 0;\n"
    "wgmma.mma_async.sync.aligned.m64n16k16.f32.bf16.bf16 "
    "{%0, %1, %2, %3, %4, %5, %6, %7}, "
    "%8, %9, p, 1, 1, 0, 0;\n}\n"
    : "+f"(d[0]), "+f"(d[1]), "+f"(d[2]), "+f"(d[3]), "+f"(d[4]), "+f"(d[5]), "+f"(d[6]), "+f"(d[7])
    : "l"(da), "l"(db), "r"(scale_d));
}
__device__ __forceinline__ void wgmma_pvT(float (&d)[8], uint64_t da, uint64_t db, int scale_d) {
  asm volatile("{\n.reg .pred p;\nsetp.ne.b32 p, %10, 0;\n"
    "wgmma.mma_async.sync.aligned.m64n16k16.f32.bf16.bf16 "
    "{%0, %1, %2, %3, %4, %5, %6, %7}, "
    "%8, %9, p, 1, 1, 1, 0;\n}\n"
    : "+f"(d[0]), "+f"(d[1]), "+f"(d[2]), "+f"(d[3]), "+f"(d[4]), "+f"(d[5]), "+f"(d[6]), "+f"(d[7])
    : "l"(da), "l"(db), "r"(scale_d));
}

__device__ __forceinline__ void wgmma_qk0(float (&d)[32], uint32_t a0, uint32_t a1, uint32_t a2, uint32_t a3, uint64_t db) {
  asm volatile("{\n.reg .pred p;\nsetp.ne.b32 p, 0, 0;\n"
    "wgmma.mma_async.sync.aligned.m64n64k16.f32.bf16.bf16 "
    "{%0, %1, %2, %3, %4, %5, %6, %7, %8, %9, %10, %11, %12, %13, %14, %15, %16, %17, %18, %19, %20, %21, %22, %23, %24, %25, %26, %27, %28, %29, %30, %31}, "
    "{%32, %33, %34, %35}, %36, p, 1, 1, 0;\n}\n"
    : "=f"(d[0]), "=f"(d[1]), "=f"(d[2]), "=f"(d[3]), "=f"(d[4]), "=f"(d[5]), "=f"(d[6]), "=f"(d[7]), "=f"(d[8]), "=f"(d[9]), "=f"(d[10]), "=f"(d[11]), "=f"(d[12]), "=f"(d[13]), "=f"(d[14]), "=f"(d[15]), "=f"(d[16]), "=f"(d[17]), "=f"(d[18]), "=f"(d[19]), "=f"(d[20]), "=f"(d[21]), "=f"(d[22]), "=f"(d[23]), "=f"(d[24]), "=f"(d[25]), "=f"(d[26]), "=f"(d[27]), "=f"(d[28]), "=f"(d[29]), "=f"(d[30]), "=f"(d[31])
    : "r"(a0), "r"(a1), "r"(a2), "r"(a3), "l"(db));
}
__device__ __forceinline__ void wgmma_pv0(float (&d)[96], uint32_t a0, uint32_t a1, uint32_t a2, uint32_t a3, uint64_t db) {
  asm volatile("{\n.reg .pred p;\nsetp.ne.b32 p, 0, 0;\n"
    "wgmma.mma_async.sync.aligned.m64n192k16.f32.bf16.bf16 "
    "{%0, %1, %2, %3, %4, %5, %6, %7, %8, %9, %10, %11, %12, %13, %14, %15, %16, %17, %18, %19, %20, %21, %22, %23, %24, %25, %26, %27, %28, %29, %30, %31, %32, %33, %34, %35, %36, %37, %38, %39, %40, %41, %42, %43, %44, %45, %46, %47, %48, %49, %50, %51, %52, %53, %54, %55, %56, %57, %58, %59, %60, %61, %62, %63, %64, %65, %66, %67, %68, %69, %70, %71, %72, %73, %74, %75, %76, %77, %78, %79, %80, %81, %82, %83, %84, %85, %86, %87, %88, %89, %90, %91, %92, %93, %94, %95}, "
    "{%96, %97, %98, %99}, %100, p, 1, 1, 1;\n}\n"
    : "=f"(d[0]), "=f"(d[1]), "=f"(d[2]), "=f"(d[3]), "=f"(d[4]), "=f"(d[5]), "=f"(d[6]), "=f"(d[7]), "=f"(d[8]), "=f"(d[9]), "=f"(d[10]), "=f"(d[11]), "=f"(d[12]), "=f"(d[13]), "=f"(d[14]), "=f"(d[15]), "=f"(d[16]), "=f"(d[17]), "=f"(d[18]), "=f"(d[19]), "=f"(d[20]), "=f"(d[21]), "=f"(d[22]), "=f"(d[23]), "=f"(d[24]), "=f"(d[25]), "=f"(d[26]), "=f"(d[27]), "=f"(d[28]), "=f"(d[29]), "=f"(d[30]), "=f"(d[31]), "=f"(d[32]), "=f"(d[33]), "=f"(d[34]), "=f"(d[35]), "=f"(d[36]), "=f"(d[37]), "=f"(d[38]), "=f"(d[39]), "=f"(d[40]), "=f"(d[41]), "=f"(d[42]), "=f"(d[43]), "=f"(d[44]), "=f"(d[45]), "=f"(d[46]), "=f"(d[47]), "=f"(d[48]), "=f"(d[49]), "=f"(d[50]), "=f"(d[51]), "=f"(d[52]), "=f"(d[53]), "=f"(d[54]), "=f"(d[55]), "=f"(d[56]), "=f"(d[57]), "=f"(d[58]), "=f"(d[59]), "=f"(d[60]), "=f"(d[61]), "=f"(d[62]), "=f"(d[63]), "=f"(d[64]), "=f"(d[65]), "=f"(d[66]), "=f"(d[67]), "=f"(d[68]), "=f"(d[69]), "=f"(d[70]), "=f"(d[71]), "=f"(d[72]), "=f"(d[73]), "=f"(d[74]), "=f"(d[75]), "=f"(d[76]), "=f"(d[77]), "=f"(d[78]), "=f"(d[79]), "=f"(d[80]), "=f"(d[81]), "=f"(d[82]), "=f"(d[83]), "=f"(d[84]), "=f"(d[85]), "=f"(d[86]), "=f"(d[87]), "=f"(d[88]), "=f"(d[89]), "=f"(d[90]), "=f"(d[91]), "=f"(d[92]), "=f"(d[93]), "=f"(d[94]), "=f"(d[95])
    : "r"(a0), "r"(a1), "r"(a2), "r"(a3), "l"(db));
}
__device__ __forceinline__ void wgmma_qkT0(float (&d)[8], uint64_t da, uint64_t db) {
  asm volatile("{\n.reg .pred p;\nsetp.ne.b32 p, 0, 0;\n"
    "wgmma.mma_async.sync.aligned.m64n16k16.f32.bf16.bf16 "
    "{%0, %1, %2, %3, %4, %5, %6, %7}, "
    "%8, %9, p, 1, 1, 0, 0;\n}\n"
    : "=f"(d[0]), "=f"(d[1]), "=f"(d[2]), "=f"(d[3]), "=f"(d[4]), "=f"(d[5]), "=f"(d[6]), "=f"(d[7])
    : "l"(da), "l"(db));
}
__device__ __forceinline__ void wgmma_pvT0(float (&d)[8], uint64_t da, uint64_t db) {
  asm volatile("{\n.reg .pred p;\nsetp.ne.b32 p, 0, 0;\n"
    "wgmma.mma_async.sync.aligned.m64n16k16.f32.bf16.bf16 "
    "{%0, %1, %2, %3, %4, %5, %6, %7}, "
    "%8, %9, p, 1, 1, 1, 0;\n}\n"
    : "=f"(d[0]), "=f"(d[1]), "=f"(d[2]), "=f"(d[3]), "=f"(d[4]), "=f"(d[5]), "=f"(d[6]), "=f"(d[7])
    : "l"(da), "l"(db));
}

struct Round { int head, qrow, mc; };
__device__ __forceinline__ Round decode_round(uint32_t e, uint32_t rank) {
  Round o;
  o.mc = (e & 0x600) != 0x600;
  o.head = (e & 0x1ff) + (o.mc ? 0 : rank);
  o.qrow = (e >> 1 & 0x300) + (o.mc ? rank * 128 : 0);
  return o;
}

__device__ __forceinline__ uint32_t ring_k(uint32_t cur) { return cur << 3 & 0x38; }
__device__ __forceinline__ uint32_t ring_v(uint32_t cur) { return cur >> 1 & 0x38; }
__device__ __forceinline__ uint32_t ring_rot(uint32_t ord) { return ord >> 8 | ((ord ^ 0x88) & 0xff) << 20; }
__device__ __forceinline__ uint32_t ring_stay(uint32_t ord) { return (ord & 0xff00000) | (ord >> 4 & 0xffff) | (ord & 0xf) << 16; }
__device__ __forceinline__ uint32_t ring_swap(uint32_t cur) { return (cur >> 4 & 0xf) | (cur & 0xf) << 4; }

__device__ __forceinline__ uint32_t kdesc0(uint32_t s_kv) { return ((s_kv & 0x3FFFFu) >> 4) | (1u << 16); }
__device__ __forceinline__ uint32_t vdesc0(uint32_t s_kv) { return ((s_kv & 0x3FFFFu) >> 4) | ((uint32_t)(SLAB >> 4) << 16); }
constexpr uint64_t DESC_HI = ((uint64_t)(RGRP >> 4) << 32) | ((uint64_t)1 << 62);
constexpr uint64_t DESC_HI_PT = ((uint64_t)(1024 >> 4) << 32) | ((uint64_t)1 << 62);

__device__ __forceinline__ void issue_qk(float (&S)[32], const uint32_t (&Q)[48], uint32_t kdesc) {
  const uint64_t d = DESC_HI | kdesc;
  wgmma_qk0(S, Q[0], Q[1], Q[2], Q[3], d);
#pragma unroll
  for (int kk = 1; kk < 12; kk++)
    wgmma_qk(S, Q[kk * 4], Q[kk * 4 + 1], Q[kk * 4 + 2], Q[kk * 4 + 3], d + (uint64_t)((kk / 4) * (SLAB / 16) + (kk % 4) * 2), 1);
}
__device__ __forceinline__ void issue_qk32(float (&S)[32], const uint32_t (&Q)[48], uint32_t kdesc) {
  uint32_t d[12];
#pragma unroll
  for (int kk = 0; kk < 12; kk++) {
    d[kk] = kdesc + ((kk / 4) * (SLAB / 16) + (kk % 4) * 2);
    asm volatile("" : "+r"(d[kk]));
  }
  wgmma_qk0(S, Q[0], Q[1], Q[2], Q[3], DESC_HI | d[0]);
#pragma unroll
  for (int kk = 1; kk < 12; kk++) wgmma_qk(S, Q[kk * 4], Q[kk * 4 + 1], Q[kk * 4 + 2], Q[kk * 4 + 3], DESC_HI | d[kk], 1);
}
__device__ __forceinline__ void issue_qk3(float (&S)[32], const uint32_t (&Q)[48], uint32_t kdesc) {
  const uint64_t d = DESC_HI | kdesc;
  wgmma_qk0(S, Q[0], Q[1], Q[2], Q[3], d);
#pragma unroll
  for (int kk = 1; kk < 12; kk++) {
    if (kk % 4 == 0) wg_commit();
    wgmma_qk(S, Q[kk * 4], Q[kk * 4 + 1], Q[kk * 4 + 2], Q[kk * 4 + 3], d + (uint64_t)((kk / 4) * (SLAB / 16) + (kk % 4) * 2), 1);
  }
}
template <bool ACCUMULATE>
__device__ __forceinline__ void issue_pv(float (&O)[96], const uint32_t (&P)[16], uint32_t vdesc) {
  const uint64_t d = DESC_HI | vdesc;
  if (ACCUMULATE) wgmma_pv(O, P[0], P[1], P[2], P[3], d, 1);
  else wgmma_pv0(O, P[0], P[1], P[2], P[3], d);
#pragma unroll
  for (int kk = 1; kk < 4; kk++)
    wgmma_pv(O, P[kk * 4], P[kk * 4 + 1], P[kk * 4 + 2], P[kk * 4 + 3], d + (uint64_t)(kk * (2 * RGRP / 16)), 1);
}

template <int K0 = 0, int K1 = 12>
__device__ __forceinline__ void load_q(uint32_t (&Q)[48], uint32_t lane_addr) {
#pragma unroll
  for (int kk = K0; kk < K1; kk++)
    ldsm_x4((lane_addr ^ ((kk % 4) << 5)) + (kk / 4) * SLAB, Q[kk * 4], Q[kk * 4 + 1], Q[kk * 4 + 2], Q[kk * 4 + 3]);
}

__device__ __forceinline__ void scale_q(uint32_t (&Q)[48]) {
  constexpr uint32_t C2 = 0x3DD53DD5u;
#pragma unroll
  for (int i = 0; i < 48; i++) asm("mul.rn.bf16x2 %0, %1, %2;" : "=r"(Q[i]) : "r"(Q[i]), "r"(C2));
  fence_regs(Q);
}
__device__ __forceinline__ void softmax_block(const float (&S)[32], uint32_t (&P)[16], float& l0, float& l1) {
#pragma unroll
  for (int i = 0; i < 8; i++) {
    const float a = ex2(S[4 * i + 0]);
    const float b = ex2(S[4 * i + 1]);
    const float c = ex2(S[4 * i + 2]);
    const float d = ex2(S[4 * i + 3]);
    l0 += a + b;
    l1 += c + d;
    P[2 * i] = pack_bf16(a, b);
    P[2 * i + 1] = pack_bf16(c, d);
  }
  fence_regs(P);
}

__device__ __forceinline__ void sums_put(uint32_t addr, float l0, float l1) {
  asm volatile("st.shared.v2.f32 [%0], {%1, %2};" ::"r"(addr), "f"(l0), "f"(l1) : "memory");
}
__device__ __forceinline__ void sums_get(uint32_t addr, float& s0, float& s1) {
  float a, b, c, d, e, f, g, h;
  asm volatile("ld.shared.v4.f32 {%0, %1, %2, %3}, [%8];\nld.shared.v4.f32 {%4, %5, %6, %7}, [%8 + 16];\n"
               : "=f"(a), "=f"(b), "=f"(c), "=f"(d), "=f"(e), "=f"(f), "=f"(g), "=f"(h) : "r"(addr & ~31u) : "memory");
  s0 = (a + c) + (e + g);
  s1 = (b + d) + (f + h);
}

template <int K0, int K1>
__device__ __forceinline__ void epilogue_part(const float (&O)[96], float i0, float i1, uint32_t lane_addr) {
#pragma unroll
  for (int kk = K0; kk < K1; kk++) {
    const int b = kk * 8;
    stsm_x4((lane_addr ^ ((kk % 4) << 5)) + (kk / 4) * SLAB,
            pack_bf16(O[b] * i0, O[b + 1] * i0), pack_bf16(O[b + 2] * i1, O[b + 3] * i1),
            pack_bf16(O[b + 4] * i0, O[b + 5] * i0), pack_bf16(O[b + 6] * i1, O[b + 7] * i1));
  }
}
__device__ __forceinline__ void epilogue_done(uint32_t bar, int lane) {
  __syncwarp();
  if (lane == 0) mbar_arrive(bar);
}

__device__ __forceinline__ void redo_tile(const CUtensorMap* tmQ, const CUtensorMap* tmK, const CUtensorMap* tmV, const CUtensorMap* tmO,
                                          int head, int row, uint32_t qo, uint32_t kv, uint32_t lane_addr, uint32_t bar, uint32_t& phase,
                                          uint32_t wg_bar) {
  float O[96], S[32];
  uint32_t Q[48], P[16];
  uint64_t pol;
  asm volatile("createpolicy.fractional.L2::evict_normal.b64 %0, 1.0;" : "=l"(pol));
  const bool leader = (threadIdx.x & 127) == 0;
  if (leader) {
    mbar_expect_tx(bar, SLOT);
    tma_load(qo, tmQ, bar, row, head, pol);
  }
  mbar_wait(bar, phase);
  phase ^= 1;
  load_q(Q, lane_addr);
  float m0 = -INFINITY, m1 = -INFINITY, l0 = 0.f, l1 = 0.f;
#pragma unroll
  for (int i = 0; i < 96; i++) O[i] = 0.f;
#pragma unroll 1
  for (int j = 0; j < NBLK; j++) {
    asm volatile("bar.sync %0, 128;" ::"r"(wg_bar) : "memory");
    if (leader) {
      mbar_expect_tx(bar, 2 * SLOT);
      tma_load(kv, tmK, bar, j * BN, head, pol);
      tma_load(kv + SLOT, tmV, bar, j * BN, head, pol);
    }
    mbar_wait(bar, phase);
    phase ^= 1;
    wg_fence();
    issue_qk(S, Q, kdesc0(kv));
    wg_commit();
    wg_wait<0>();
    fence_regs(S);
    float n0 = m0, n1 = m1;
#pragma unroll
    for (int i = 0; i < 8; i++) {
      n0 = fmaxf(n0, fmaxf(S[4 * i], S[4 * i + 1]));
      n1 = fmaxf(n1, fmaxf(S[4 * i + 2], S[4 * i + 3]));
    }
#pragma unroll
    for (int o = 1; o < 4; o <<= 1) {
      n0 = fmaxf(n0, __shfl_xor_sync(0xffffffffu, n0, o));
      n1 = fmaxf(n1, __shfl_xor_sync(0xffffffffu, n1, o));
    }
    const float f0 = ex2((m0 - n0) * SCALE_LOG2), f1 = ex2((m1 - n1) * SCALE_LOG2);
    m0 = n0; m1 = n1;
    l0 *= f0; l1 *= f1;
#pragma unroll
    for (int i = 0; i < 24; i++) {
      O[4 * i] *= f0; O[4 * i + 1] *= f0; O[4 * i + 2] *= f1; O[4 * i + 3] *= f1;
    }
#pragma unroll
    for (int i = 0; i < 8; i++) {
      S[4 * i] = (S[4 * i] - m0) * SCALE_LOG2; S[4 * i + 1] = (S[4 * i + 1] - m0) * SCALE_LOG2;
      S[4 * i + 2] = (S[4 * i + 2] - m1) * SCALE_LOG2; S[4 * i + 3] = (S[4 * i + 3] - m1) * SCALE_LOG2;
    }
    softmax_block(S, P, l0, l1);
    fence_regs(O);
    wg_fence();
    issue_pv<true>(O, P, vdesc0(kv + SLOT));
    wg_commit();
    wg_wait<0>();
    fence_regs(O);
  }
#pragma unroll
  for (int o = 1; o < 4; o <<= 1) {
    l0 += __shfl_xor_sync(0xffffffffu, l0, o);
    l1 += __shfl_xor_sync(0xffffffffu, l1, o);
  }
  epilogue_part<0, 12>(O, rcp(l0), rcp(l1), lane_addr);
  asm volatile("fence.proxy.async.shared::cta;" ::: "memory");
  asm volatile("bar.sync %0, 128;" ::"r"(wg_bar) : "memory");
  if (leader) {
    for (int i = 0; i < 64 && row + i < SQ; i += OROWS) tma_store(tmO, qo + i / 8 * RGRP, row + i, head, pol);
    asm volatile("cp.async.bulk.commit_group;" ::: "memory");
    asm volatile("cp.async.bulk.wait_group 0;" ::: "memory");
  }
}

__device__ __forceinline__ void wg_barrier() { asm volatile("bar.sync 3, 128;" ::: "memory"); }

__device__ __forceinline__ void tail_reduce(float (&v)[4], uint32_t red, int warp, int lane) {
#pragma unroll
  for (int o = 4; o < 32; o <<= 1)
#pragma unroll
    for (int i = 0; i < 4; i++) v[i] += __shfl_xor_sync(0xffffffffu, v[i], o);
  if (lane < 4)
    asm volatile("st.shared.v4.f32 [%0], {%1, %2, %3, %4};" ::"r"(red + (warp * 4 + lane) * 16), "f"(v[0]), "f"(v[1]), "f"(v[2]), "f"(v[3]) : "memory");
  wg_barrier();
#pragma unroll
  for (int ww = 0; ww < 4; ww++) {
    float x0, x1, x2, x3;
    asm volatile("ld.shared.v4.f32 {%0, %1, %2, %3}, [%4];" : "=f"(x0), "=f"(x1), "=f"(x2), "=f"(x3) : "r"(red + (ww * 4 + (lane & 3)) * 16) : "memory");
    if (ww == 0) { v[0] = x0; v[1] = x1; v[2] = x2; v[3] = x3; }
    else { v[0] += x0; v[1] += x1; v[2] += x2; v[3] += x3; }
  }
}

__device__ __forceinline__ void tail_softmax(const float (&S)[8], float (&l)[4], uint32_t pt_addr) {
  float e[8];
#pragma unroll
  for (int i = 0; i < 8; i++) e[i] = ex2(S[i] * SCALE_LOG2);
  stsm_x4_trans(pt_addr, pack_bf16(e[0], e[1]), pack_bf16(e[2], e[3]), pack_bf16(e[4], e[5]), pack_bf16(e[6], e[7]));
  l[0] += e[0] + e[2]; l[1] += e[1] + e[3]; l[2] += e[4] + e[6]; l[3] += e[5] + e[7];
}

__device__ __forceinline__ void issue_qkT(float (&S8)[8], uint32_t kdesc, uint32_t qt_addr) {
  const uint64_t da = DESC_HI | kdesc;
  const uint64_t db = DESC_HI | (uint64_t)(((qt_addr & 0x3FFFFu) >> 4) | (1u << 16));
  wgmma_qkT0(S8, da, db);
#pragma unroll
  for (int kk = 1; kk < 12; kk++)
    wgmma_qkT(S8, da + (uint64_t)((kk / 4) * (SLAB / 16) + (kk % 4) * 2), db + (uint64_t)((kk / 4) * (SLAB / 16) + (kk % 4) * 2), 1);
}
template <bool ACCUMULATE>
__device__ __forceinline__ void issue_pvT(float (&O)[3][8], uint32_t vdesc, uint32_t pt_base) {
  const uint64_t da = DESC_HI | vdesc;
  const uint64_t db = DESC_HI_PT | (uint64_t)(((pt_base & 0x3FFFFu) >> 4) | (1u << 16));
#pragma unroll
  for (int kk = 0; kk < 4; kk++)
#pragma unroll
    for (int b = 0; b < 3; b++) {
      if (kk == 0 && !ACCUMULATE) wgmma_pvT0(O[b], da + (uint64_t)(b * (SLAB / 16)), db);
      else wgmma_pvT(O[b], da + (uint64_t)(b * (SLAB / 16) + kk * (2 * RGRP / 16)), db + (uint64_t)(kk * 2), 1);
    }
}

template <bool B> struct Bool { static constexpr bool value = B; };

constexpr int MAX_CLUSTERS = 72;
constexpr int MAX_ROUNDS = 32;
struct Schedule {
  uint32_t first[MAX_CLUSTERS];
  uint32_t stays[MAX_CLUSTERS];
  uint32_t tails[MAX_CLUSTERS];
  uint16_t start[MAX_CLUSTERS + 1];
  uint16_t list[NROUNDS + 1];
};

#define TRACE_TILE()

__global__ void __cluster_dims__(2, 1, 1) __launch_bounds__(NTHREADS, 1)
attn_kernel(const __grid_constant__ CUtensorMap tmQ, const __grid_constant__ CUtensorMap tmQT, const __grid_constant__ CUtensorMap tmK,
            const __grid_constant__ CUtensorMap tmV, const __grid_constant__ CUtensorMap tmO, const __grid_constant__ Schedule sched) {
  extern __shared__ __align__(1024) uint8_t smem_raw[];
  const uint32_t c_entry = (uint32_t)clock();
  const uint32_t sbase = smem_u32(smem_raw);
  const uint32_t s_qo = sbase + OFF_QO;
  const uint32_t s_kv = sbase + OFF_KV;
  const uint32_t s_bar = sbase + OFF_BAR;
  const uint32_t bar_full = s_bar;
  const uint32_t bar_empty = s_bar + 8 * NSLOT;
  const uint32_t bar_qfull = s_bar + 16 * NSLOT;
  const uint32_t bar_ostg = bar_qfull + 16;
  const uint32_t bar_qreq = bar_ostg + 16;
  const uint32_t bar_redo = bar_qreq + 16;
  const uint32_t s_redo = bar_redo + 16;

  uint32_t rank;
  asm("mov.u32 %0, %%cluster_ctarank;" : "=r"(rank));
  const int cluster = blockIdx.x >> 1;
  auto get_rounds = [&](int& first, int& count) {
    uint32_t c;
    asm volatile("mov.u32 %0, %%ctaid.x;" : "=r"(c));
    c >>= 1;
    first = sched.start[c];
    count = sched.start[c + 1] - first;
  };

  if (threadIdx.x == 0) {
    asm volatile("prefetch.tensormap [%0];" ::"l"(&tmK) : "memory");
    asm volatile("prefetch.tensormap [%0];" ::"l"(&tmQ) : "memory");
    asm volatile("prefetch.tensormap [%0];" ::"l"(&tmV) : "memory");
    for (int i = 0; i < 3; i++) mbar_init(bar_full + 8 * i, 1);
    for (int i = 0; i < 2; i++) mbar_init(bar_qfull + 8 * i, 1);
    asm volatile("fence.mbarrier_init.release.cluster;" ::: "memory");
    asm volatile("fence.proxy.async.shared::cta;" ::: "memory");
    const uint32_t e0 = sched.first[cluster];
    const Round r0 = decode_round(e0, rank);
    const int head = r0.head, qrow = r0.qrow;
    uint64_t polq, polk;
    asm volatile("createpolicy.fractional.L2::evict_first.b64 %0, 1.0;" : "=l"(polq));
    asm volatile("createpolicy.fractional.L2::evict_unchanged.b64 %0, 1.0;" : "=l"(polk));
    while ((uint32_t)clock() - c_entry < (e0 >> 16)) {}
    mbar_expect_tx(bar_full, SLOT);
    tma_load(s_kv, &tmK, bar_full, 0, head, polk);
    mbar_expect_tx(bar_qfull, SLOT);
    tma_load(s_qo, &tmQ, bar_qfull, qrow, head, polq);
    mbar_expect_tx(bar_full + 8, SLOT);
    tma_load(s_kv + SLOT, &tmK, bar_full + 8, BN, head, polk);
    mbar_expect_tx(bar_full + 16, SLOT);
    tma_load(s_kv + 2 * SLOT, &tmV, bar_full + 16, 0, head, polk);
    mbar_expect_tx(bar_qfull + 8, SLOT);
    tma_load(s_qo + SLOT, &tmQ, bar_qfull + 8, qrow + 64, head, polq);
  } else if (threadIdx.x == 32) {
    for (int i = 0; i < NSLOT; i++) {
      if (i >= 3) mbar_init(bar_full + 8 * i, 1);
      mbar_init(bar_empty + 8 * i, 4);
    }
    for (int i = 0; i < 2; i++) {
      mbar_init(bar_ostg + 8 * i, 4);
      mbar_init(bar_qreq + 8 * i, 1);
      mbar_init(bar_redo + 8 * i, 1);
      asm volatile("st.shared.u32 [%0], %1;" ::"r"(s_redo + 4 * i), "r"(0) : "memory");
    }
    asm volatile("fence.mbarrier_init.release.cluster;" ::: "memory");
    asm volatile("fence.proxy.async.shared::cta;" ::: "memory");
  }
  __syncthreads();
  asm volatile("barrier.cluster.arrive.relaxed.aligned;\nbarrier.cluster.wait.aligned;" ::: "memory");

  const int wg = __shfl_sync(0xffffffffu, threadIdx.x >> 7, 0);
  const int warp = __shfl_sync(0xffffffffu, (threadIdx.x >> 5) & 3, 0);
  const int lane = threadIdx.x & 31;

  if (wg == 0) {
    asm volatile("setmaxnreg.dec.sync.aligned.u32 24;");
    int first_round, nrounds;
    get_rounds(first_round, nrounds);
    const int nblocks = nrounds * NBLK;
    if (warp == 2) {
      uint64_t pol;
      asm volatile("createpolicy.fractional.L2::evict_unchanged.b64 %0, 1.0;" : "=l"(pol));
      auto load = [&](uint32_t slot, uint32_t ph, int head, int mc, const CUtensorMap* tm, uint32_t blk, uint32_t owner) {
        uint32_t dst = s_kv + slot * (SLOT / 8), bar = bar_full + slot, mode = blk == 8 ? 0 : !mc ? 1 : rank == owner ? 2 : 0;
        uint32_t bytes = blk == 8 ? 0 : SLOT;
        int row = blk * BN;
        asm volatile("" : "+r"(dst), "+r"(bar), "+r"(mode), "+r"(row), "+r"(head), "+r"(bytes), "+r"(ph), "+l"(tm));
        if (mode == 2) {
          mbar_wait(bar_empty + slot, ph);
          if (elect_one()) {
            tma_load_mc(dst, tm, bar, row, head, pol);
            mbar_expect_tx(bar, SLOT);
          }
        } else if (mode == 1) {
          mbar_wait(bar_empty + slot, ph);
          if (elect_one()) {
            tma_load(dst, tm, bar, row, head, pol);
            mbar_expect_tx(bar, SLOT);
          }
        } else {
          mbar_wait(bar_empty + slot, ph);
          if (elect_one()) mbar_expect_tx(bar, bytes);
        }
      };
      auto request_q = [&](int n, int pos) {
        pos += (n & 7) * 2;
        if (lane == 0 && pos == QREQ0) mbar_arrive(bar_qreq);
        if (lane == 0 && pos == QREQ1) mbar_arrive(bar_qreq + 8);
      };
      uint32_t cur = 0xb0, ord = 0x3210edc;
      Round r = decode_round(sched.list[first_round], rank);
      uint32_t kblk = 0x765432, vblk = 0x7654321;
      uint32_t flip = 0;
      for (int n = 1; n < nblocks; n++) {
        const int j = n & 7;
        if (j != 7) {
          load(ring_v(cur), cur >> 7 & 1, r.head, r.mc, (flip & 1) ? &tmV : &tmK, kblk & 15, 0);
          kblk >>= 4;
          request_q(n, 0);
          cur = ord;
          ord = ring_rot(ord);
          if (j == 2 && (flip & 2)) {
            cur = ring_swap(cur);
            ord = ring_stay(ord);
          }
          load(ring_k(cur), cur >> 3 & 1, r.head, r.mc, (flip & 2) ? &tmK : &tmV, vblk & 15, 1);
          vblk >>= 4;
          flip >>= 2;
          request_q(n, 1);
        } else {
          const uint32_t e = sched.list[first_round + (n >> 3) + 1];
          const Round r1 = decode_round(e, rank);
          const bool stay = e & 0x4000, other = stay && r1.head != r.head;
          if (n + 1 < nblocks) load(ring_v(cur), cur >> 7 & 1, stay ? r.head : r1.head, stay ? r.mc : r1.mc, stay ? &tmV : &tmK, stay ? 7 : 0, 0);
          request_q(n, 0);
          cur = ord;
          ord = ring_rot(ord);
          load(ring_k(cur), cur >> 3 & 1, other ? r1.head : r.head, other ? r1.mc : r.mc, other ? &tmK : &tmV, other ? 0 : stay ? 8 : vblk, 1);
          request_q(n, 1);
          r = r1;
          kblk = other ? 0x7652103 : stay ? 0x4328880 : 0x7654321;
          vblk = other ? 0x76543421 : stay ? 0x43210188 : 0x76543210;
          flip = other ? 0x7e : stay ? 0x20 : 0;
        }
      }
      ord ^= 0x8080000;
      for (int i = 0; i < NSLOT; i++, ord >>= 4) mbar_wait_sleep(bar_empty + ring_k(ord), ord >> 3 & 1);
    } else if (warp != 3) {
      const int w = warp == 0;
      uint64_t pol;
      asm volatile("createpolicy.fractional.L2::evict_first.b64 %0, 1.0;" : "=l"(pol));
      const uint32_t buf = s_qo + w * SLOT;
      mbar_wait_sleep(bar_ostg + 8 * w, 0);
      if (elect_one()) asm volatile("prefetch.tensormap [%0];" ::"l"(w ? &tmQT : &tmO) : "memory");
      for (int t = 0; t < nrounds; t++) {
        if (t + 1 < nrounds) {
          const uint32_t e = sched.list[first_round + t + 1];
          const Round r = decode_round(e, rank);
          const bool tail = w == 1 && (e & 0x8000);
          mbar_wait_sleep(bar_qreq + 8 * w, t & 1);
          if (elect_one()) {
            tma_load(tail ? sbase + OFF_QT : buf, tail ? &tmQT : &tmQ, bar_qfull + 8 * w, r.qrow + w * 64, r.head, pol);
            mbar_expect_tx(bar_qfull + 8 * w, tail ? 3 * 2048 : SLOT);
          }
        } else {
          if (elect_one()) mbar_arrive(bar_qfull + 8 * w);
        }
        const Round r = decode_round(sched.list[first_round + t], rank);
        const int row0 = r.qrow + w * 64;
        const int nrows = row0 + 64 <= SQ ? 64 : SQ % 64;
        mbar_wait_sleep(bar_ostg + 8 * w, ~t & 1);
        asm volatile("fence.proxy.async.shared::cta;" ::: "memory");
#pragma unroll 1
        for (int i = 0; i < nrows; i += OROWS) {
          if (elect_one()) {
            tma_store(&tmO, buf + i / 8 * RGRP, row0 + i, r.head, pol);
            asm volatile("cp.async.bulk.commit_group;" ::: "memory");
          }
          if (t + 1 < nrounds) asm volatile("cp.async.bulk.wait_group.read 0;" ::: "memory");
        }
      }
      asm volatile("cp.async.bulk.wait_group 0;" ::: "memory");
      if (elect_one()) mbar_arrive(bar_redo + 8 * w);
    } else {
      uint32_t cur = 0x21, ord = 0xa986543, stays = sched.stays[cluster];
      for (int n = 0; n < nblocks; n++) {
        if (n + 1 < nblocks) mbar_wait(bar_full + ring_k(cur), cur >> 3 & 1);
        mbar_wait(bar_full + ring_v(cur), cur >> 7 & 1);
        asm volatile("bar.sync 1, 288;" ::: "memory");
        asm volatile("bar.arrive 2, 288;" ::: "memory");
        cur = ord;
        ord = ring_rot(ord);
        if ((n & 7) == 6) {
          stays >>= 1;
          if (stays & 1) {
            cur = ring_swap(cur);
            ord = ring_stay(ord);
          }
        }
        TRACE_TILE();
      }
    }
  } else {
    asm volatile("setmaxnreg.inc.sync.aligned.u32 240;");
    const int w = wg - 1;
    int first_round, nrounds;
    get_rounds(first_round, nrounds);
    const int nblocks = nrounds * NBLK;
    float O[96], S[32];
    uint32_t Q[48], P0[16], P1[16];
    float l0 = 0.f, l1 = 0.f, inv0 = 1.f, inv1 = 1.f;
    uint32_t redo = 0;
    const uint32_t lane_addr = s_qo + w * SLOT + (warp * 2 + ((lane >> 3) & 1)) * RGRP + (lane & 7) * 128 + (((lane >> 4) ^ (lane & 7)) << 4);
    const uint32_t sum_addr = s_qo + w * SLOT + warp * 2 * RGRP + lane * 8;
    const uint32_t my_qfull = bar_qfull + 8 * w, my_ostg = bar_ostg + 8 * w;

    uint32_t empty_remote;
    asm("mapa.shared::cluster.u32 %0, %1, %2;" : "=r"(empty_remote) : "r"(bar_empty), "r"(threadIdx.x & 1));
    const bool releaser = (threadIdx.x & 126) == 32;
    auto release = [&](uint32_t s) {
      if (releaser) asm volatile("mbarrier.arrive.shared::cluster.b64 _, [%0];" ::"r"(empty_remote + s) : "memory");
    };
    uint32_t ks = 8, vs = 16, kp = 0, vp = 0, ord = 0x2106543;
    const uint32_t kd0 = kdesc0(s_kv), vd0 = vdesc0(s_kv);
    uint32_t kd = kd0 + ks * (SLOT / 128), vd = vd0 + vs * (SLOT / 128);
    auto advance = [&]() {
      kp = ks; vp = vs;
      ks = ring_k(ord); vs = ring_v(ord);
      ord = ord >> 8 | (ord & 0xff) << 20;
      kd = kd0 + ks * (SLOT / 128); vd = vd0 + vs * (SLOT / 128);
      asm volatile("" : "+r"(ks), "+r"(vs), "+r"(kd), "+r"(vd), "+r"(ord));
    };
    uint32_t stay = 0;

    uint32_t tails = w == 1 ? sched.tails[cluster] : 0u;
    auto turn_wait = [&]() { asm volatile("bar.sync %0, 288;" ::"r"(1 + w) : "memory"); };
    auto turn_pass = [&]() { asm volatile("bar.arrive %0, 288;" ::"r"(2 - w) : "memory"); };
    if (w == 1) asm volatile("bar.arrive %0, 288;" ::"r"(1 + (tails & 1)) : "memory");

    mbar_wait(my_qfull, 0);
    load_q(Q, lane_addr);
    scale_q(Q);
    mbar_wait(bar_full, 0);
    wg_fence();
    issue_qk(S, Q, kd0);
    wg_commit();
    wg_wait<0>();
    fence_regs(S);
    release(0);
    __syncwarp();
    if (lane == 0) mbar_arrive(my_ostg);
    uint32_t pending = 0;

    int n = 0;
    auto finish_sums = [&]() {
      float s0, s1;
      sums_get(sum_addr, s0, s1);
      inv0 = rcp(s0); inv1 = rcp(s1);
      l0 = l1 = 0.f;
      asm volatile("" : "+f"(inv0), "+f"(inv1)::"memory");
    };
    auto check_sums = [&](int t) { check_inv(inv0, inv1, redo, 1u << (t & 31)); };

    int exit_n = -1;
#pragma unroll 1
    while (true) {
#pragma unroll 1
      while (true) {
        const int j = n & 7;
        softmax_block(S, P0, l0, l1);
        asm volatile("" : "+f"(l0), "+f"(l1)::"memory");
        if (j != 0) {
          wg_wait<0>();
          release(vp);
          turn_wait();
          wg_fence();
          issue_qk3(S, Q, kd);
          wg_commit();
          issue_pv<true>(O, P0, vd);
          wg_commit();
          turn_pass();
          advance();
          if (j == 6) {
            mbar_wait(my_qfull, ((n >> 3) + 1) & 1);
            wg_wait<3>();
            load_q<0, 4>(Q, lane_addr);
            wg_wait<2>();
            load_q<4, 8>(Q, lane_addr);
          }
          wg_wait<1>();
          fence_regs(S);
          fence_regs(P1);
        } else {
          wg_wait<0>();
          fence_regs(O);
          fence_regs(P1);
          if (pending) {
            release(vp);
            epilogue_part<0, ESPLIT>(O, inv0, inv1, lane_addr);
          }
          turn_wait();
          wg_fence();
          issue_qk32(S, Q, kd);
          wg_commit();
          if (pending) {
            epilogue_part<ESPLIT, 12>(O, inv0, inv1, lane_addr);
            epilogue_done(my_ostg, lane);
          }
          wg_fence();
          issue_pv<false>(O, P0, vd);
          wg_commit();
          turn_pass();
          advance();
          check_sums((n >> 3) - 1);
          exit_n = ((tails & 2) || n + 8 == nblocks) ? n + 6 : -1;
          tails >>= 1;
          stay = sched.list[first_round + (n >> 3) + 1] & 0x4000;
          asm volatile("" : "+r"(exit_n), "+r"(tails), "+r"(redo), "+r"(stay));
          wg_wait<1>();
          fence_regs(S);
          pending = true;
        }
        release(kp);
        softmax_block(S, P1, l0, l1);
        asm volatile("" : "+f"(l0), "+f"(l1)::"memory");
        if (j == 6) {
          load_q<8, 12>(Q, lane_addr);
          sums_put(sum_addr, l0, l1);
          wg_wait<0>();
          release(vp);
          { const uint32_t k = ks; ks = stay ? vs : ks; vs = stay ? k : vs; ord = stay ? ring_stay(ord) : ord; }
          kd = kd0 + ks * (SLOT / 128); vd = vd0 + vs * (SLOT / 128);
          asm volatile("" : "+r"(ks), "+r"(vs), "+r"(kd), "+r"(vd), "+r"(ord));
          scale_q(Q);
          if (n == exit_n) {
            turn_wait();
            wg_fence();
            issue_pv<true>(O, P1, vd);
            wg_commit();
            break;
          }
          asm volatile("" ::: "memory");
          turn_wait();
          wg_fence();
          issue_qk32(S, Q, kd);
          wg_commit();
          issue_pv<true>(O, P1, vd);
          wg_commit();
          turn_pass();
          advance();
          if (pending) finish_sums();
          wg_wait<1>();
        } else {
          wg_wait<0>();
          release(vp);
          turn_wait();
          wg_fence();
          issue_qk(S, Q, kd);
          wg_commit();
          issue_pv<true>(O, P1, vd);
          wg_commit();
          turn_pass();
          advance();
          wg_wait<1>();
        }
        fence_regs(S);
        fence_regs(P0);
        release(kp);
        n += 2;
      }
      if (n + 2 == nblocks) {
        if (w == 0) turn_pass();
        finish_sums();
        check_sums(n >> 3);
        wg_wait<0>();
        fence_regs(O);
        release(vs);
        epilogue_part<0, 12>(O, inv0, inv1, lane_addr);
        epilogue_done(my_ostg, lane);
        break;
      }
      const int t = n >> 3;
      const uint32_t qt = sbase + OFF_QT, pt = sbase + OFF_PT, red = sbase + OFF_RED;
      const uint32_t tl = ((lane & 7) + (lane >> 4) * 8) * 128 + (((warp * 2 + ((lane >> 3) & 1)) ^ (lane & 7)) << 4);
      const bool tlast = n + 10 == nblocks;
      float lt[4] = {0.f, 0.f, 0.f, 0.f};
      float ST[8], OT[3][8];
      wg_fence();
      issue_qkT(ST, kd, qt);
      wg_commit();
      turn_pass();
      finish_sums();
      check_sums(t);
      wg_wait<0>();
      fence_regs(ST);
      fence_regs(O);
      release(ks);
      release(vs);
      advance();
      epilogue_part<0, NT_SPLIT>(O, inv0, inv1, lane_addr);
      if (NT_SPLIT == 12) epilogue_done(my_ostg, lane);
      tail_softmax(ST, lt, pt + tl);
      auto tail_step = [&](auto first_c, int jj) {
        constexpr bool FIRST = decltype(first_c)::value;
        asm volatile("fence.proxy.async.shared::cta;" ::: "memory");
        turn_wait();
        wg_fence();
        issue_qkT(ST, kd, qt);
        wg_commit();
        issue_pvT<!FIRST>(OT, vd, pt + (jj & 1) * 2048);
        wg_commit();
        turn_pass();
        advance();
        wg_wait<1>();
        fence_regs(ST);
        release(kp);
        tail_softmax(ST, lt, pt + (~jj & 1) * 2048 + tl);
        wg_wait<0>();
        fence_regs(OT[0]); fence_regs(OT[1]); fence_regs(OT[2]);
        release(vp);
      };
      tail_step(Bool<true>(), 0);
      if (NT_SPLIT < 12) {
        epilogue_part<NT_SPLIT, 12>(O, inv0, inv1, lane_addr);
        epilogue_done(my_ostg, lane);
      }
#pragma unroll 1
      for (int jj = 1; jj < 7; jj++) tail_step(Bool<false>(), jj);
      mbar_wait(my_qfull, t & 1);
      load_q(Q, lane_addr);
      scale_q(Q);
      tail_reduce(lt, red, warp, lane);
#pragma unroll
      for (int i = 0; i < 4; i++) lt[i] = rcp(lt[i]);
      check_inv(lt[0], lt[1], redo, 1u << ((t + 1) & 31));
      check_inv(lt[2], lt[3], redo, 1u << ((t + 1) & 31));
      inv0 = inv1 = 1.f;
      asm volatile("fence.proxy.async.shared::cta;" ::: "memory");
      turn_wait();
      wg_fence();
      issue_pvT<true>(OT, vd, pt + 2048);
      wg_commit();
      issue_qk(S, Q, kd);
      wg_commit();
      if (!tlast) turn_pass();
      wg_wait<1>();
      fence_regs(OT[0]); fence_regs(OT[1]); fence_regs(OT[2]);
      release(vs);
#pragma unroll
      for (int b = 0; b < 3; b++)
        stsm_x4_trans(s_qo + SLOT + b * SLAB + tl + (lane >> 4) * (RGRP - 1024),
                      pack_bf16(OT[b][0] * lt[0], OT[b][1] * lt[1]), pack_bf16(OT[b][2] * lt[0], OT[b][3] * lt[1]),
                      pack_bf16(OT[b][4] * lt[2], OT[b][5] * lt[3]), pack_bf16(OT[b][6] * lt[2], OT[b][7] * lt[3]));
      epilogue_done(my_ostg, lane);
      wg_wait<0>();
      fence_regs(S);
      if (tlast) break;
      release(ks);
      advance();
#pragma unroll
      for (int i = 0; i < 96; i++) O[i] = 0.f;
      pending = false;
      n += 10;
      tails >>= 1;
    }
    if (redo) asm volatile("red.shared.or.b32 [%0], %1;" ::"r"(s_redo + 4 * w), "r"(redo) : "memory");
    asm volatile("bar.sync 4, 256;" ::: "memory");
    asm volatile("ld.shared.u32 %0, [%1];" : "=r"(redo) : "r"(s_redo + 4 * w) : "memory");
    redo = __shfl_sync(0xffffffffu, redo, 0);
    if (redo) {
      mbar_wait_sleep(bar_redo + 8 * w, 0);
      asm volatile("bar.sync %0, 128;" ::"r"(5 + w) : "memory");
      uint32_t phase = 1;
      get_rounds(first_round, nrounds);
      uint32_t rank;
      asm volatile("mov.u32 %0, %%cluster_ctarank;" : "=r"(rank));
#pragma unroll 1
      for (int t = 0; t < nrounds; t++) {
        if (!(redo >> (t & 31) & 1)) continue;
        const Round r = decode_round(sched.list[first_round + t], rank);
        redo_tile(&tmQ, &tmK, &tmV, &tmO, r.head, r.qrow + w * 64, s_qo + w * SLOT, s_kv + 2 * w * SLOT, lane_addr, bar_redo + 8 * w, phase, 5 + w);
      }
    }
  }
}

typedef CUresult (*EncodeFn)(CUtensorMap*, CUtensorMapDataType, cuuint32_t, void*, const cuuint64_t*, const cuuint64_t*,
                             const cuuint32_t*, const cuuint32_t*, CUtensorMapInterleave, CUtensorMapSwizzle,
                             CUtensorMapL2promotion, CUtensorMapFloatOOBfill);

void make_map(EncodeFn fn, CUtensorMap* tm, const void* ptr, int rows, int box_rows) {
  cuuint64_t dims[5] = {64, 8, 3, (cuuint64_t)rows / 8, (cuuint64_t)NHEADS};
  cuuint64_t strides[4] = {HD * 2, 128, 8 * HD * 2, (cuuint64_t)rows * HD * 2};
  cuuint32_t box[5] = {64, 8, 3, (cuuint32_t)box_rows / 8, 1};
  cuuint32_t estr[5] = {1, 1, 1, 1, 1};
  fn(tm, CU_TENSOR_MAP_DATA_TYPE_BFLOAT16, 5, const_cast<void*>(ptr), dims, strides, box, estr,
     CU_TENSOR_MAP_INTERLEAVE_NONE, CU_TENSOR_MAP_SWIZZLE_128B, CU_TENSOR_MAP_L2_PROMOTION_L2_128B, CU_TENSOR_MAP_FLOAT_OOB_FILL_NONE);
}

#define STAGGER 250
#define COST_N 12690
#define COST_T 10800
#define COST_TN 12720
#define TAIL_LATE 36
#define TAIL_MAX 60
#define HEAVY_STEP 3
const uint16_t DELAY66[66] = {
  0, 86, 950, 1122, 259, 690, 604, 431, 172, 345, 777, 518, 1900, 1381, 2245, 1295, 1209, 2159, 863, 1468, 3109, 1554,
  2331, 2677, 1727, 3281, 1036, 1640, 3800, 4318, 3195, 3022, 2504, 3540, 3368, 3886, 2936, 2590, 2418, 3713, 2072, 3454, 2763, 4145,
  4231, 2850, 4490, 3627, 5354, 4404, 4922, 4577, 4836, 5095, 3972, 5440, 4663, 5181, 5268, 5009, 5527, 4059, 5613, 4750, 1813, 1986,
};
const uint16_t LIST66[66][28] = {
  {0x0000,0x0020,0xc620,0x0042,0xc642,0x005d,0x445d,0x0094,0x4294,0x00b6,0xc6b6,0x00dc,0xc6dc,0x00f9,0x42f9,0x012a,0x452a,0x014a,0xc74a,0x0364,0x018a,0xc78a,0x01ac,0xc7ac,0x05b3,0x01db,0x45db,0x87ea},
  {0x0200,0xc600,0x0025,0x4425,0x004f,0x444f,0x0084,0xc684,0x0494,0x02b6,0x44b6,0x00d5,0x42d5,0x0108,0xc708,0x0119,0x4319,0x873a,0x054a,0x8764,0x037a,0x058a,0x03ac,0x87b2,0x05be,0x87de,0x03f4,0xc7f4},
  {0x0400,0x0021,0x0036,0x4236,0x005c,0xc65c,0x0075,0x4275,0x009f,0x429f,0x00d0,0xc6d0,0x04d5,0x02f6,0x0308,0x0318,0x0519,0x014b,0x434b,0x017a,0x457a,0x019e,0x459e,0x01bf,0x43bf,0x01ea,0x43ea,0xffff},
  {0x0001,0x0024,0x4424,0x004e,0x444e,0x0274,0xc674,0x0095,0x4295,0x00b7,0x42b7,0x00dd,0x42dd,0x0109,0x4309,0x8718,0x013a,0x453a,0x0164,0x4564,0x017d,0x457d,0x01ad,0x43ad,0x01de,0x01eb,0x43eb,0xffff},
  {0x0004,0xc604,0x0229,0x0044,0xc644,0x0264,0x0265,0x008d,0x448d,0x02ad,0x00c6,0xc6c6,0x02ee,0x02ef,0x0111,0x4511,0x8730,0x014c,0xc74c,0x036e,0x036f,0x0195,0x4595,0x87b8,0x01d2,0xc7d2,0x03f6,0xc7f6},
  {0x000e,0xc60e,0x0227,0x0046,0xc646,0x0268,0x0269,0x008b,0x448b,0x02a9,0x00c8,0xc6c8,0x02ea,0x02eb,0x010f,0x450f,0x872e,0x014e,0xc74e,0x0370,0x0371,0x0193,0x4593,0x87b4,0x01d4,0xc7d4,0x03f0,0xc7f0},
  {0x000c,0xc60c,0x002d,0x442d,0x024b,0x0072,0xc672,0x028e,0x028f,0x00b1,0x44b1,0x86ce,0x00f2,0x44f2,0x0312,0x0313,0x0135,0x4535,0x8756,0x0178,0xc778,0x0396,0x0397,0x87b0,0x05b1,0x87d8,0x03e1,0x87fc},
  {0x0008,0x0009,0x4409,0x8632,0x0058,0xc658,0x0278,0x0279,0x0099,0x4499,0x02b9,0x00de,0xc6de,0x02fa,0x02fb,0x011f,0x451f,0x873c,0x0160,0xc760,0x0382,0x0383,0x879c,0x01c0,0xc7c0,0x03e2,0x45e2,0x87fe},
  {0x0002,0xc602,0x0225,0x0242,0x4442,0x006e,0xc66e,0x0284,0x8694,0x00af,0x44af,0x02dc,0x44dc,0x86f6,0x04f9,0x032a,0xc72a,0x033a,0x0159,0x4559,0x877a,0x038a,0x879e,0x05ac,0x03be,0x87da,0x03db,0x05eb},
  {0x0006,0xc606,0x002b,0x442b,0x0250,0x0070,0xc670,0x0290,0x0291,0x00ab,0x44ab,0x02cd,0x00f4,0xc6f4,0x0316,0x0317,0x0133,0x4533,0x8752,0x0176,0xc776,0x039a,0x459a,0x87ba,0x05bb,0x87d6,0x01f8,0xc7f8},
  {0x0010,0x0022,0xc622,0x0248,0xc648,0x0266,0x0267,0x0089,0x4489,0x02a7,0x00ca,0xc6ca,0x02e6,0x02e7,0x010b,0x450b,0x872c,0x0150,0xc750,0x0366,0x0367,0x8790,0x01ab,0x87b6,0x05b7,0x87cc,0x03ec,0xc7ec},
  {0x000a,0x000b,0x0234,0xc634,0x005a,0xc65a,0x027c,0x027d,0x009b,0x449b,0x02bb,0x00e0,0xc6e0,0x0302,0x0303,0x0121,0x4521,0x033f,0x0162,0xc762,0x018c,0xc78c,0x01ae,0xc7ae,0x03d0,0xc7d0,0x01fa,0xc7fa},
  {0x0204,0x0028,0xc628,0x0244,0x4444,0x0065,0x4465,0x028d,0x00ac,0xc6ac,0x02c6,0x44c6,0x00ef,0x44ef,0x0311,0x0130,0x4530,0x034c,0x034d,0x016f,0x456f,0x0395,0x01b9,0x43b9,0x03d2,0x05d3,0x05f7,0xffff},
  {0x020e,0x0026,0xc626,0x0246,0x4446,0x0069,0x4469,0x028b,0x00a8,0xc6a8,0x02c8,0x44c8,0x00eb,0x44eb,0x030f,0x012e,0x452e,0x014f,0x434f,0x0570,0x0192,0x4592,0x01b5,0x43b5,0x03d4,0x05d5,0x03f1,0xffff},
  {0x020c,0x002c,0x442c,0x024a,0xc64a,0x0272,0x4472,0x008f,0x448f,0x02b1,0x00cf,0x42cf,0x02f2,0x0112,0xc712,0x0134,0x4534,0x0157,0x4557,0x0179,0x4579,0x8796,0x01b0,0x43b0,0x01d8,0x43d8,0x01fc,0xffff},
  {0x0208,0xc608,0x0032,0x4432,0x0258,0x4458,0x0079,0x4479,0x0299,0x00b8,0xc6b8,0x02de,0x44de,0x00fb,0x44fb,0x031f,0x013c,0x453c,0x0360,0x0361,0x0183,0x4583,0x059c,0x03c0,0x05c1,0x03e3,0x03ff,0xffff},
  {0x0202,0x0220,0x4420,0x0436,0x025c,0x445c,0x026f,0x0485,0x049e,0x86ae,0x02d0,0x44d0,0x00f8,0xc6f8,0x0508,0x0123,0x4323,0x033b,0x0359,0x017b,0x437b,0x019f,0x439f,0x05b2,0x05bf,0x05da,0x05ea,0xffff},
  {0x0206,0x002a,0x442a,0x0051,0xc650,0x0270,0x4470,0x0091,0x4491,0x86aa,0x00cc,0x44cc,0x00f5,0x44f5,0x0516,0x0132,0xc732,0x0152,0x4552,0x0376,0x0377,0x019b,0x459b,0x03ba,0x01d7,0x01e7,0x45e7,0xffff},
  {0x0210,0xc610,0x0223,0x0048,0x4448,0x0067,0x4467,0x0289,0x00a6,0x44a6,0x00cb,0x44cb,0x04e6,0x010a,0x450a,0x012d,0x452d,0x0151,0x4551,0x8766,0x0190,0x4390,0x01b6,0x43b6,0x01cd,0x43cd,0x01ed,0xffff},
  {0x020a,0x020b,0x440b,0x0235,0x005b,0x445b,0x047c,0x009a,0xc69a,0x00ba,0xc6ba,0x02e0,0x44e0,0x0103,0x4503,0x0321,0x013e,0x453e,0x0163,0x4563,0x038c,0x058d,0x01af,0x45af,0x03d1,0x45d1,0x03fa,0xffff},
  {0x0404,0x0228,0x4428,0x0045,0x0064,0x4464,0x028c,0x448c,0x00ad,0x44ad,0x02c7,0x00ee,0xc6ee,0x0310,0xc710,0x0330,0x0331,0x014d,0x454d,0x056e,0x0394,0xc794,0x01b8,0x45b8,0x01d3,0x43d3,0x03f7,0xffff},
  {0x040e,0x0226,0x4426,0x0047,0x4447,0x0468,0x008a,0xc68a,0x02a8,0x44a8,0x00c9,0x44c9,0x04ea,0x010e,0xc70e,0x032e,0x032f,0x034e,0x054f,0x0171,0x4571,0x0393,0x03b4,0x05b5,0x05d4,0x01f0,0x45f0,0xffff},
  {0x040c,0x022c,0xc62c,0x004a,0x444a,0x0073,0x4473,0x048e,0x00b0,0xc6b0,0x00ce,0x44ce,0x00f3,0x42f3,0x0113,0x4513,0x0335,0x0357,0x0556,0x0578,0x0196,0x4596,0x01b1,0x43b1,0x03e0,0xc7e0,0x03fc,0xffff},
  {0x0408,0x0209,0x0033,0x4233,0x0059,0x0078,0x4478,0x0298,0xc698,0x02b8,0x44b8,0x00df,0x00fa,0x44fa,0x031e,0xc71e,0x013d,0x433d,0x0161,0x4561,0x8782,0x019c,0x439c,0x01c1,0x43c1,0x01e3,0x45e3,0xffff},
  {0x0402,0x0203,0x0037,0xc636,0x0443,0x026e,0x446e,0x0484,0x029e,0x049f,0x04b7,0x02d1,0x04dd,0x02f7,0x0122,0x4522,0x032b,0x0358,0xc758,0x0365,0x057b,0x038b,0x059f,0x05ad,0x03de,0x45de,0x03f5,0xffff},
  {0x0406,0x022a,0xc62a,0x0050,0x4450,0x0071,0x4471,0x8690,0x00aa,0x44aa,0x02cc,0xc6cc,0x02f4,0x44f4,0x0117,0x4517,0x0532,0x0352,0x0353,0x0177,0x4577,0x039b,0x01ba,0x45ba,0x03d7,0x03e7,0x03f8,0xffff},
  {0x0410,0x0222,0x4422,0x0049,0x4449,0x0466,0x0088,0xc688,0x02a6,0xc6a6,0x02ca,0x44ca,0x00e7,0x44e7,0x030b,0x012c,0x452c,0x0350,0x0351,0x0167,0x4567,0x0590,0x01b7,0x43b7,0x03cc,0x01ec,0x45ec,0xffff},
  {0x040a,0xc60a,0x0034,0x4434,0x025a,0x445a,0x007d,0x447d,0x029b,0x02ba,0x44ba,0x00e1,0x44e1,0x0502,0x0120,0x4520,0x013f,0x453f,0x0363,0x0572,0x058c,0x058f,0x05ae,0x01d0,0x45d0,0x87e4,0x05fa,0xffff},
  {0x0205,0x0029,0x4429,0x0245,0x4445,0x8664,0x008c,0xc68c,0x02ac,0x44ac,0x00c7,0x44c7,0x04ee,0x0110,0x4510,0x0131,0x4531,0x054c,0x016e,0xc76e,0x0194,0x4594,0x03b8,0x05b9,0x05d2,0x01f6,0x45f6,0xffff},
  {0x020f,0x0027,0x4427,0x0247,0x0068,0xc668,0x028a,0x448a,0x00a9,0x44a9,0x02c9,0x00ea,0xc6ea,0x030e,0x450e,0x012f,0x452f,0x054e,0x0170,0xc770,0x0392,0xc792,0x01b4,0x45b4,0x01d5,0x43d5,0x01f1,0xffff},
  {0x020d,0x440d,0x022d,0x004b,0x444b,0x0273,0x008e,0xc68e,0x02b0,0x44b0,0x02ce,0x04cf,0x86f2,0x04f3,0x0512,0x0334,0xc734,0x0156,0x4356,0x0378,0x0379,0x0197,0x4597,0x05b0,0x01e0,0x45e0,0x05fc,0xffff},
  {0x0016,0x4416,0x0232,0x0433,0x0259,0x4459,0x8678,0x0098,0x4498,0x00b9,0x44b9,0x02df,0x44df,0x86fa,0x011e,0x451e,0x033c,0x053d,0x0560,0x0182,0x4582,0x019d,0x439d,0x05c0,0x01e2,0xc7e2,0x01ff,0xffff},
  {0x0003,0x4403,0x0237,0x4437,0x024f,0x006f,0x446f,0x009e,0xc69e,0x02af,0x02d4,0x44d4,0x02f8,0x44f8,0x0322,0xc722,0x0523,0x0158,0x4558,0x037c,0xc77c,0x037d,0x01b2,0x43b2,0x01da,0x43da,0x01f5,0xffff},
  {0x0207,0x4407,0x022b,0x0251,0x4451,0x0271,0x0090,0x4490,0x02aa,0x02ab,0x00cd,0x44cd,0x02f5,0x0116,0xc716,0x0332,0x0333,0x0153,0x4553,0x0576,0x019a,0xc79a,0x01bb,0x43bb,0x05d7,0x87e6,0x05f8,0xffff},
  {0x0011,0x0023,0x4423,0x0249,0x0066,0xc666,0x0288,0x4488,0x00a7,0x44a7,0x02cb,0x00e6,0xc6e6,0x030a,0xc70a,0x032c,0x032d,0x0550,0x0166,0x4566,0x0191,0x4391,0x03ab,0x01cc,0x45cc,0x05cd,0x03ed,0xffff},
  {0x0212,0x4412,0x0035,0x4435,0x025b,0x007c,0xc67c,0x029a,0x449a,0x00bb,0x44bb,0x02e1,0x0102,0xc702,0x0320,0xc720,0x033e,0xc73e,0x0362,0x4562,0x018d,0x438d,0x03ae,0x03af,0x01d1,0x01e4,0x45e4,0xffff},
  {0x0005,0x4405,0x003e,0xc63e,0x005e,0x445e,0x0081,0x4281,0x00a3,0x44a3,0x02c1,0x00e3,0x44e3,0x0504,0x0126,0xc726,0x0144,0x4544,0x0169,0x4569,0x0586,0x01a8,0x45a8,0x03ca,0xc7ca,0x01ee,0x01f7,0xffff},
  {0x000f,0x440f,0x003c,0x443c,0x0260,0xc660,0x007f,0x427f,0x00a1,0x44a1,0x02c3,0x00e4,0xc6e4,0x00ff,0x42ff,0x0125,0x4525,0x0347,0x016a,0x456a,0x0384,0x0585,0x03a3,0x45a3,0x05c7,0x87e8,0x03e9,0xffff},
  {0x000d,0x0015,0x0238,0xc638,0x0057,0x4257,0x007b,0x447b,0x0296,0x00be,0x44be,0x02da,0x04db,0x02fd,0x011d,0xc71c,0x0142,0x4542,0x035c,0x055d,0x0381,0x4581,0x05a1,0x03c9,0xc7c8,0x03d9,0x01fd,0xffff},
  {0x0216,0xc616,0x0231,0x0052,0x4452,0x006d,0x446d,0x0293,0x00b4,0x44b4,0x00d7,0x44d7,0x00f1,0x44f1,0x0315,0x0139,0x4539,0x035b,0x0174,0xc774,0x0398,0xc798,0x01bc,0x45bc,0x01dd,0x45dd,0x05ff,0xffff},
  {0x0007,0x0019,0x003a,0xc63a,0x0254,0x0255,0x0077,0x4477,0x029d,0x00bc,0x44bc,0x86d8,0x02d9,0x0101,0x011a,0x451a,0x0140,0x4540,0x015f,0x455f,0x037f,0x03a4,0xc7a4,0x03c2,0x45c2,0x01e6,0x45e6,0xffff},
  {0x0211,0x4411,0x0040,0xc640,0x0062,0x4462,0x0083,0x4283,0x00a5,0x44a5,0x02c4,0x00e8,0xc6e8,0x0306,0x0307,0x0129,0x4529,0x0348,0x016c,0x456c,0x0588,0x01aa,0x45aa,0x01cf,0x45cf,0x03f3,0xc7f2,0xffff},
  {0x0012,0xc612,0x022f,0x004c,0x444c,0x026a,0x0086,0x4486,0x00b2,0xc6b2,0x00d2,0x44d2,0x02ec,0x010c,0x450c,0x0336,0xc736,0x0154,0x4554,0x0372,0x018e,0x458e,0x01a7,0x43a7,0x01c5,0x01e5,0x45e5,0xffff},
  {0x001a,0x001b,0x441b,0x023f,0x005f,0x445f,0x0480,0x02a2,0xc6a2,0x02c0,0xc6c0,0x00e2,0x44e2,0x0304,0x0505,0x0327,0x0344,0xc744,0x0168,0x4568,0x0386,0x0587,0x03a9,0x45a9,0x05cb,0x03ef,0xc7ee,0xffff},
  {0x001c,0x001d,0x003d,0x423d,0x0061,0x007e,0x447e,0x02a0,0xc6a0,0x00c3,0x44c3,0x02e5,0x44e5,0x86fe,0x0124,0x4524,0x0147,0x4547,0x036b,0x0184,0xc784,0x0385,0x01a3,0x03c6,0xc7c6,0x01e8,0x45e8,0xffff},
  {0x0014,0xc614,0x0038,0x4438,0x0256,0x0457,0x027b,0x0096,0x4496,0x00bf,0x44bf,0x04da,0x00fc,0xc6fc,0x011c,0x431c,0x0143,0x4543,0x055c,0x0180,0x4580,0x03a0,0xc7a0,0x01c8,0x45c8,0x01e1,0x45e1,0xffff},
  {0x0017,0x0030,0xc630,0x0252,0xc652,0x026c,0x026d,0x0093,0x4493,0x02b4,0x00d6,0x44d6,0x04f0,0x0114,0x4514,0x0338,0xc738,0x015a,0x455a,0x0374,0x0198,0x4598,0x03bc,0xc7bc,0x01dc,0x43dc,0x01fe,0xffff},
  {0x0018,0x0219,0x003b,0x0054,0x4454,0x0276,0xc676,0x009c,0x449c,0x00bd,0x00d8,0x42d8,0x0100,0x4500,0x011b,0x451b,0x0341,0x015e,0xc75e,0x037e,0xc77e,0x01a4,0x45a4,0x01c3,0x45c3,0x03e6,0x05f9,0xffff},
  {0x001e,0x001f,0x0041,0x4241,0x0063,0x0082,0x4482,0x02a4,0xc6a4,0x00c5,0xc6c4,0x02e8,0x44e8,0x0107,0x4507,0x0329,0x0149,0xc748,0x016d,0x456d,0x0189,0x4389,0x87aa,0x05b6,0x03ce,0x01f2,0x45f2,0xffff},
  {0x0013,0x002e,0xc62e,0x004d,0x424d,0x006b,0x426b,0x0087,0x00b3,0x42b3,0x00d3,0x44d3,0x86ec,0x04ed,0x870c,0x0136,0x4536,0x0155,0x4355,0x0173,0x4573,0x01a6,0x45a6,0x03c4,0xc7c4,0x03e4,0x01fb,0xffff},
  {0x021a,0xc61a,0x023e,0x443e,0x025e,0xc65e,0x0280,0x0481,0x02a3,0x00c0,0x44c0,0x02e2,0xc6e2,0x0105,0x4305,0x0127,0x4527,0x0345,0x0368,0xc768,0x0187,0x4387,0x01a9,0x01ca,0x45ca,0x03ee,0x45ee,0xffff},
  {0x021c,0x021d,0x441d,0x043d,0x0261,0x4461,0x867e,0x00a0,0x44a0,0x02c2,0xc6c2,0x02e4,0x44e4,0x02fe,0x04ff,0x0325,0x0346,0xc746,0x016b,0x456b,0x0584,0x03a2,0xc7a2,0x01c6,0x45c6,0x01e9,0x45e9,0xffff},
  {0x0214,0x0215,0x0039,0x0056,0x4456,0x027a,0xc67a,0x0097,0xc696,0x02be,0xc6be,0x00db,0x42db,0x00fd,0x44fd,0x051c,0x0342,0xc742,0x015d,0x435d,0x0181,0x01a0,0x45a0,0x03c8,0x01d9,0x45d9,0x03fd,0xffff},
  {0x0217,0x0230,0x4430,0x0053,0x006c,0x446c,0x0292,0xc692,0x00b5,0xc6b4,0x02d6,0xc6d6,0x02f0,0x02f1,0x0115,0x4515,0x0339,0x015b,0x455b,0x0574,0x0575,0x0399,0x059d,0x03bd,0x03dd,0xc7dc,0x03fe,0xffff},
  {0x0218,0xc618,0x023a,0x443a,0x0055,0x4455,0x0277,0x009d,0x449d,0x02bd,0x44bd,0x04d8,0x0300,0xc700,0x031a,0xc71a,0x0340,0xc740,0x035e,0x035f,0x017f,0x457f,0x03a5,0x01c2,0x01d6,0x43d6,0x01f9,0xffff},
  {0x021e,0xc61e,0x0240,0x4440,0x0262,0xc662,0x0282,0x0483,0x02a5,0x00c4,0x44c4,0x00e9,0x44e9,0x0506,0x0128,0x4528,0x0349,0x4549,0x036d,0x0188,0xc788,0x0589,0x05ab,0x03cf,0xc7ce,0x03f2,0x05ed,0xffff},
  {0x0213,0x022e,0x442e,0x024c,0x006a,0xc66a,0x0286,0xc686,0x02b2,0x44b2,0x02d2,0xc6d2,0x00ed,0x42ed,0x010d,0x450d,0x0337,0x0354,0x0555,0x0373,0x038e,0xc78e,0x03a6,0x01c4,0x45c4,0x03e5,0x03fb,0xffff},
  {0x041a,0x021b,0x003f,0x443f,0x025f,0x0080,0xc680,0x00a2,0x44a2,0x00c1,0x44c1,0x02e3,0x0104,0xc704,0x0326,0x4526,0x0145,0x4545,0x0369,0x0186,0xc786,0x03a8,0xc7a8,0x01cb,0x43cb,0x01ef,0x45ef,0xffff},
  {0x041c,0xc61c,0x023c,0xc63c,0x0060,0x4460,0x027e,0x047f,0x02a1,0x00c2,0x44c2,0x00e5,0x00fe,0x44fe,0x0324,0xc724,0x0146,0x4546,0x036a,0xc76a,0x0185,0x01a2,0x45a2,0x01c7,0x43c7,0x03e8,0x05f1,0xffff},
  {0x0414,0x0415,0x0239,0x4439,0x8656,0x007a,0x447a,0x0297,0x4497,0x02bf,0x00da,0xc6da,0x02fc,0x44fc,0x031d,0x451d,0x0343,0x015c,0xc75c,0x0380,0xc780,0x01a1,0x43a1,0x01c9,0x45c9,0x05d8,0x05fd,0xffff},
  {0x0417,0x0031,0x4431,0x0253,0x4453,0x866c,0x0092,0x4492,0x02b5,0x44b5,0x02d7,0x00f0,0xc6f0,0x0314,0xc714,0x0138,0x4538,0x035a,0xc75a,0x0175,0x4375,0x0199,0x4599,0x01bd,0x45bd,0x05dc,0x05fe,0xffff},
  {0x0418,0x0419,0x023b,0x443b,0x8654,0x0076,0x4476,0x029c,0xc69c,0x02bc,0xc6bc,0x00d9,0x44d9,0x0301,0x4501,0x031b,0x0141,0x4541,0x055e,0x017e,0x457e,0x01a5,0x45a5,0x03c3,0xc7c2,0x05d6,0x03f9,0xffff},
  {0x041e,0x021f,0x441f,0x0441,0x0263,0x4463,0x8682,0x00a4,0x44a4,0x02c5,0x44c5,0x02e9,0x0106,0xc706,0x0328,0xc728,0x0148,0x4548,0x036c,0xc76c,0x0388,0x0591,0x03aa,0x01ce,0x45ce,0x01f3,0x45f3,0xffff},
  {0x0413,0x002f,0x442f,0x864c,0x044d,0x046a,0x046b,0x0287,0x4487,0x04b3,0x02d3,0x00ec,0x44ec,0x030c,0x030d,0x0137,0x4537,0x8754,0x0172,0xc772,0x018f,0x438f,0x87a6,0x05a7,0x03c5,0x45c5,0x05fb,0xffff},
  {0x0201,0x0224,0xc624,0x0043,0x4243,0x0074,0x4474,0x0475,0x0495,0x02ae,0x00d1,0x44d1,0x00f7,0x44f7,0x0509,0x012b,0x452b,0x034a,0x0165,0x4565,0x018b,0x458b,0x01be,0xc7be,0x01df,0x01f4,0x45f4,0xffff},
  {0x0401,0x0221,0x4421,0x024e,0xc64e,0x025d,0x0085,0x4285,0x00ae,0x44ae,0x00d4,0xc6d4,0x00f6,0x44f6,0x0118,0x4518,0x013b,0x453b,0x054b,0x017c,0x457c,0x039e,0x01b3,0x43b3,0x03df,0x45df,0x05f5,0xffff},
};

void make_schedule(Schedule& s, int nclusters) {
  static uint16_t lists[MAX_CLUSTERS][NROUNDS];
  int cnt[MAX_CLUSTERS] = {0}, len[MAX_CLUSTERS], ntail[MAX_CLUSTERS] = {0}, quota[MAX_CLUSTERS] = {0};
  long long busy[MAX_CLUSTERS], fin[MAX_CLUSTERS];
  const int ntails = NROUNDS / 7, base = NROUNDS / nclusters, nheavy = NROUNDS % nclusters;
  const int step = nheavy * HEAVY_STEP <= nclusters ? HEAVY_STEP : 1;
  for (int c = 0; c < nclusters; c++) {
    len[c] = base + (c % step == 0 && c / step < nheavy);
    busy[c] = c / 3 * STAGGER;
    fin[c] = busy[c] + (long long)len[c] * COST_N;
  }
  for (int k = 0; k < ntails; k++) {
    int c = -1;
    for (int i = 0; i < nclusters; i++)
      if (quota[i] < len[i] / 2 && (c < 0 || fin[i] > fin[c])) c = i;
    quota[c]++;
    fin[c] -= 2 * COST_N - COST_T - COST_TN;
  }
  int gn = 0, gt = 3;
  for (int k = 0; k < NROUNDS; k++) {
    int c = -1;
    for (int i = 0; i < nclusters; i++)
      if (cnt[i] < len[i] && (c < 0 || busy[i] < busy[c])) c = i;
    const bool after_tail = cnt[c] > 0 && (lists[c][cnt[c] - 1] & 0x8000);
    const bool may_t = cnt[c] > 0 && !after_tail;
    const int left = len[c] - cnt[c], q = quota[c] - ntail[c];
    const bool due = (long long)(gt / 7) * quota[c] * 8 >= (long long)(ntail[c] * 8 + (c * 5 & 7)) * ntails;
    bool tail = may_t && q > 0 && (2 * q > left || (gn - gt >= TAIL_LATE && due) || gn - gt >= TAIL_MAX);
    if (4 * quota[c] >= len[c]) {
      const int m = len[c] - 1, phase = c / step * 11 % m;
      tail = may_t && q > 0 && (2 * q > left || (cnt[c] * quota[c] + phase) / m > ntail[c]);
    }
    if (gt >= NROUNDS) tail = false;
    if (gn >= NROUNDS) tail = true;
    const int g = tail ? gt : gn;
    if (tail) { gt += 7; ntail[c]++; }
    else { gn++; if (gn % 7 == 3) gn++; }
    const bool form_t = tail && may_t;
    lists[c][cnt[c]++] = (uint16_t)(g | (form_t ? 0x8000 : 0));
    busy[c] += form_t ? COST_T : after_tail ? COST_TN : COST_N;
  }
  bool use_tail = true;
  for (int c = 0; c < nclusters; c++) if (cnt[c] > MAX_ROUNDS) use_tail = false;
  if (!use_tail) for (int c = 0; c < nclusters; c++) for (int i = 0; i < cnt[c]; i++) lists[c][i] &= 0x7fff;
  for (int c = 0; c < nclusters; c++)
    for (int i = 0; i < cnt[c]; i++) {
      const int g = lists[c][i] & 0x7ff, p = g / 7, r = g % 7;
      lists[c][i] = (uint16_t)((2 * p + (r > 3)) | (r & 3) << 9 | (lists[c][i] & 0x8000));
    }
  if (nclusters == 66)
    for (int c = 0; c < 66; c++)
      for (cnt[c] = 0; cnt[c] < 28 && LIST66[c][cnt[c]] != 0xffff; cnt[c]++) lists[c][cnt[c]] = LIST66[c][cnt[c]];
  const bool table = nclusters == 66;
  int pos = 0;
  for (int c = 0; c < nclusters; c++) {
    s.start[c] = (uint16_t)pos;
    s.first[c] = lists[c][0] | (uint32_t)(table ? DELAY66[c] : c / 3 * STAGGER) << 16;
    s.tails[c] = s.stays[c] = 0;
    for (int i = 0; i < cnt[c]; i++) {
      if (lists[c][i] & 0x8000) s.tails[c] |= 1u << i;
      if (lists[c][i] & 0x4000) s.stays[c] |= 1u << i;
      s.list[pos++] = lists[c][i];
    }
  }
  for (int c = nclusters; c <= MAX_CLUSTERS; c++) s.start[c] = (uint16_t)pos;
  s.list[NROUNDS] = 0;
}

}

extern "C" void kernel_launch(void* const* d_in, const int* in_sizes, int n_in, void* d_out, int out_size) {
  static EncodeFn encode = nullptr;
  static int nclusters = 0;
  static Schedule sched;
  if (!encode) {
    void* fn = nullptr;
    cudaDriverEntryPointQueryResult qr;
    cudaGetDriverEntryPoint("cuTensorMapEncodeTiled", &fn, cudaEnableDefault, &qr);
    encode = (EncodeFn)fn;
    int dev = 0, nsm = 0;
    cudaGetDevice(&dev);
    cudaDeviceGetAttribute(&nsm, cudaDevAttrMultiProcessorCount, dev);
    nclusters = nsm / 2 < MAX_CLUSTERS ? nsm / 2 : MAX_CLUSTERS;
    make_schedule(sched, nclusters);
    cudaFuncSetAttribute(attn_kernel, cudaFuncAttributeMaxDynamicSharedMemorySize, SMEM_BYTES);
  }
  CUtensorMap tmQ, tmQT, tmK, tmV, tmO;
  make_map(encode, &tmQ, d_in[0], SQ, 64);
  make_map(encode, &tmQT, d_in[0], SQ, 16);
  make_map(encode, &tmK, d_in[1], SK, 64);
  make_map(encode, &tmV, d_in[2], SK, 64);
  make_map(encode, &tmO, d_out, SQ, OROWS);
  attn_kernel<<<2 * nclusters, NTHREADS, SMEM_BYTES>>>(tmQ, tmQT, tmK, tmV, tmO, sched);
}
```
